```python
import torch

def _softmax(x, axis=-1):
    return torch.softmax(x, dim=axis)
def _gelu(x):
    return torch.nn.functional.gelu(x, approximate="tanh")
def _silu(x):
    return torch.nn.functional.silu(x)
def _sigmoid(x):
    return torch.sigmoid(x)
def _layernorm(x, axis=-1, eps=1e-5):
    m = x.mean(dim=axis, keepdim=True)
    v = x.var(dim=axis, keepdim=True, unbiased=False)
    return (x - m) / torch.sqrt(v + eps)
def _scatter_add(tgt, idx, src, axis=0):
    return tgt.clone().index_add_(axis, idx, src)
def _segment_sum(src, seg, n):
    out = torch.zeros((n,) + src.shape[1:], dtype=src.dtype)
    return out.index_add_(0, seg, src)
def _pad(x, pw):
    flat = tuple(v for pair in reversed(pw) for v in pair)
    return torch.nn.functional.pad(x, flat)

kernel_name = 'recurrent_scan__linear_attn_block__dense_activation_mish__prompt'

def setup_inputs():

    _w = (lambda a: (lambda t: t.to(torch.bfloat16) if t.is_floating_point() else t)(torch.as_tensor(a)))
    def _A_setup():
        B, S, D = 1, 2048, 512
        return {
            "x": _w((lambda *s: torch.randn(*s, dtype=torch.bfloat16) * 0.05)(B, S, D)),
            "wqkv": _w((lambda *s: torch.randn(*s, dtype=torch.bfloat16) * 0.2)(D, 3 * D)),
            "wo": _w((lambda *s: torch.randn(*s, dtype=torch.bfloat16) * 0.2)(D, D)),
        }
    _A_in = _A_setup()

    def _B_setup():
        B, S, D, F = 1, 2048, 512, 1792
        return {
            "x": _w((lambda *s: torch.randn(*s, dtype=torch.bfloat16) * 0.05)(B, S, D)),
            "w1": _w((lambda *s: torch.randn(*s, dtype=torch.bfloat16) * 0.8)(D, F) * (D ** -0.5)),
            "b1": _w((lambda *s: torch.randn(*s, dtype=torch.bfloat16) * 0.2)(F)),
            "w2": _w((lambda *s: torch.randn(*s, dtype=torch.bfloat16) * 0.1)(F, D) * (F ** -0.5)),
        }
    _B_in = _B_setup()

    return {
        "A_x": _A_in["x"],
        "A_wqkv": _A_in["wqkv"],
        "A_wo": _A_in["wo"],
        "B_x": _B_in["x"],
        "B_w1": _B_in["w1"],
        "B_b1": _B_in["b1"],
        "B_w2": _B_in["w2"],
    }

def reference(A_x, A_wqkv, A_wo, B_x, B_w1, B_b1, B_w2):
    def _A_ref(x, wqkv, wo):
        B, S, D = x.shape
        H = 32; Dh = D // H
        qkv = (lambda x, *d: x.permute(*d))((x @ wqkv).reshape(B, S, 3, H, Dh), 2, 0, 3, 1, 4)
        q, k, v = qkv[0], qkv[1], qkv[2]
        phi = lambda t: torch.where(t > 0, t + 1, torch.exp(t)) + 1e-6
        pq, pk = phi(q), phi(k)
        kv = torch.einsum("bhsd,bhse->bhde", pk, v)
        z = torch.einsum("bhsd->bhd", pk)
        num = torch.einsum("bhqd,bhde->bhqe", pq, kv)
        den = torch.einsum("bhqd,bhd->bhq", pq, z)[..., None] + 1e-6
        o = num / den
        return (lambda x, *d: x.permute(*d))(o, 0, 2, 1, 3).reshape(B, S, D) @ wo

    def _B_ref(x, w1, b1, w2):
        h = torch.einsum("bsd,df->bsf", x, w1) + b1
        sp = torch.log1p(torch.exp(-torch.abs(h))) + torch.where(h > 0, h, torch.zeros_like(h))
        act = h * torch.tanh(sp)
        return torch.einsum("bsf,fd->bsd", act, w2)

    x = A_x
    xn = _layernorm(x, axis=-1)
    s = _A_ref(xn, A_wqkv, A_wo)
    g = _silu(_B_ref(xn, B_w1, B_b1, B_w2))
    return x + s * g
```

```cpp
#include <cuda_runtime.h>
#include <cuda_bf16.h>
#include <cuda.h>
#include <stdint.h>

namespace {

constexpr int SEQ = 2048, DM = 512, FF = 1792;
constexpr int NCTA = 128;
constexpr int NSLOT = 5;
constexpr int SLOT_BYTES = 16384;
constexpr int OFF_D = 0;
constexpr int OFF_RING = 131072;
constexpr int OFF_MISC = OFF_RING + NSLOT * SLOT_BYTES;
constexpr int OFF_BAR = OFF_MISC;
constexpr int OFF_EPOCH = OFF_MISC + 120;
constexpr int OFF_RSTD = OFF_MISC + 128;
constexpr int OFF_B1 = OFF_MISC + 640;
constexpr int OFF_KVRED = OFF_MISC + 1536;
constexpr int OFF_KVT = OFF_MISC + 5888;
constexpr int OFF_ZB = OFF_MISC + 7936;
constexpr int SMEM_USED = OFF_MISC + 8192;
constexpr int SMEM_ALLOC = SMEM_USED + 1024;

constexpr int BAR_FULL = 0, BAR_EMPTY = NSLOT, BAR_STATS = 2 * NSLOT, BAR_KVPART = 2 * NSLOT + 1, BAR_KVREADY = 2 * NSLOT + 2;

constexpr int NSTAGES = 56;

__device__ uint4 g_act[128 * 112 * 32];
__device__ uint4 g_o[128 * 32 * 32];
__device__ float4 g_yp[NCTA * 8 * 8 * 32];
__device__ float g_kvp[16 * 32 * 272];
__device__ unsigned g_cntA[128 * 2];
__device__ unsigned g_cntB[128 * 2];
__device__ unsigned g_cntO[128];
__device__ unsigned g_flagY[NCTA * 8];
__device__ unsigned g_cntKV[8];
__device__ unsigned g_done;

__device__ __forceinline__ uint32_t smem_u32(const void* p) { return (uint32_t)__cvta_generic_to_shared(p); }
__device__ __forceinline__ void mbar_init(uint32_t bar, uint32_t cnt) { asm volatile("mbarrier.init.shared::cta.b64 [%0], %1;" ::"r"(bar), "r"(cnt)); }
__device__ __forceinline__ void mbar_expect_tx(uint32_t bar, uint32_t bytes) { asm volatile("mbarrier.arrive.expect_tx.shared::cta.b64 _, [%0], %1;" ::"r"(bar), "r"(bytes) : "memory"); }
__device__ __forceinline__ void mbar_arrive(uint32_t bar) { asm volatile("mbarrier.arrive.shared::cta.b64 _, [%0];" ::"r"(bar) : "memory"); }
__device__ __forceinline__ void mbar_wait(uint32_t bar, uint32_t parity) {
  uint32_t done;
  asm volatile("{\n.reg .pred p;\nmbarrier.try_wait.parity.shared::cta.b64 p, [%1], %2;\nselp.u32 %0, 1, 0, p;\n}" : "=r"(done) : "r"(bar), "r"(parity) : "memory");
  if (!done) {
    uint32_t it = 0;
    do {
      asm volatile("{\n.reg .pred p;\nmbarrier.try_wait.parity.shared::cta.b64 p, [%1], %2;\nselp.u32 %0, 1, 0, p;\n}" : "=r"(done) : "r"(bar), "r"(parity) : "memory");
      if (++it > (1u << 24)) __trap();
    } while (!done);
  }
}
__device__ __forceinline__ void tma2d(uint32_t dst, const CUtensorMap* tm, int c0, int c1, uint32_t bar) {
  asm volatile("cp.async.bulk.tensor.2d.shared::cluster.global.mbarrier::complete_tx::bytes [%0], [%1, {%3, %4}], [%2];" ::"r"(dst), "l"(tm), "r"(bar), "r"(c0), "r"(c1) : "memory");
}
__device__ __forceinline__ void wg_fence() { asm volatile("wgmma.fence.sync.aligned;" ::: "memory"); }
__device__ __forceinline__ void wg_commit() { asm volatile("wgmma.commit_group.sync.aligned;" ::: "memory"); }
template <int N> __device__ __forceinline__ void wg_wait() { asm volatile("wgmma.wait_group.sync.aligned %0;" ::"n"(N) : "memory"); }
template <int N> __device__ __forceinline__ void fence_regs(float (&d)[N]) {
#pragma unroll
  for (int i = 0; i < N; i++) asm volatile("" : "+f"(d[i])::"memory");
}
__device__ __forceinline__ void fence_u4(uint4& v) { asm volatile("" : "+r"(v.x), "+r"(v.y), "+r"(v.z), "+r"(v.w)::"memory"); }
__device__ __forceinline__ void named_bar_sync(int id, int n) { asm volatile("bar.sync %0, %1;" ::"r"(id), "r"(n) : "memory"); }
__device__ __forceinline__ uint64_t make_desc(uint32_t addr, uint32_t lbo_bytes, uint32_t sbo_bytes) {
  return (uint64_t)((addr & 0x3FFFF) >> 4) | ((uint64_t)(lbo_bytes >> 4) << 16) | ((uint64_t)(sbo_bytes >> 4) << 32) | (1ull << 62);
}
__device__ __forceinline__ void mma16816(float (&c)[4], uint32_t a0, uint32_t a1, uint32_t a2, uint32_t a3, uint32_t b0, uint32_t b1) {
  asm volatile("mma.sync.aligned.m16n8k16.row.col.f32.bf16.bf16.f32 {%0,%1,%2,%3}, {%4,%5,%6,%7}, {%8,%9}, {%0,%1,%2,%3};"
               : "+f"(c[0]), "+f"(c[1]), "+f"(c[2]), "+f"(c[3]) : "r"(a0), "r"(a1), "r"(a2), "r"(a3), "r"(b0), "r"(b1));
}
__device__ __forceinline__ uint32_t movmat(uint32_t a) { uint32_t d; asm volatile("movmatrix.sync.aligned.m8n8.trans.b16 %0, %1;" : "=r"(d) : "r"(a)); return d; }
__device__ __forceinline__ uint32_t pack2(float lo, float hi) { uint32_t r; asm("cvt.rn.bf16x2.f32 %0, %1, %2;" : "=r"(r) : "f"(hi), "f"(lo)); return r; }
__device__ __forceinline__ float ex2(float x) { float r; asm("ex2.approx.ftz.f32 %0, %1;" : "=f"(r) : "f"(x)); return r; }
__device__ __forceinline__ float rcp(float x) { float r; asm("rcp.approx.ftz.f32 %0, %1;" : "=f"(r) : "f"(x)); return r; }
__device__ __forceinline__ float bf_lo(uint32_t v) { return __uint_as_float(v << 16); }
__device__ __forceinline__ float bf_hi(uint32_t v) { return __uint_as_float(v & 0xffff0000u); }
__device__ __forceinline__ uint32_t hsub2_bf16(uint32_t a, uint32_t b) {
  __nv_bfloat162 x = *reinterpret_cast<__nv_bfloat162*>(&a), y = *reinterpret_cast<__nv_bfloat162*>(&b);
  __nv_bfloat162 r = __hsub2(x, y);
  return *reinterpret_cast<uint32_t*>(&r);
}
__device__ __forceinline__ uint4 ldg_nc(const void* p) {
  uint4 v; asm volatile("ld.global.nc.L1::no_allocate.v4.u32 {%0,%1,%2,%3}, [%4];" : "=r"(v.x), "=r"(v.y), "=r"(v.z), "=r"(v.w) : "l"(p)); return v;
}
__device__ __forceinline__ uint4 ldg_cg(const void* p) {
  uint4 v; asm volatile("ld.global.cg.v4.u32 {%0,%1,%2,%3}, [%4];" : "=r"(v.x), "=r"(v.y), "=r"(v.z), "=r"(v.w) : "l"(p) : "memory"); return v;
}
__device__ __forceinline__ void stg_v4(void* p, uint32_t a, uint32_t b, uint32_t c, uint32_t d) {
  asm volatile("st.global.v4.u32 [%0], {%1,%2,%3,%4};" ::"l"(p), "r"(a), "r"(b), "r"(c), "r"(d) : "memory");
}
__device__ __forceinline__ void sts_v4(uint32_t addr, uint32_t a, uint32_t b, uint32_t c, uint32_t d) {
  asm volatile("st.shared.v4.u32 [%0], {%1,%2,%3,%4};" ::"r"(addr), "r"(a), "r"(b), "r"(c), "r"(d) : "memory");
}
__device__ __forceinline__ float lds_f32(uint32_t addr) { float v; asm volatile("ld.shared.f32 %0, [%1];" : "=f"(v) : "r"(addr) : "memory"); return v; }
__device__ __forceinline__ float2 lds_f32x2(uint32_t addr) { float2 v; asm volatile("ld.shared.v2.f32 {%0,%1}, [%2];" : "=f"(v.x), "=f"(v.y) : "r"(addr) : "memory"); return v; }
__device__ __forceinline__ uint32_t lds_u32(uint32_t addr) { uint32_t v; asm volatile("ld.shared.u32 %0, [%1];" : "=r"(v) : "r"(addr) : "memory"); return v; }
__device__ __forceinline__ void red_shared_add(uint32_t addr, float v) { asm volatile("red.shared.add.f32 [%0], %1;" ::"r"(addr), "f"(v) : "memory"); }
__device__ __forceinline__ void warp_publish(unsigned* cnt, int lane) {
  __syncwarp();
  if (lane == 0) {
    __threadfence();
    asm volatile("red.relaxed.gpu.global.add.u32 [%0], 1;" ::"l"(cnt) : "memory");
  }
}
__device__ __forceinline__ void warp_wait_ge(const unsigned* cnt, unsigned target, int lane) {
  if (lane == 0) {
    unsigned v; uint32_t it = 0;
    while (true) {
      asm volatile("ld.acquire.gpu.global.u32 %0, [%1];" : "=r"(v) : "l"(cnt) : "memory");
      if ((int)(v - target) >= 0) break;
      if (++it > (1u << 22)) __trap();
    }
  }
  __syncwarp();
}

__device__ __forceinline__ void wgmma_ss_n192(float (&d)[96], uint64_t da, uint64_t db, int scale_d) {
  asm volatile("{\n.reg .pred p;\nsetp.ne.b32 p, %98, 0;\n"
    "wgmma.mma_async.sync.aligned.m64n192k16.f32.bf16.bf16 {%0, %1, %2, %3, %4, %5, %6, %7, %8, %9, %10, %11, %12, %13, %14, %15, %16, %17, %18, %19, %20, %21, %22, %23, %24, %25, %26, %27, %28, %29, %30, %31, %32, %33, %34, %35, %36, %37, %38, %39, %40, %41, %42, %43, %44, %45, %46, %47, %48, %49, %50, %51, %52, %53, %54, %55, %56, %57, %58, %59, %60, %61, %62, %63, %64, %65, %66, %67, %68, %69, %70, %71, %72, %73, %74, %75, %76, %77, %78, %79, %80, %81, %82, %83, %84, %85, %86, %87, %88, %89, %90, %91, %92, %93, %94, %95}, %96, %97, p, 1, 1, 0, 1;\n}\n"
    : "+f"(d[0]), "+f"(d[1]), "+f"(d[2]), "+f"(d[3]), "+f"(d[4]), "+f"(d[5]), "+f"(d[6]), "+f"(d[7]), "+f"(d[8]), "+f"(d[9]), "+f"(d[10]), "+f"(d[11]), "+f"(d[12]), "+f"(d[13]), "+f"(d[14]), "+f"(d[15]), "+f"(d[16]), "+f"(d[17]), "+f"(d[18]), "+f"(d[19]), "+f"(d[20]), "+f"(d[21]), "+f"(d[22]), "+f"(d[23]), "+f"(d[24]), "+f"(d[25]), "+f"(d[26]), "+f"(d[27]), "+f"(d[28]), "+f"(d[29]), "+f"(d[30]), "+f"(d[31]), "+f"(d[32]), "+f"(d[33]), "+f"(d[34]), "+f"(d[35]), "+f"(d[36]), "+f"(d[37]), "+f"(d[38]), "+f"(d[39]), "+f"(d[40]), "+f"(d[41]), "+f"(d[42]), "+f"(d[43]), "+f"(d[44]), "+f"(d[45]), "+f"(d[46]), "+f"(d[47]), "+f"(d[48]), "+f"(d[49]), "+f"(d[50]), "+f"(d[51]), "+f"(d[52]), "+f"(d[53]), "+f"(d[54]), "+f"(d[55]), "+f"(d[56]), "+f"(d[57]), "+f"(d[58]), "+f"(d[59]), "+f"(d[60]), "+f"(d[61]), "+f"(d[62]), "+f"(d[63]), "+f"(d[64]), "+f"(d[65]), "+f"(d[66]), "+f"(d[67]), "+f"(d[68]), "+f"(d[69]), "+f"(d[70]), "+f"(d[71]), "+f"(d[72]), "+f"(d[73]), "+f"(d[74]), "+f"(d[75]), "+f"(d[76]), "+f"(d[77]), "+f"(d[78]), "+f"(d[79]), "+f"(d[80]), "+f"(d[81]), "+f"(d[82]), "+f"(d[83]), "+f"(d[84]), "+f"(d[85]), "+f"(d[86]), "+f"(d[87]), "+f"(d[88]), "+f"(d[89]), "+f"(d[90]), "+f"(d[91]), "+f"(d[92]), "+f"(d[93]), "+f"(d[94]), "+f"(d[95])
    : "l"(da), "l"(db), "r"(scale_d));
}
__device__ __forceinline__ void wgmma_ss_n128(float (&d)[64], uint64_t da, uint64_t db, int scale_d) {
  asm volatile("{\n.reg .pred p;\nsetp.ne.b32 p, %66, 0;\n"
    "wgmma.mma_async.sync.aligned.m64n128k16.f32.bf16.bf16 {%0, %1, %2, %3, %4, %5, %6, %7, %8, %9, %10, %11, %12, %13, %14, %15, %16, %17, %18, %19, %20, %21, %22, %23, %24, %25, %26, %27, %28, %29, %30, %31, %32, %33, %34, %35, %36, %37, %38, %39, %40, %41, %42, %43, %44, %45, %46, %47, %48, %49, %50, %51, %52, %53, %54, %55, %56, %57, %58, %59, %60, %61, %62, %63}, %64, %65, p, 1, 1, 0, 1;\n}\n"
    : "+f"(d[0]), "+f"(d[1]), "+f"(d[2]), "+f"(d[3]), "+f"(d[4]), "+f"(d[5]), "+f"(d[6]), "+f"(d[7]), "+f"(d[8]), "+f"(d[9]), "+f"(d[10]), "+f"(d[11]), "+f"(d[12]), "+f"(d[13]), "+f"(d[14]), "+f"(d[15]), "+f"(d[16]), "+f"(d[17]), "+f"(d[18]), "+f"(d[19]), "+f"(d[20]), "+f"(d[21]), "+f"(d[22]), "+f"(d[23]), "+f"(d[24]), "+f"(d[25]), "+f"(d[26]), "+f"(d[27]), "+f"(d[28]), "+f"(d[29]), "+f"(d[30]), "+f"(d[31]), "+f"(d[32]), "+f"(d[33]), "+f"(d[34]), "+f"(d[35]), "+f"(d[36]), "+f"(d[37]), "+f"(d[38]), "+f"(d[39]), "+f"(d[40]), "+f"(d[41]), "+f"(d[42]), "+f"(d[43]), "+f"(d[44]), "+f"(d[45]), "+f"(d[46]), "+f"(d[47]), "+f"(d[48]), "+f"(d[49]), "+f"(d[50]), "+f"(d[51]), "+f"(d[52]), "+f"(d[53]), "+f"(d[54]), "+f"(d[55]), "+f"(d[56]), "+f"(d[57]), "+f"(d[58]), "+f"(d[59]), "+f"(d[60]), "+f"(d[61]), "+f"(d[62]), "+f"(d[63])
    : "l"(da), "l"(db), "r"(scale_d));
}
__device__ __forceinline__ void wgmma_ss_n96(float (&d)[48], uint64_t da, uint64_t db, int scale_d) {
  asm volatile("{\n.reg .pred p;\nsetp.ne.b32 p, %50, 0;\n"
    "wgmma.mma_async.sync.aligned.m64n96k16.f32.bf16.bf16 {%0, %1, %2, %3, %4, %5, %6, %7, %8, %9, %10, %11, %12, %13, %14, %15, %16, %17, %18, %19, %20, %21, %22, %23, %24, %25, %26, %27, %28, %29, %30, %31, %32, %33, %34, %35, %36, %37, %38, %39, %40, %41, %42, %43, %44, %45, %46, %47}, %48, %49, p, 1, 1, 0, 1;\n}\n"
    : "+f"(d[0]), "+f"(d[1]), "+f"(d[2]), "+f"(d[3]), "+f"(d[4]), "+f"(d[5]), "+f"(d[6]), "+f"(d[7]), "+f"(d[8]), "+f"(d[9]), "+f"(d[10]), "+f"(d[11]), "+f"(d[12]), "+f"(d[13]), "+f"(d[14]), "+f"(d[15]), "+f"(d[16]), "+f"(d[17]), "+f"(d[18]), "+f"(d[19]), "+f"(d[20]), "+f"(d[21]), "+f"(d[22]), "+f"(d[23]), "+f"(d[24]), "+f"(d[25]), "+f"(d[26]), "+f"(d[27]), "+f"(d[28]), "+f"(d[29]), "+f"(d[30]), "+f"(d[31]), "+f"(d[32]), "+f"(d[33]), "+f"(d[34]), "+f"(d[35]), "+f"(d[36]), "+f"(d[37]), "+f"(d[38]), "+f"(d[39]), "+f"(d[40]), "+f"(d[41]), "+f"(d[42]), "+f"(d[43]), "+f"(d[44]), "+f"(d[45]), "+f"(d[46]), "+f"(d[47])
    : "l"(da), "l"(db), "r"(scale_d));
}
__device__ __forceinline__ void wgmma_rs_n128(float (&d)[64], uint32_t a0, uint32_t a1, uint32_t a2, uint32_t a3, uint64_t db, int scale_d) {
  asm volatile("{\n.reg .pred p;\nsetp.ne.b32 p, %69, 0;\n"
    "wgmma.mma_async.sync.aligned.m64n128k16.f32.bf16.bf16 {%0, %1, %2, %3, %4, %5, %6, %7, %8, %9, %10, %11, %12, %13, %14, %15, %16, %17, %18, %19, %20, %21, %22, %23, %24, %25, %26, %27, %28, %29, %30, %31, %32, %33, %34, %35, %36, %37, %38, %39, %40, %41, %42, %43, %44, %45, %46, %47, %48, %49, %50, %51, %52, %53, %54, %55, %56, %57, %58, %59, %60, %61, %62, %63}, {%64, %65, %66, %67}, %68, p, 1, 1, 1;\n}\n"
    : "+f"(d[0]), "+f"(d[1]), "+f"(d[2]), "+f"(d[3]), "+f"(d[4]), "+f"(d[5]), "+f"(d[6]), "+f"(d[7]), "+f"(d[8]), "+f"(d[9]), "+f"(d[10]), "+f"(d[11]), "+f"(d[12]), "+f"(d[13]), "+f"(d[14]), "+f"(d[15]), "+f"(d[16]), "+f"(d[17]), "+f"(d[18]), "+f"(d[19]), "+f"(d[20]), "+f"(d[21]), "+f"(d[22]), "+f"(d[23]), "+f"(d[24]), "+f"(d[25]), "+f"(d[26]), "+f"(d[27]), "+f"(d[28]), "+f"(d[29]), "+f"(d[30]), "+f"(d[31]), "+f"(d[32]), "+f"(d[33]), "+f"(d[34]), "+f"(d[35]), "+f"(d[36]), "+f"(d[37]), "+f"(d[38]), "+f"(d[39]), "+f"(d[40]), "+f"(d[41]), "+f"(d[42]), "+f"(d[43]), "+f"(d[44]), "+f"(d[45]), "+f"(d[46]), "+f"(d[47]), "+f"(d[48]), "+f"(d[49]), "+f"(d[50]), "+f"(d[51]), "+f"(d[52]), "+f"(d[53]), "+f"(d[54]), "+f"(d[55]), "+f"(d[56]), "+f"(d[57]), "+f"(d[58]), "+f"(d[59]), "+f"(d[60]), "+f"(d[61]), "+f"(d[62]), "+f"(d[63])
    : "r"(a0), "r"(a1), "r"(a2), "r"(a3), "l"(db), "r"(scale_d));
}
__device__ __forceinline__ void wgmma_rs_n64(float (&d)[32], uint32_t a0, uint32_t a1, uint32_t a2, uint32_t a3, uint64_t db, int scale_d) {
  asm volatile("{\n.reg .pred p;\nsetp.ne.b32 p, %37, 0;\n"
    "wgmma.mma_async.sync.aligned.m64n64k16.f32.bf16.bf16 {%0, %1, %2, %3, %4, %5, %6, %7, %8, %9, %10, %11, %12, %13, %14, %15, %16, %17, %18, %19, %20, %21, %22, %23, %24, %25, %26, %27, %28, %29, %30, %31}, {%32, %33, %34, %35}, %36, p, 1, 1, 1;\n}\n"
    : "+f"(d[0]), "+f"(d[1]), "+f"(d[2]), "+f"(d[3]), "+f"(d[4]), "+f"(d[5]), "+f"(d[6]), "+f"(d[7]), "+f"(d[8]), "+f"(d[9]), "+f"(d[10]), "+f"(d[11]), "+f"(d[12]), "+f"(d[13]), "+f"(d[14]), "+f"(d[15]), "+f"(d[16]), "+f"(d[17]), "+f"(d[18]), "+f"(d[19]), "+f"(d[20]), "+f"(d[21]), "+f"(d[22]), "+f"(d[23]), "+f"(d[24]), "+f"(d[25]), "+f"(d[26]), "+f"(d[27]), "+f"(d[28]), "+f"(d[29]), "+f"(d[30]), "+f"(d[31])
    : "r"(a0), "r"(a1), "r"(a2), "r"(a3), "l"(db), "r"(scale_d));
}


__device__ __forceinline__ float phi_f(float t) {
  float e = ex2(t * 1.4426950408889634f);
  return (t > 0.f ? t + 1.f : e) + 1e-6f;
}
__device__ __forceinline__ float mish_f(float h) {
  float u = ex2(fminf(h, 20.f) * 1.4426950408889634f);
  float n = u * (u + 2.f);
  return h * n * rcp(n + 2.f);
}
__device__ __forceinline__ float silu_f(float y) { return y * rcp(1.f + ex2(-y * 1.4426950408889634f)); }

struct Ring {
  int slot; uint32_t phase;
  __device__ __forceinline__ void next() { if (++slot == NSLOT) { slot = 0; phase ^= 1; } }
};

__global__ void __launch_bounds__(384, 1)
fused_kernel(const __grid_constant__ CUtensorMap tm_qkv, const __grid_constant__ CUtensorMap tm_w1,
             const __grid_constant__ CUtensorMap tm_w2a, const __grid_constant__ CUtensorMap tm_w2b,
             const __grid_constant__ CUtensorMap tm_wo,
             const __nv_bfloat16* __restrict__ x, const __nv_bfloat16* __restrict__ b1, __nv_bfloat16* __restrict__ out) {
  extern __shared__ uint8_t smem_raw[];
  const uint32_t sb = (smem_u32(smem_raw) + 1023u) & ~1023u;
  uint8_t* sgen = smem_raw + (sb - smem_u32(smem_raw));
  const int tid = threadIdx.x, warp = tid >> 5, lane = tid & 31;
  const int bid = blockIdx.x;
  const int G = bid >> 4, gi = bid & 15;
  const int khalf = G & 1;
  const int rb = (G >> 1) * 4 + (gi >> 2);
  const int nt = gi & 3;
  const int j = khalf + 2 * nt;
  const uint32_t bar0 = sb + OFF_BAR;

  if (tid == 0) {
    for (int i = 0; i < NSLOT; i++) { mbar_init(bar0 + 8 * (BAR_FULL + i), 1); mbar_init(bar0 + 8 * (BAR_EMPTY + i), 8); }
    mbar_init(bar0 + 8 * BAR_STATS, 3);
    mbar_init(bar0 + 8 * BAR_KVPART, 8);
    mbar_init(bar0 + 8 * BAR_KVREADY, 3);
    asm volatile("fence.mbarrier_init.release.cluster;" ::: "memory");
    unsigned dn; asm volatile("ld.relaxed.gpu.global.u32 %0, [%1];" : "=r"(dn) : "l"(&g_done) : "memory");
    *reinterpret_cast<unsigned*>(sgen + OFF_EPOCH) = dn / NCTA + 1u;
  }
  for (int i = tid; i < 4 * 272; i += 384) reinterpret_cast<float*>(sgen + OFF_KVRED)[i] = 0.f;
  __syncthreads();
  const unsigned ep1 = *reinterpret_cast<volatile unsigned*>(sgen + OFF_EPOCH);

  if (warp >= 8) {
    asm volatile("setmaxnreg.dec.sync.aligned.u32 88;");
    if (warp == 8) {
      if (lane == 0) {
        Ring r{0, 1};
        const int c_own = 128 * nt + 64 * khalf, c_par = 128 * nt + 64 * (1 - khalf);
        for (int st = 0; st < NSTAGES; st++) {
          const uint32_t full = bar0 + 8 * (BAR_FULL + r.slot);
          const uint32_t dst = sb + OFF_RING + r.slot * SLOT_BYTES;
          mbar_wait(bar0 + 8 * (BAR_EMPTY + r.slot), r.phase);
          if (st < 16) {
            mbar_expect_tx(full, 12288);
            const int k0 = 32 * st;
            tma2d(dst, &tm_qkv, 64 * j, k0, full);
            tma2d(dst + 4096, &tm_qkv, 512 + 64 * j, k0, full);
            tma2d(dst + 8192, &tm_qkv, 1024 + 64 * j, k0, full);
          } else if (st < 32) {
            mbar_expect_tx(full, 16384);
            const int i = st - 16;
            const int k0 = 64 * (i & 7), c0 = 224 * j + (i >> 3) * 128;
            tma2d(dst, &tm_w1, c0, k0, full);
            tma2d(dst + 8192, &tm_w1, c0 + 64, k0, full);
          } else if (st < 40) {
            mbar_expect_tx(full, 16384);
            const int i = st - 32;
            const int k0 = 224 * (4 * khalf + (i >> 1)) + 64 * (i & 1);
            tma2d(dst, &tm_w2a, c_own, k0, full);
            tma2d(dst + 8192, &tm_w2a, c_par, k0, full);
          } else if (st < 48) {
            mbar_expect_tx(full, 12288);
            const int i = st - 40;
            const int k0 = 224 * (4 * khalf + (i >> 1)) + 128 + 48 * (i & 1);
            tma2d(dst, &tm_w2b, c_own, k0, full);
            tma2d(dst + 6144, &tm_w2b, c_par, k0, full);
          } else {
            mbar_expect_tx(full, 8192);
            tma2d(dst, &tm_wo, c_own, 64 * (st - 48), full);
          }
          r.next();
        }
      }
    } else {
      const int aw = warp - 9;
      for (int i = aw * 32 + lane; i < 224; i += 96) reinterpret_cast<float*>(sgen + OFF_B1)[i] = __bfloat162float(b1[224 * j + i]);
      for (int r0 = aw * 4; r0 < 128; r0 += 12) {
        uint4 v[4][2];
#pragma unroll
        for (int q = 0; q < 4; q++) {
          const __nv_bfloat16* p = x + (size_t)(rb * 128 + r0 + q) * DM + lane * 8;
          v[q][0] = ldg_nc(p); v[q][1] = ldg_nc(p + 256);
        }
        float s[4];
#pragma unroll
        for (int q = 0; q < 4; q++) {
          float a = 0.f;
#pragma unroll
          for (int h = 0; h < 2; h++) {
            a += bf_lo(v[q][h].x) + bf_hi(v[q][h].x) + bf_lo(v[q][h].y) + bf_hi(v[q][h].y);
            a += bf_lo(v[q][h].z) + bf_hi(v[q][h].z) + bf_lo(v[q][h].w) + bf_hi(v[q][h].w);
          }
          s[q] = a;
        }
#pragma unroll
        for (int o = 16; o > 0; o >>= 1) {
#pragma unroll
          for (int q = 0; q < 4; q++) s[q] += __shfl_xor_sync(0xffffffffu, s[q], o);
        }
        float ss[4];
#pragma unroll
        for (int q = 0; q < 4; q++) {
          const float m = s[q] * (1.f / DM);
          float a = 0.f;
#pragma unroll
          for (int h = 0; h < 2; h++) {
            const uint32_t w4[4] = {v[q][h].x, v[q][h].y, v[q][h].z, v[q][h].w};
#pragma unroll
            for (int e = 0; e < 4; e++) {
              float d0 = bf_lo(w4[e]) - m, d1 = bf_hi(w4[e]) - m;
              a = fmaf(d0, d0, a); a = fmaf(d1, d1, a);
            }
          }
          ss[q] = a;
        }
#pragma unroll
        for (int o = 16; o > 0; o >>= 1) {
#pragma unroll
          for (int q = 0; q < 4; q++) ss[q] += __shfl_xor_sync(0xffffffffu, ss[q], o);
        }
        if (lane < 4) {
          float var = (lane == 0 ? ss[0] : lane == 1 ? ss[1] : lane == 2 ? ss[2] : ss[3]) * (1.f / DM);
          reinterpret_cast<float*>(sgen + OFF_RSTD)[r0 + lane] = rsqrtf(var + 1e-5f);
        }
      }
      __syncwarp();
      if (lane == 0) mbar_arrive(bar0 + 8 * BAR_STATS);
      if (aw == 0) {
        mbar_wait(bar0 + 8 * BAR_KVPART, 0);
        const float4* src = reinterpret_cast<const float4*>(sgen + OFF_KVRED);
        float4* dst = reinterpret_cast<float4*>(g_kvp + (size_t)(rb * 32 + 4 * j) * 272);
        for (int i = lane; i < 272; i += 32) dst[i] = src[i];
        warp_publish(&g_cntKV[j], lane);
      }
      warp_wait_ge(&g_cntKV[j], 16u * ep1, lane);
      for (int i = aw * 32 + lane; i < 272; i += 96) {
        float4 acc = make_float4(0.f, 0.f, 0.f, 0.f);
        uint4 t[16];
#pragma unroll
        for (int r = 0; r < 16; r++) t[r] = ldg_cg(reinterpret_cast<const float4*>(g_kvp + (size_t)(r * 32 + 4 * j) * 272) + i);
#pragma unroll
        for (int r = 0; r < 16; r++) {
          acc.x += __uint_as_float(t[r].x); acc.y += __uint_as_float(t[r].y);
          acc.z += __uint_as_float(t[r].z); acc.w += __uint_as_float(t[r].w);
        }
        const int hh = i / 68, e4 = (i % 68) * 4;
        const float vals[4] = {acc.x, acc.y, acc.z, acc.w};
        if (e4 < 256) {
          const int d = e4 >> 4, e = e4 & 15;
#pragma unroll
          for (int q = 0; q < 4; q++)
            reinterpret_cast<__nv_bfloat16*>(sgen + OFF_KVT)[(hh * 16 + e + q) * 16 + d] = __float2bfloat16(vals[q]);
        } else {
#pragma unroll
          for (int q = 0; q < 4; q++)
            reinterpret_cast<__nv_bfloat16*>(sgen + OFF_ZB)[hh * 16 + (e4 - 256) + q] = __float2bfloat16(vals[q]);
        }
      }
      __syncwarp();
      if (lane == 0) mbar_arrive(bar0 + 8 * BAR_KVREADY);
    }
  } else {
    asm volatile("setmaxnreg.inc.sync.aligned.u32 208;");
    const int wg = warp >> 2;
    const int g = lane >> 2, t = lane & 3;
    const int lr0 = warp * 16 + g;
    const int slab = rb * 8 + warp;
    {
      uint4 q[16], p[16];
      const __nv_bfloat16* xr0 = x + (size_t)(rb * 128 + lr0) * DM + 8 * t;
      const __nv_bfloat16* xr1 = xr0 + 8 * DM;
      const int par = g & 1;
#pragma unroll
      for (int c = 0; c < 16; c++) { q[c] = ldg_nc(xr0 + 32 * (c ^ par)); p[c] = ldg_nc(xr1 + 32 * (c ^ par)); }
      float sm4[4][4];
#pragma unroll
      for (int a = 0; a < 4; a++) { sm4[a][0] = sm4[a][1] = sm4[a][2] = sm4[a][3] = 0.f; }
      const uint32_t ones = 0x3F803F80u;
#pragma unroll
      for (int c = 0; c < 16; c++) {
        mma16816(sm4[(2 * c) & 3], q[c].x, p[c].x, q[c].y, p[c].y, ones, ones);
        mma16816(sm4[(2 * c + 1) & 3], q[c].z, p[c].z, q[c].w, p[c].w, ones, ones);
      }
      const float m0 = (sm4[0][0] + sm4[1][0] + sm4[2][0] + sm4[3][0]) * (1.f / DM);
      const float m1 = (sm4[0][2] + sm4[1][2] + sm4[2][2] + sm4[3][2]) * (1.f / DM);
      const uint32_t mb0 = pack2(m0, m0), mb1 = pack2(m1, m1);
      const uint32_t rowa = sb + OFF_D + lr0 * 128, rowb = rowa + 1024;
#pragma unroll
      for (int c = 0; c < 16; c++) {
        const int cc = c ^ par;
        const uint32_t u = (uint32_t)(((cc & 1) * 4 + t) ^ g) * 16;
        const uint32_t off = (uint32_t)(cc >> 1) * 16384 + u;
        sts_v4(rowa + off, hsub2_bf16(q[c].x, mb0), hsub2_bf16(q[c].y, mb0), hsub2_bf16(q[c].z, mb0), hsub2_bf16(q[c].w, mb0));
        sts_v4(rowb + off, hsub2_bf16(p[c].x, mb1), hsub2_bf16(p[c].y, mb1), hsub2_bf16(p[c].z, mb1), hsub2_bf16(p[c].w, mb1));
      }
      asm volatile("fence.proxy.async.shared::cta;" ::: "memory");
      named_bar_sync(1 + wg, 128);
    }
    Ring r{0, 0};
    const uint32_t a_base = sb + OFF_D + wg * 8192;
    const uint32_t ring_base = sb + OFF_RING;
    uint32_t prev_empty = 0;
    auto release_prev = [&]() { if (prev_empty && lane == 0) mbar_arrive(prev_empty); };

    uint32_t pq[16];
    float rs0, rs1;
    {
      float acc[96];
      for (int st = 0; st < 16; st++) {
        mbar_wait(bar0 + 8 * (BAR_FULL + r.slot), r.phase);
        const uint32_t bs = ring_base + r.slot * SLOT_BYTES;
        const uint32_t as = a_base + (st >> 1) * 16384 + (st & 1) * 64;
        wg_fence();
        wgmma_ss_n192(acc, make_desc(as, 16, 1024), make_desc(bs, 4096, 1024), st != 0);
        wgmma_ss_n192(acc, make_desc(as + 32, 16, 1024), make_desc(bs + 2048, 4096, 1024), 1);
        wg_commit();
        wg_wait<1>();
        release_prev();
        prev_empty = bar0 + 8 * (BAR_EMPTY + r.slot);
        r.next();
      }
      wg_wait<0>();
      fence_regs(acc);
      release_prev(); prev_empty = 0;
      mbar_wait(bar0 + 8 * BAR_STATS, 0);
      rs0 = lds_f32(sb + OFF_RSTD + lr0 * 4);
      rs1 = lds_f32(sb + OFF_RSTD + (lr0 + 8) * 4);
#pragma unroll
      for (int nb = 0; nb < 8; nb++) {
        pq[2 * nb] = pack2(phi_f(acc[4 * nb] * rs0), phi_f(acc[4 * nb + 1] * rs0));
        pq[2 * nb + 1] = pack2(phi_f(acc[4 * nb + 2] * rs1), phi_f(acc[4 * nb + 3] * rs1));
      }
      const uint32_t ones = 0x3F803F80u;
#pragma unroll
      for (int hh = 0; hh < 4; hh++) {
        uint32_t kt[2][2], vt[2][2];
#pragma unroll
        for (int db = 0; db < 2; db++) {
          const int nb = 8 + 2 * hh + db;
          kt[db][0] = movmat(pack2(phi_f(acc[4 * nb] * rs0), phi_f(acc[4 * nb + 1] * rs0)));
          kt[db][1] = movmat(pack2(phi_f(acc[4 * nb + 2] * rs1), phi_f(acc[4 * nb + 3] * rs1)));
          const int nv = 16 + 2 * hh + db;
          vt[db][0] = movmat(pack2(acc[4 * nv] * rs0, acc[4 * nv + 1] * rs0));
          vt[db][1] = movmat(pack2(acc[4 * nv + 2] * rs1, acc[4 * nv + 3] * rs1));
        }
        const uint32_t rbase = sb + OFF_KVRED + hh * 272 * 4;
#pragma unroll
        for (int eb = 0; eb < 2; eb++) {
          float c[4] = {0.f, 0.f, 0.f, 0.f};
          mma16816(c, kt[0][0], kt[1][0], kt[0][1], kt[1][1], vt[eb][0], vt[eb][1]);
          const uint32_t a0 = rbase + (g * 16 + eb * 8 + 2 * t) * 4;
          red_shared_add(a0, c[0]); red_shared_add(a0 + 4, c[1]);
          red_shared_add(a0 + 512, c[2]); red_shared_add(a0 + 516, c[3]);
        }
        float cz[4] = {0.f, 0.f, 0.f, 0.f};
        mma16816(cz, kt[0][0], kt[1][0], kt[0][1], kt[1][1], ones, ones);
        if (t == 0) { red_shared_add(rbase + (256 + g) * 4, cz[0]); red_shared_add(rbase + (264 + g) * 4, cz[2]); }
      }
      __syncwarp();
      if (lane == 0) mbar_arrive(bar0 + 8 * BAR_KVPART);
    }
    uint4* act_out = g_act + (size_t)(slab * 112 + 14 * j) * 32 + lane;
    {
      float acc[64];
      for (int st = 0; st < 8; st++) {
        mbar_wait(bar0 + 8 * (BAR_FULL + r.slot), r.phase);
        const uint32_t bs = ring_base + r.slot * SLOT_BYTES;
        const uint32_t as = a_base + st * 16384;
        wg_fence();
#pragma unroll
        for (int kk = 0; kk < 4; kk++)
          wgmma_ss_n128(acc, make_desc(as + kk * 32, 16, 1024), make_desc(bs + kk * 2048, 8192, 1024), (st | kk) != 0);
        wg_commit();
        wg_wait<1>();
        release_prev();
        prev_empty = bar0 + 8 * (BAR_EMPTY + r.slot);
        r.next();
      }
      wg_wait<0>();
      fence_regs(acc);
      release_prev(); prev_empty = 0;
#pragma unroll
      for (int kt = 0; kt < 8; kt++) {
        const float2 ba = lds_f32x2(sb + OFF_B1 + (16 * kt + 2 * t) * 4);
        const float2 bb = lds_f32x2(sb + OFF_B1 + (16 * kt + 8 + 2 * t) * 4);
        const float* c = acc + 8 * kt;
        uint32_t a0 = pack2(mish_f(fmaf(c[0], rs0, ba.x)), mish_f(fmaf(c[1], rs0, ba.y)));
        uint32_t a1 = pack2(mish_f(fmaf(c[2], rs1, ba.x)), mish_f(fmaf(c[3], rs1, ba.y)));
        uint32_t a2 = pack2(mish_f(fmaf(c[4], rs0, bb.x)), mish_f(fmaf(c[5], rs0, bb.y)));
        uint32_t a3 = pack2(mish_f(fmaf(c[6], rs1, bb.x)), mish_f(fmaf(c[7], rs1, bb.y)));
        stg_v4(act_out + kt * 32, a0, a1, a2, a3);
      }
      warp_publish(&g_cntA[slab * 2 + (j >> 2)], lane);
    }
    {
      float acc[48];
      for (int st = 0; st < 8; st++) {
        mbar_wait(bar0 + 8 * (BAR_FULL + r.slot), r.phase);
        const uint32_t bs = ring_base + r.slot * SLOT_BYTES;
        const uint32_t as = a_base + st * 16384;
        wg_fence();
#pragma unroll
        for (int kk = 0; kk < 4; kk++)
          wgmma_ss_n96(acc, make_desc(as + kk * 32, 16, 1024), make_desc(bs + kk * 2048, 8192, 1024), (st | kk) != 0);
        wg_commit();
        wg_wait<1>();
        release_prev();
        prev_empty = bar0 + 8 * (BAR_EMPTY + r.slot);
        r.next();
      }
      wg_wait<0>();
      fence_regs(acc);
      release_prev(); prev_empty = 0;
#pragma unroll
      for (int kt = 0; kt < 6; kt++) {
        const float2 ba = lds_f32x2(sb + OFF_B1 + (128 + 16 * kt + 2 * t) * 4);
        const float2 bb = lds_f32x2(sb + OFF_B1 + (128 + 16 * kt + 8 + 2 * t) * 4);
        const float* c = acc + 8 * kt;
        uint32_t a0 = pack2(mish_f(fmaf(c[0], rs0, ba.x)), mish_f(fmaf(c[1], rs0, ba.y)));
        uint32_t a1 = pack2(mish_f(fmaf(c[2], rs1, ba.x)), mish_f(fmaf(c[3], rs1, ba.y)));
        uint32_t a2 = pack2(mish_f(fmaf(c[4], rs0, bb.x)), mish_f(fmaf(c[5], rs0, bb.y)));
        uint32_t a3 = pack2(mish_f(fmaf(c[6], rs1, bb.x)), mish_f(fmaf(c[7], rs1, bb.y)));
        stg_v4(act_out + (8 + kt) * 32, a0, a1, a2, a3);
      }
      warp_publish(&g_cntB[slab * 2 + (j >> 2)], lane);
    }
    {
      mbar_wait(bar0 + 8 * BAR_KVREADY, 0);
      uint4* o_out = g_o + (size_t)(slab * 32 + 4 * j) * 32 + lane;
#pragma unroll
      for (int hh = 0; hh < 4; hh++) {
        float n0[4] = {0.f, 0.f, 0.f, 0.f}, n1[4] = {0.f, 0.f, 0.f, 0.f}, dn[4] = {0.f, 0.f, 0.f, 0.f};
        const uint32_t kb = sb + OFF_KVT + ((hh * 16 + g) * 16 + 2 * t) * 2;
        const uint32_t zb = sb + OFF_ZB + (hh * 16 + 2 * t) * 2;
        mma16816(n0, pq[4 * hh], pq[4 * hh + 1], pq[4 * hh + 2], pq[4 * hh + 3], lds_u32(kb), lds_u32(kb + 16));
        mma16816(n1, pq[4 * hh], pq[4 * hh + 1], pq[4 * hh + 2], pq[4 * hh + 3], lds_u32(kb + 256), lds_u32(kb + 256 + 16));
        mma16816(dn, pq[4 * hh], pq[4 * hh + 1], pq[4 * hh + 2], pq[4 * hh + 3], lds_u32(zb), lds_u32(zb + 16));
        const float i0 = __fdividef(1.f, dn[0] + 1e-6f), i1 = __fdividef(1.f, dn[2] + 1e-6f);
        stg_v4(o_out + hh * 32, pack2(n0[0] * i0, n0[1] * i0), pack2(n0[2] * i1, n0[3] * i1), pack2(n1[0] * i0, n1[1] * i0), pack2(n1[2] * i1, n1[3] * i1));
      }
      warp_publish(&g_cntO[slab], lane);
    }
    float accy[64];
    {
      const uint4* act_in = g_act + (size_t)(slab * 112 + 56 * khalf) * 32 + lane;
      warp_wait_ge(&g_cntA[slab * 2 + khalf], 4u * ep1, lane);
      uint4 ab[2][4];
#pragma unroll
      for (int kk = 0; kk < 4; kk++) ab[0][kk] = ldg_cg(act_in + kk * 32);
#pragma unroll
      for (int st = 0; st < 8; st++) {
        if (st + 1 < 8) {
          const int kt = 14 * ((st + 1) >> 1) + 4 * ((st + 1) & 1);
#pragma unroll
          for (int kk = 0; kk < 4; kk++) ab[(st + 1) & 1][kk] = ldg_cg(act_in + (kt + kk) * 32);
        }
        mbar_wait(bar0 + 8 * (BAR_FULL + r.slot), r.phase);
        const uint32_t bs = ring_base + r.slot * SLOT_BYTES;
        wg_fence();
#pragma unroll
        for (int kk = 0; kk < 4; kk++) {
          const uint4 a = ab[st & 1][kk];
          wgmma_rs_n128(accy, a.x, a.y, a.z, a.w, make_desc(bs + kk * 2048, 8192, 1024), (st | kk) != 0);
        }
        wg_commit();
        wg_wait<0>();
#pragma unroll
        for (int kk = 0; kk < 4; kk++) fence_u4(ab[st & 1][kk]);
        if (lane == 0) mbar_arrive(bar0 + 8 * (BAR_EMPTY + r.slot));
        r.next();
      }
      warp_wait_ge(&g_cntB[slab * 2 + khalf], 4u * ep1, lane);
#pragma unroll
      for (int kk = 0; kk < 3; kk++) ab[0][kk] = ldg_cg(act_in + (8 + kk) * 32);
#pragma unroll
      for (int st = 0; st < 8; st++) {
        if (st + 1 < 8) {
          const int kt = 14 * ((st + 1) >> 1) + 8 + 3 * ((st + 1) & 1);
#pragma unroll
          for (int kk = 0; kk < 3; kk++) ab[(st + 1) & 1][kk] = ldg_cg(act_in + (kt + kk) * 32);
        }
        mbar_wait(bar0 + 8 * (BAR_FULL + r.slot), r.phase);
        const uint32_t bs = ring_base + r.slot * SLOT_BYTES;
        wg_fence();
#pragma unroll
        for (int kk = 0; kk < 3; kk++) {
          const uint4 a = ab[st & 1][kk];
          wgmma_rs_n128(accy, a.x, a.y, a.z, a.w, make_desc(bs + kk * 2048, 6144, 1024), 1);
        }
        wg_commit();
        wg_wait<0>();
#pragma unroll
        for (int kk = 0; kk < 3; kk++) fence_u4(ab[st & 1][kk]);
        if (lane == 0) mbar_arrive(bar0 + 8 * (BAR_EMPTY + r.slot));
        r.next();
      }
      fence_regs(accy);
      float4* yp = g_yp + (size_t)((bid * 8 + warp) * 8) * 32 + lane;
#pragma unroll
      for (int q = 0; q < 8; q++)
        stg_v4(yp + q * 32, __float_as_uint(accy[32 + 4 * q]), __float_as_uint(accy[33 + 4 * q]), __float_as_uint(accy[34 + 4 * q]), __float_as_uint(accy[35 + 4 * q]));
      warp_publish(&g_flagY[bid * 8 + warp], lane);
    }
    float accs[32];
    {
      const uint4* o_in = g_o + (size_t)(slab * 32) * 32 + lane;
      warp_wait_ge(&g_cntO[slab], 8u * ep1, lane);
      uint4 ab[2][4];
#pragma unroll
      for (int kk = 0; kk < 4; kk++) ab[0][kk] = ldg_cg(o_in + kk * 32);
#pragma unroll
      for (int st = 0; st < 8; st++) {
        if (st + 1 < 8) {
#pragma unroll
          for (int kk = 0; kk < 4; kk++) ab[(st + 1) & 1][kk] = ldg_cg(o_in + (4 * (st + 1) + kk) * 32);
        }
        mbar_wait(bar0 + 8 * (BAR_FULL + r.slot), r.phase);
        const uint32_t bs = ring_base + r.slot * SLOT_BYTES;
        wg_fence();
#pragma unroll
        for (int kk = 0; kk < 4; kk++) {
          const uint4 a = ab[st & 1][kk];
          wgmma_rs_n64(accs, a.x, a.y, a.z, a.w, make_desc(bs + kk * 2048, 8192, 1024), (st | kk) != 0);
        }
        wg_commit();
        wg_wait<0>();
#pragma unroll
        for (int kk = 0; kk < 4; kk++) fence_u4(ab[st & 1][kk]);
        if (lane == 0) mbar_arrive(bar0 + 8 * (BAR_EMPTY + r.slot));
        r.next();
      }
      fence_regs(accs);
    }
    {
      const int pbid = bid ^ 16;
      warp_wait_ge(&g_flagY[pbid * 8 + warp], ep1, lane);
      const float4* yp = g_yp + (size_t)((pbid * 8 + warp) * 8) * 32 + lane;
      const int c0 = 128 * nt + 64 * khalf + 2 * t;
      const size_t ro0 = (size_t)(rb * 128 + lr0) * DM + c0, ro1 = ro0 + 8 * DM;
#pragma unroll
      for (int q = 0; q < 8; q++) {
        const uint4 pv = ldg_cg(yp + q * 32);
        const uint32_t x0 = *reinterpret_cast<const uint32_t*>(x + ro0 + 8 * q);
        const uint32_t x1 = *reinterpret_cast<const uint32_t*>(x + ro1 + 8 * q);
        const float y0 = accy[4 * q] + __uint_as_float(pv.x), y1 = accy[4 * q + 1] + __uint_as_float(pv.y);
        const float y2 = accy[4 * q + 2] + __uint_as_float(pv.z), y3 = accy[4 * q + 3] + __uint_as_float(pv.w);
        const float o0 = fmaf(accs[4 * q], silu_f(y0), bf_lo(x0)), o1 = fmaf(accs[4 * q + 1], silu_f(y1), bf_hi(x0));
        const float o2 = fmaf(accs[4 * q + 2], silu_f(y2), bf_lo(x1)), o3 = fmaf(accs[4 * q + 3], silu_f(y3), bf_hi(x1));
        *reinterpret_cast<uint32_t*>(out + ro0 + 8 * q) = pack2(o0, o1);
        *reinterpret_cast<uint32_t*>(out + ro1 + 8 * q) = pack2(o2, o3);
      }
    }
    if (tid == 0) asm volatile("red.relaxed.gpu.global.add.u32 [%0], 1;" ::"l"(&g_done) : "memory");
  }
}

typedef CUresult (*EncodeFn)(CUtensorMap*, CUtensorMapDataType, cuuint32_t, void*, const cuuint64_t*, const cuuint64_t*,
                             const cuuint32_t*, const cuuint32_t*, CUtensorMapInterleave, CUtensorMapSwizzle,
                             CUtensorMapL2promotion, CUtensorMapFloatOOBfill);

void make_map(EncodeFn enc, CUtensorMap* tm, const void* ptr, int rows, int cols, int box_rows) {
  cuuint64_t gd[2] = {(cuuint64_t)cols, (cuuint64_t)rows};
  cuuint64_t gs[1] = {(cuuint64_t)cols * 2};
  cuuint32_t bd[2] = {64, (cuuint32_t)box_rows};
  cuuint32_t es[2] = {1, 1};
  enc(tm, CU_TENSOR_MAP_DATA_TYPE_BFLOAT16, 2, const_cast<void*>(ptr), gd, gs, bd, es, CU_TENSOR_MAP_INTERLEAVE_NONE,
      CU_TENSOR_MAP_SWIZZLE_128B, CU_TENSOR_MAP_L2_PROMOTION_L2_128B, CU_TENSOR_MAP_FLOAT_OOB_FILL_NONE);
}

}

extern "C" void kernel_launch(void* const* d_in, const int* in_sizes, int n_in, void* d_out, int out_size) {
  const __nv_bfloat16* x = (const __nv_bfloat16*)d_in[0];
  const void* wqkv = d_in[1];
  const void* wo = d_in[2];
  const void* w1 = d_in[4];
  const __nv_bfloat16* b1 = (const __nv_bfloat16*)d_in[5];
  const void* w2 = d_in[6];
  static EncodeFn enc = nullptr;
  if (!enc) {
    cudaDriverEntryPointQueryResult qr;
    void* fn = nullptr;
    cudaGetDriverEntryPoint("cuTensorMapEncodeTiled", &fn, cudaEnableDefault, &qr);
    enc = (EncodeFn)fn;
    cudaFuncSetAttribute(fused_kernel, cudaFuncAttributeMaxDynamicSharedMemorySize, SMEM_ALLOC);
  }
  CUtensorMap tq, t1, t2a, t2b, to;
  make_map(enc, &tq, wqkv, DM, 3 * DM, 32);
  make_map(enc, &t1, w1, DM, FF, 64);
  make_map(enc, &t2a, w2, FF, DM, 64);
  make_map(enc, &t2b, w2, FF, DM, 48);
  make_map(enc, &to, wo, DM, DM, 64);
  fused_kernel<<<NCTA, 384, SMEM_ALLOC>>>(tq, t1, t2a, t2b, to, x, b1, (__nv_bfloat16*)d_out);
}
```

```cpp
#include <cuda_runtime.h>
#include <cuda_bf16.h>
#include <cuda.h>
#include <stdint.h>

namespace {

constexpr int DM = 512, FF = 1792;
constexpr int NCTA = 128;
constexpr int NSLOT = 5;
constexpr int SLOT_BYTES = 16384;
constexpr int OFF_D = 0;
constexpr int OFF_RING = 131072;
constexpr int OFF_MISC = OFF_RING + NSLOT * SLOT_BYTES;
constexpr int OFF_BAR = OFF_MISC;
constexpr int OFF_EPOCH = OFF_MISC + 256;
constexpr int OFF_RSTD = OFF_MISC + 512;
constexpr int OFF_DELTA = OFF_MISC + 1024;
constexpr int OFF_B1 = OFF_MISC + 1536;
constexpr int OFF_KVT = OFF_MISC + 2560;
constexpr int OFF_ZB = OFF_MISC + 4608;
constexpr int SMEM_USED = OFF_MISC + 4864;
constexpr int SMEM_ALLOC = SMEM_USED + 1024;

enum { BAR_FULL = 0, BAR_EMPTY = NSLOT, BAR_DREADY = 2 * NSLOT, BAR_STATS,
       BAR_PUB_A, BAR_PUB_KV, BAR_PUB_B, BAR_PQ, BAR_PUB_Y,
       BAR_RDY_A, BAR_RDY_KV, BAR_RDY_B, BAR_RDY_O, BAR_RDY_Y, BAR_COUNT };

constexpr int NSTAGES = 56;

__device__ uint4 g_act[128 * 112 * 32];
__device__ uint4 g_o[128 * 32 * 32];
__device__ float4 g_yp[NCTA * 8 * 8 * 32];
__device__ float g_kv[2][32 * 272];
__device__ unsigned g_cntA[16 * 2 * 8];
__device__ unsigned g_cntB[16 * 2 * 8];
__device__ unsigned g_cntO[16 * 8];
__device__ unsigned g_flagY[NCTA * 8];
__device__ unsigned g_cntKV[8 * 8];
__device__ unsigned g_done;

#define PROF(i)

__device__ __forceinline__ uint32_t smem_u32(const void* p) { return (uint32_t)__cvta_generic_to_shared(p); }
__device__ __forceinline__ void mbar_init(uint32_t bar, uint32_t cnt) { asm volatile("mbarrier.init.shared::cta.b64 [%0], %1;" ::"r"(bar), "r"(cnt)); }
__device__ __forceinline__ void mbar_expect_tx(uint32_t bar, uint32_t bytes) { asm volatile("mbarrier.arrive.expect_tx.shared::cta.b64 _, [%0], %1;" ::"r"(bar), "r"(bytes) : "memory"); }
__device__ __forceinline__ void mbar_arrive(uint32_t bar) { asm volatile("mbarrier.arrive.shared::cta.b64 _, [%0];" ::"r"(bar) : "memory"); }
__device__ __forceinline__ void mbar_wait(uint32_t bar, uint32_t parity) {
  asm volatile("{\n.reg .pred P1;\n.reg .u32 cnt;\n"
               "mbarrier.try_wait.parity.shared::cta.b64 P1, [%0], %1;\n@P1 bra DONE;\n"
               "mov.u32 cnt, 0;\n"
               "LAB_WAIT:\n"
               "mbarrier.try_wait.parity.shared::cta.b64 P1, [%0], %1;\n@P1 bra DONE;\n"
               "add.u32 cnt, cnt, 1;\nsetp.lt.u32 P1, cnt, 16777216;\n@P1 bra LAB_WAIT;\ntrap;\n"
               "DONE:\n}" ::"r"(bar), "r"(parity) : "memory");
}
__device__ __forceinline__ void tma2d(uint32_t dst, const CUtensorMap* tm, int c0, int c1, uint32_t bar) {
  asm volatile("cp.async.bulk.tensor.2d.shared::cluster.global.mbarrier::complete_tx::bytes [%0], [%1, {%3, %4}], [%2];" ::"r"(dst), "l"(tm), "r"(bar), "r"(c0), "r"(c1) : "memory");
}
__device__ __forceinline__ void wg_fence() { asm volatile("wgmma.fence.sync.aligned;" ::: "memory"); }
__device__ __forceinline__ void wg_commit() { asm volatile("wgmma.commit_group.sync.aligned;" ::: "memory"); }
template <int N> __device__ __forceinline__ void wg_wait() { asm volatile("wgmma.wait_group.sync.aligned %0;" ::"n"(N) : "memory"); }
template <int N> __device__ __forceinline__ void zero_regs(float (&d)[N]) {
#pragma unroll
  for (int i = 0; i < N; i++) d[i] = 0.f;
}
template <int N> __device__ __forceinline__ void fence_regs(float (&d)[N]) {
#pragma unroll
  for (int i = 0; i < N; i++) asm volatile("" : "+f"(d[i])::"memory");
}
__device__ __forceinline__ void fence_u4(uint4& v) { asm volatile("" : "+r"(v.x), "+r"(v.y), "+r"(v.z), "+r"(v.w)::"memory"); }
__device__ __forceinline__ void named_bar_sync(int id, int n) { asm volatile("bar.sync %0, %1;" ::"r"(id), "r"(n) : "memory"); }
__device__ __forceinline__ uint64_t make_desc(uint32_t addr, uint32_t lbo_bytes, uint32_t sbo_bytes) {
  return (uint64_t)((addr & 0x3FFFF) >> 4) | ((uint64_t)(lbo_bytes >> 4) << 16) | ((uint64_t)(sbo_bytes >> 4) << 32) | (1ull << 62);
}
__device__ __forceinline__ void mma16816(float (&c)[4], uint32_t a0, uint32_t a1, uint32_t a2, uint32_t a3, uint32_t b0, uint32_t b1) {
  asm volatile("mma.sync.aligned.m16n8k16.row.col.f32.bf16.bf16.f32 {%0,%1,%2,%3}, {%4,%5,%6,%7}, {%8,%9}, {%0,%1,%2,%3};"
               : "+f"(c[0]), "+f"(c[1]), "+f"(c[2]), "+f"(c[3]) : "r"(a0), "r"(a1), "r"(a2), "r"(a3), "r"(b0), "r"(b1));
}
__device__ __forceinline__ uint32_t movmat(uint32_t a) { uint32_t d; asm volatile("movmatrix.sync.aligned.m8n8.trans.b16 %0, %1;" : "=r"(d) : "r"(a)); return d; }
__device__ __forceinline__ uint32_t pack2(float lo, float hi) { uint32_t r; asm("cvt.rn.bf16x2.f32 %0, %1, %2;" : "=r"(r) : "f"(hi), "f"(lo)); return r; }
__device__ __forceinline__ float ex2(float x) { float r; asm("ex2.approx.ftz.f32 %0, %1;" : "=f"(r) : "f"(x)); return r; }
__device__ __forceinline__ float rcp(float x) { float r; asm("rcp.approx.ftz.f32 %0, %1;" : "=f"(r) : "f"(x)); return r; }
__device__ __forceinline__ float bf_lo(uint32_t v) { return __uint_as_float(v << 16); }
__device__ __forceinline__ float bf_hi(uint32_t v) { return __uint_as_float(v & 0xffff0000u); }
__device__ __forceinline__ uint32_t hsub2_bf16(uint32_t a, uint32_t b) {
  __nv_bfloat162 x = *reinterpret_cast<__nv_bfloat162*>(&a), y = *reinterpret_cast<__nv_bfloat162*>(&b);
  __nv_bfloat162 r = __hsub2(x, y);
  return *reinterpret_cast<uint32_t*>(&r);
}
__device__ __forceinline__ uint4 ldg_nc(const void* p) {
  uint4 v; asm volatile("ld.global.nc.L1::no_allocate.v4.u32 {%0,%1,%2,%3}, [%4];" : "=r"(v.x), "=r"(v.y), "=r"(v.z), "=r"(v.w) : "l"(p)); return v;
}
__device__ __forceinline__ uint32_t ldg_nc32(const void* p) {
  uint32_t v; asm volatile("ld.global.nc.u32 %0, [%1];" : "=r"(v) : "l"(p)); return v;
}
__device__ __forceinline__ uint4 ldg_cg(const void* p) {
  uint4 v; asm volatile("ld.global.cg.v4.u32 {%0,%1,%2,%3}, [%4];" : "=r"(v.x), "=r"(v.y), "=r"(v.z), "=r"(v.w) : "l"(p) : "memory"); return v;
}
__device__ __forceinline__ void stg_v4(void* p, uint32_t a, uint32_t b, uint32_t c, uint32_t d) {
  asm volatile("st.global.v4.u32 [%0], {%1,%2,%3,%4};" ::"l"(p), "r"(a), "r"(b), "r"(c), "r"(d) : "memory");
}
__device__ __forceinline__ void sts_v4(uint32_t addr, uint32_t a, uint32_t b, uint32_t c, uint32_t d) {
  asm volatile("st.shared.v4.u32 [%0], {%1,%2,%3,%4};" ::"r"(addr), "r"(a), "r"(b), "r"(c), "r"(d) : "memory");
}
__device__ __forceinline__ void sts_f32(uint32_t addr, float v) { asm volatile("st.shared.f32 [%0], %1;" ::"r"(addr), "f"(v) : "memory"); }
__device__ __forceinline__ uint4 lds_v4(uint32_t addr) { uint4 v; asm volatile("ld.shared.v4.u32 {%0,%1,%2,%3}, [%4];" : "=r"(v.x), "=r"(v.y), "=r"(v.z), "=r"(v.w) : "r"(addr) : "memory"); return v; }
__device__ __forceinline__ float lds_f32(uint32_t addr) { float v; asm volatile("ld.shared.f32 %0, [%1];" : "=f"(v) : "r"(addr) : "memory"); return v; }
__device__ __forceinline__ float2 lds_f32x2(uint32_t addr) { float2 v; asm volatile("ld.shared.v2.f32 {%0,%1}, [%2];" : "=f"(v.x), "=f"(v.y) : "r"(addr) : "memory"); return v; }
__device__ __forceinline__ uint32_t lds_u32(uint32_t addr) { uint32_t v; asm volatile("ld.shared.u32 %0, [%1];" : "=r"(v) : "r"(addr) : "memory"); return v; }
__device__ __forceinline__ void red_add_v2(float* p, float a, float b) { asm volatile("red.relaxed.gpu.global.add.v2.f32 [%0], {%1,%2};" ::"l"(p), "f"(a), "f"(b) : "memory"); }
__device__ __forceinline__ void red_add_f32(float* p, float a) { asm volatile("red.relaxed.gpu.global.add.f32 [%0], %1;" ::"l"(p), "f"(a) : "memory"); }
__device__ __forceinline__ void red_inc(unsigned* cnt) { asm volatile("red.relaxed.gpu.global.add.u32 [%0], 1;" ::"l"(cnt) : "memory"); }
__device__ __forceinline__ void poll_ge(const unsigned* cnt, unsigned target) {
  asm volatile("{\n.reg .pred P1;\n.reg .u32 cnt, v;\n.reg .s32 d;\n"
               "mov.u32 cnt, 0;\n"
               "LAB_POLL:\n"
               "ld.acquire.gpu.global.u32 v, [%0];\nsub.s32 d, v, %1;\nsetp.ge.s32 P1, d, 0;\n@P1 bra DONE;\n"
               "add.u32 cnt, cnt, 1;\nsetp.lt.u32 P1, cnt, 4194304;\n@P1 bra LAB_POLL;\ntrap;\n"
               "DONE:\n}" ::"l"(cnt), "r"(target) : "memory");
}

__device__ __forceinline__ void wgmma_ss_n192(float (&d)[96], uint64_t da, uint64_t db, int scale_d) {
  asm volatile("{\n.reg .pred p;\nsetp.ne.b32 p, %98, 0;\n"
    "wgmma.mma_async.sync.aligned.m64n192k16.f32.bf16.bf16 {%0, %1, %2, %3, %4, %5, %6, %7, %8, %9, %10, %11, %12, %13, %14, %15, %16, %17, %18, %19, %20, %21, %22, %23, %24, %25, %26, %27, %28, %29, %30, %31, %32, %33, %34, %35, %36, %37, %38, %39, %40, %41, %42, %43, %44, %45, %46, %47, %48, %49, %50, %51, %52, %53, %54, %55, %56, %57, %58, %59, %60, %61, %62, %63, %64, %65, %66, %67, %68, %69, %70, %71, %72, %73, %74, %75, %76, %77, %78, %79, %80, %81, %82, %83, %84, %85, %86, %87, %88, %89, %90, %91, %92, %93, %94, %95}, %96, %97, p, 1, 1, 0, 1;\n}\n"
    : "+f"(d[0]), "+f"(d[1]), "+f"(d[2]), "+f"(d[3]), "+f"(d[4]), "+f"(d[5]), "+f"(d[6]), "+f"(d[7]), "+f"(d[8]), "+f"(d[9]), "+f"(d[10]), "+f"(d[11]), "+f"(d[12]), "+f"(d[13]), "+f"(d[14]), "+f"(d[15]), "+f"(d[16]), "+f"(d[17]), "+f"(d[18]), "+f"(d[19]), "+f"(d[20]), "+f"(d[21]), "+f"(d[22]), "+f"(d[23]), "+f"(d[24]), "+f"(d[25]), "+f"(d[26]), "+f"(d[27]), "+f"(d[28]), "+f"(d[29]), "+f"(d[30]), "+f"(d[31]), "+f"(d[32]), "+f"(d[33]), "+f"(d[34]), "+f"(d[35]), "+f"(d[36]), "+f"(d[37]), "+f"(d[38]), "+f"(d[39]), "+f"(d[40]), "+f"(d[41]), "+f"(d[42]), "+f"(d[43]), "+f"(d[44]), "+f"(d[45]), "+f"(d[46]), "+f"(d[47]), "+f"(d[48]), "+f"(d[49]), "+f"(d[50]), "+f"(d[51]), "+f"(d[52]), "+f"(d[53]), "+f"(d[54]), "+f"(d[55]), "+f"(d[56]), "+f"(d[57]), "+f"(d[58]), "+f"(d[59]), "+f"(d[60]), "+f"(d[61]), "+f"(d[62]), "+f"(d[63]), "+f"(d[64]), "+f"(d[65]), "+f"(d[66]), "+f"(d[67]), "+f"(d[68]), "+f"(d[69]), "+f"(d[70]), "+f"(d[71]), "+f"(d[72]), "+f"(d[73]), "+f"(d[74]), "+f"(d[75]), "+f"(d[76]), "+f"(d[77]), "+f"(d[78]), "+f"(d[79]), "+f"(d[80]), "+f"(d[81]), "+f"(d[82]), "+f"(d[83]), "+f"(d[84]), "+f"(d[85]), "+f"(d[86]), "+f"(d[87]), "+f"(d[88]), "+f"(d[89]), "+f"(d[90]), "+f"(d[91]), "+f"(d[92]), "+f"(d[93]), "+f"(d[94]), "+f"(d[95])
    : "l"(da), "l"(db), "r"(scale_d));
}
__device__ __forceinline__ void wgmma_ss_n128(float (&d)[64], uint64_t da, uint64_t db, int scale_d) {
  asm volatile("{\n.reg .pred p;\nsetp.ne.b32 p, %66, 0;\n"
    "wgmma.mma_async.sync.aligned.m64n128k16.f32.bf16.bf16 {%0, %1, %2, %3, %4, %5, %6, %7, %8, %9, %10, %11, %12, %13, %14, %15, %16, %17, %18, %19, %20, %21, %22, %23, %24, %25, %26, %27, %28, %29, %30, %31, %32, %33, %34, %35, %36, %37, %38, %39, %40, %41, %42, %43, %44, %45, %46, %47, %48, %49, %50, %51, %52, %53, %54, %55, %56, %57, %58, %59, %60, %61, %62, %63}, %64, %65, p, 1, 1, 0, 1;\n}\n"
    : "+f"(d[0]), "+f"(d[1]), "+f"(d[2]), "+f"(d[3]), "+f"(d[4]), "+f"(d[5]), "+f"(d[6]), "+f"(d[7]), "+f"(d[8]), "+f"(d[9]), "+f"(d[10]), "+f"(d[11]), "+f"(d[12]), "+f"(d[13]), "+f"(d[14]), "+f"(d[15]), "+f"(d[16]), "+f"(d[17]), "+f"(d[18]), "+f"(d[19]), "+f"(d[20]), "+f"(d[21]), "+f"(d[22]), "+f"(d[23]), "+f"(d[24]), "+f"(d[25]), "+f"(d[26]), "+f"(d[27]), "+f"(d[28]), "+f"(d[29]), "+f"(d[30]), "+f"(d[31]), "+f"(d[32]), "+f"(d[33]), "+f"(d[34]), "+f"(d[35]), "+f"(d[36]), "+f"(d[37]), "+f"(d[38]), "+f"(d[39]), "+f"(d[40]), "+f"(d[41]), "+f"(d[42]), "+f"(d[43]), "+f"(d[44]), "+f"(d[45]), "+f"(d[46]), "+f"(d[47]), "+f"(d[48]), "+f"(d[49]), "+f"(d[50]), "+f"(d[51]), "+f"(d[52]), "+f"(d[53]), "+f"(d[54]), "+f"(d[55]), "+f"(d[56]), "+f"(d[57]), "+f"(d[58]), "+f"(d[59]), "+f"(d[60]), "+f"(d[61]), "+f"(d[62]), "+f"(d[63])
    : "l"(da), "l"(db), "r"(scale_d));
}
__device__ __forceinline__ void wgmma_ss_n96(float (&d)[48], uint64_t da, uint64_t db, int scale_d) {
  asm volatile("{\n.reg .pred p;\nsetp.ne.b32 p, %50, 0;\n"
    "wgmma.mma_async.sync.aligned.m64n96k16.f32.bf16.bf16 {%0, %1, %2, %3, %4, %5, %6, %7, %8, %9, %10, %11, %12, %13, %14, %15, %16, %17, %18, %19, %20, %21, %22, %23, %24, %25, %26, %27, %28, %29, %30, %31, %32, %33, %34, %35, %36, %37, %38, %39, %40, %41, %42, %43, %44, %45, %46, %47}, %48, %49, p, 1, 1, 0, 1;\n}\n"
    : "+f"(d[0]), "+f"(d[1]), "+f"(d[2]), "+f"(d[3]), "+f"(d[4]), "+f"(d[5]), "+f"(d[6]), "+f"(d[7]), "+f"(d[8]), "+f"(d[9]), "+f"(d[10]), "+f"(d[11]), "+f"(d[12]), "+f"(d[13]), "+f"(d[14]), "+f"(d[15]), "+f"(d[16]), "+f"(d[17]), "+f"(d[18]), "+f"(d[19]), "+f"(d[20]), "+f"(d[21]), "+f"(d[22]), "+f"(d[23]), "+f"(d[24]), "+f"(d[25]), "+f"(d[26]), "+f"(d[27]), "+f"(d[28]), "+f"(d[29]), "+f"(d[30]), "+f"(d[31]), "+f"(d[32]), "+f"(d[33]), "+f"(d[34]), "+f"(d[35]), "+f"(d[36]), "+f"(d[37]), "+f"(d[38]), "+f"(d[39]), "+f"(d[40]), "+f"(d[41]), "+f"(d[42]), "+f"(d[43]), "+f"(d[44]), "+f"(d[45]), "+f"(d[46]), "+f"(d[47])
    : "l"(da), "l"(db), "r"(scale_d));
}
__device__ __forceinline__ void wgmma_rs_n128(float (&d)[64], uint32_t a0, uint32_t a1, uint32_t a2, uint32_t a3, uint64_t db, int scale_d) {
  asm volatile("{\n.reg .pred p;\nsetp.ne.b32 p, %69, 0;\n"
    "wgmma.mma_async.sync.aligned.m64n128k16.f32.bf16.bf16 {%0, %1, %2, %3, %4, %5, %6, %7, %8, %9, %10, %11, %12, %13, %14, %15, %16, %17, %18, %19, %20, %21, %22, %23, %24, %25, %26, %27, %28, %29, %30, %31, %32, %33, %34, %35, %36, %37, %38, %39, %40, %41, %42, %43, %44, %45, %46, %47, %48, %49, %50, %51, %52, %53, %54, %55, %56, %57, %58, %59, %60, %61, %62, %63}, {%64, %65, %66, %67}, %68, p, 1, 1, 1;\n}\n"
    : "+f"(d[0]), "+f"(d[1]), "+f"(d[2]), "+f"(d[3]), "+f"(d[4]), "+f"(d[5]), "+f"(d[6]), "+f"(d[7]), "+f"(d[8]), "+f"(d[9]), "+f"(d[10]), "+f"(d[11]), "+f"(d[12]), "+f"(d[13]), "+f"(d[14]), "+f"(d[15]), "+f"(d[16]), "+f"(d[17]), "+f"(d[18]), "+f"(d[19]), "+f"(d[20]), "+f"(d[21]), "+f"(d[22]), "+f"(d[23]), "+f"(d[24]), "+f"(d[25]), "+f"(d[26]), "+f"(d[27]), "+f"(d[28]), "+f"(d[29]), "+f"(d[30]), "+f"(d[31]), "+f"(d[32]), "+f"(d[33]), "+f"(d[34]), "+f"(d[35]), "+f"(d[36]), "+f"(d[37]), "+f"(d[38]), "+f"(d[39]), "+f"(d[40]), "+f"(d[41]), "+f"(d[42]), "+f"(d[43]), "+f"(d[44]), "+f"(d[45]), "+f"(d[46]), "+f"(d[47]), "+f"(d[48]), "+f"(d[49]), "+f"(d[50]), "+f"(d[51]), "+f"(d[52]), "+f"(d[53]), "+f"(d[54]), "+f"(d[55]), "+f"(d[56]), "+f"(d[57]), "+f"(d[58]), "+f"(d[59]), "+f"(d[60]), "+f"(d[61]), "+f"(d[62]), "+f"(d[63])
    : "r"(a0), "r"(a1), "r"(a2), "r"(a3), "l"(db), "r"(scale_d));
}
__device__ __forceinline__ void wgmma_rs_n64(float (&d)[32], uint32_t a0, uint32_t a1, uint32_t a2, uint32_t a3, uint64_t db, int scale_d) {
  asm volatile("{\n.reg .pred p;\nsetp.ne.b32 p, %37, 0;\n"
    "wgmma.mma_async.sync.aligned.m64n64k16.f32.bf16.bf16 {%0, %1, %2, %3, %4, %5, %6, %7, %8, %9, %10, %11, %12, %13, %14, %15, %16, %17, %18, %19, %20, %21, %22, %23, %24, %25, %26, %27, %28, %29, %30, %31}, {%32, %33, %34, %35}, %36, p, 1, 1, 1;\n}\n"
    : "+f"(d[0]), "+f"(d[1]), "+f"(d[2]), "+f"(d[3]), "+f"(d[4]), "+f"(d[5]), "+f"(d[6]), "+f"(d[7]), "+f"(d[8]), "+f"(d[9]), "+f"(d[10]), "+f"(d[11]), "+f"(d[12]), "+f"(d[13]), "+f"(d[14]), "+f"(d[15]), "+f"(d[16]), "+f"(d[17]), "+f"(d[18]), "+f"(d[19]), "+f"(d[20]), "+f"(d[21]), "+f"(d[22]), "+f"(d[23]), "+f"(d[24]), "+f"(d[25]), "+f"(d[26]), "+f"(d[27]), "+f"(d[28]), "+f"(d[29]), "+f"(d[30]), "+f"(d[31])
    : "r"(a0), "r"(a1), "r"(a2), "r"(a3), "l"(db), "r"(scale_d));
}

__device__ __forceinline__ float phi_f(float t) {
  float e = ex2(t * 1.4426950408889634f);
  return (t > 0.f ? t + 1.f : e) + 1e-6f;
}
__device__ __forceinline__ float mish_f(float h) {
  float u = ex2(fminf(h, 20.f) * 1.4426950408889634f);
  float n = u * (u + 2.f);
  return h * n * rcp(n + 2.f);
}
__device__ __forceinline__ float silu_f(float y) { return y * rcp(1.f + ex2(-y * 1.4426950408889634f)); }

struct Ring {
  int slot; uint32_t phase;
  __device__ __forceinline__ void next() { if (++slot == NSLOT) { slot = 0; phase ^= 1; } }
};

__device__ __forceinline__ void mish_tile(const float* c, uint32_t bias_addr, float rs0, float rs1, uint4* dst) {
  const float2 ba = lds_f32x2(bias_addr);
  const float2 bb = lds_f32x2(bias_addr + 32);
  uint32_t a0 = pack2(mish_f(fmaf(c[0], rs0, ba.x)), mish_f(fmaf(c[1], rs0, ba.y)));
  uint32_t a1 = pack2(mish_f(fmaf(c[2], rs1, ba.x)), mish_f(fmaf(c[3], rs1, ba.y)));
  uint32_t a2 = pack2(mish_f(fmaf(c[4], rs0, bb.x)), mish_f(fmaf(c[5], rs0, bb.y)));
  uint32_t a3 = pack2(mish_f(fmaf(c[6], rs1, bb.x)), mish_f(fmaf(c[7], rs1, bb.y)));
  stg_v4(dst, a0, a1, a2, a3);
}

__global__ void __launch_bounds__(384, 1)
fused_kernel(const __grid_constant__ CUtensorMap tm_qkv, const __grid_constant__ CUtensorMap tm_w1,
             const __grid_constant__ CUtensorMap tm_w2a, const __grid_constant__ CUtensorMap tm_w2b,
             const __grid_constant__ CUtensorMap tm_wo,
             const __nv_bfloat16* __restrict__ x, const __nv_bfloat16* __restrict__ b1, __nv_bfloat16* __restrict__ out) {
  extern __shared__ uint8_t smem_raw[];
  const uint32_t sb = (smem_u32(smem_raw) + 1023u) & ~1023u;
  uint8_t* sgen = smem_raw + (sb - smem_u32(smem_raw));
  const int tid = threadIdx.x, warp = tid >> 5, lane = tid & 31;
  const int bid = blockIdx.x;
  const int G = bid >> 4, gi = bid & 15;
  const int khalf = G & 1;
  const int rb = (G >> 1) * 4 + (gi >> 2);
  const int nt = gi & 3;
  const int j = khalf + 2 * nt;
  const uint32_t bar0 = sb + OFF_BAR;
  PROF(0);

  if (warp >= 8) {
    asm volatile("setmaxnreg.dec.sync.aligned.u32 40;");
    if (warp == 8) {
      if (lane == 0) {
        for (int i = 0; i < NSLOT; i++) { mbar_init(bar0 + 8 * (BAR_FULL + i), 1); mbar_init(bar0 + 8 * (BAR_EMPTY + i), 8); }
        mbar_init(bar0 + 8 * BAR_DREADY, 8);
        mbar_init(bar0 + 8 * BAR_STATS, 3);
        for (int i = BAR_PUB_A; i <= BAR_PUB_Y; i++) mbar_init(bar0 + 8 * i, 8);
        for (int i = BAR_RDY_A; i <= BAR_RDY_Y; i++) mbar_init(bar0 + 8 * i, 1);
        asm volatile("fence.mbarrier_init.release.cluster;" ::: "memory");
        asm volatile("fence.proxy.async.shared::cta;" ::: "memory");
      }
      __syncwarp();
      const int c_own = 128 * nt + 64 * khalf, c_par = 128 * nt + 64 * (1 - khalf);
      Ring r{0, 1};
      for (int st = 0; st < NSTAGES; st++) {
        if (st == NSLOT) named_bar_sync(0, 384);
        if (lane == 0) {
          const uint32_t full = bar0 + 8 * (BAR_FULL + r.slot);
          const uint32_t dst = sb + OFF_RING + r.slot * SLOT_BYTES;
          mbar_wait(bar0 + 8 * (BAR_EMPTY + r.slot), r.phase);
          if (st < 8) {
            mbar_expect_tx(full, 16384);
            const int k0 = 64 * st, c0 = 224 * j;
            tma2d(dst, &tm_w1, c0, k0, full);
            tma2d(dst + 8192, &tm_w1, c0 + 64, k0, full);
          } else if (st < 24) {
            mbar_expect_tx(full, 12288);
            const int k0 = 32 * (st - 8);
            tma2d(dst, &tm_qkv, 64 * j, k0, full);
            tma2d(dst + 4096, &tm_qkv, 512 + 64 * j, k0, full);
            tma2d(dst + 8192, &tm_qkv, 1024 + 64 * j, k0, full);
          } else if (st < 32) {
            mbar_expect_tx(full, 16384);
            const int k0 = 64 * (st - 24), c0 = 224 * j + 128;
            tma2d(dst, &tm_w1, c0, k0, full);
            tma2d(dst + 8192, &tm_w1, c0 + 64, k0, full);
          } else if (st < 40) {
            mbar_expect_tx(full, 16384);
            const int i = st - 32;
            const int k0 = 224 * (4 * khalf + (i >> 1)) + 64 * (i & 1);
            tma2d(dst, &tm_w2a, c_own, k0, full);
            tma2d(dst + 8192, &tm_w2a, c_par, k0, full);
          } else if (st < 48) {
            mbar_expect_tx(full, 12288);
            const int i = st - 40;
            const int k0 = 224 * (4 * khalf + (i >> 1)) + 128 + 48 * (i & 1);
            tma2d(dst, &tm_w2b, c_own, k0, full);
            tma2d(dst + 6144, &tm_w2b, c_par, k0, full);
          } else {
            mbar_expect_tx(full, 8192);
            tma2d(dst, &tm_wo, c_own, 64 * (st - 48), full);
          }
        }
        __syncwarp();
        r.next();
      }
    } else {
      const int aw = warp - 9;
      unsigned ep1;
      {
        unsigned dn; asm volatile("ld.relaxed.gpu.global.u32 %0, [%1];" : "=r"(dn) : "l"(&g_done) : "memory");
        ep1 = dn / NCTA + 1u;
      }
      for (int i = aw * 32 + lane; i < 224; i += 96) reinterpret_cast<float*>(sgen + OFF_B1)[i] = __bfloat162float(b1[224 * j + i]);
      if (aw == 0 && lane == 0) *reinterpret_cast<volatile unsigned*>(sgen + OFF_EPOCH) = ep1;
      if (rb == 0) {
        float4* z = reinterpret_cast<float4*>(&g_kv[ep1 & 1][4 * j * 272]);
        for (int i = aw * 32 + lane; i < 272; i += 96) z[i] = make_float4(0.f, 0.f, 0.f, 0.f);
      }
      named_bar_sync(0, 384);
      mbar_wait(bar0 + 8 * BAR_DREADY, 0);
      for (int it = aw * 32 + lane; it < 256; it += 96) {
        const int row = it >> 1, hf = it & 1;
        const uint32_t base = sb + OFF_D + hf * 65536 + row * 128;
        float a0 = 0.f, a1 = 0.f, a2 = 0.f, a3 = 0.f;
#pragma unroll 1
        for (int c = 0; c < 4; c++) {
#pragma unroll
          for (int u = 0; u < 8; u++) {
            const uint4 v = lds_v4(base + c * 16384 + (uint32_t)((u ^ (hf << 2) ^ (row & 7)) << 4));
            float f;
            f = bf_lo(v.x); a0 = fmaf(f, f, a0); f = bf_hi(v.x); a1 = fmaf(f, f, a1);
            f = bf_lo(v.y); a2 = fmaf(f, f, a2); f = bf_hi(v.y); a3 = fmaf(f, f, a3);
            f = bf_lo(v.z); a0 = fmaf(f, f, a0); f = bf_hi(v.z); a1 = fmaf(f, f, a1);
            f = bf_lo(v.w); a2 = fmaf(f, f, a2); f = bf_hi(v.w); a3 = fmaf(f, f, a3);
          }
        }
        float s = (a0 + a1) + (a2 + a3);
        s += __shfl_xor_sync(__activemask(), s, 1);
        if (hf == 0) {
          const float dl = lds_f32(sb + OFF_DELTA + row * 4);
          const float var = fmaxf(s * (1.f / DM) - dl * dl, 0.f);
          sts_f32(sb + OFF_RSTD + row * 4, rsqrtf(var + 1e-5f));
        }
      }
      __syncwarp();
      if (lane == 0) mbar_arrive(bar0 + 8 * BAR_STATS);
      PROF(1);
      if (aw == 0) {
        if (lane == 0) {
          mbar_wait(bar0 + 8 * BAR_PUB_A, 0);  __threadfence(); red_inc(&g_cntA[(rb * 2 + (j >> 2)) * 8]);
          mbar_wait(bar0 + 8 * BAR_PUB_KV, 0); __threadfence(); red_inc(&g_cntKV[j * 8]);
          mbar_wait(bar0 + 8 * BAR_PUB_B, 0);  __threadfence(); red_inc(&g_cntB[(rb * 2 + (j >> 2)) * 8]);
          mbar_wait(bar0 + 8 * BAR_PUB_Y, 0);  __threadfence(); red_inc(&g_flagY[bid * 8]);
        }
      } else if (aw == 1) {
        if (lane == 0) {
          poll_ge(&g_cntA[(rb * 2 + khalf) * 8], 4u * ep1); mbar_arrive(bar0 + 8 * BAR_RDY_A);
          poll_ge(&g_cntB[(rb * 2 + khalf) * 8], 4u * ep1); mbar_arrive(bar0 + 8 * BAR_RDY_B);
          poll_ge(&g_cntO[rb * 8], 8u * ep1);               mbar_arrive(bar0 + 8 * BAR_RDY_O);
          poll_ge(&g_flagY[(bid ^ 16) * 8], ep1);           mbar_arrive(bar0 + 8 * BAR_RDY_Y);
        }
      } else {
        if (lane == 0) poll_ge(&g_cntKV[j * 8], 16u * ep1);
        __syncwarp();
        PROF(2);
        const float4* src = reinterpret_cast<const float4*>(&g_kv[(ep1 & 1) ^ 1][4 * j * 272]);
#pragma unroll 1
        for (int q0 = 0; q0 < 9; q0 += 3) {
          uint4 t[3];
#pragma unroll
          for (int q = 0; q < 3; q++) { const int i = (q0 + q) * 32 + lane; if (i < 272) t[q] = ldg_cg(src + i); }
#pragma unroll
          for (int q = 0; q < 3; q++) {
            const int i = (q0 + q) * 32 + lane;
            if (i < 272) {
              const int hh = i / 68, e4 = (i % 68) * 4;
              const float vals[4] = {__uint_as_float(t[q].x), __uint_as_float(t[q].y), __uint_as_float(t[q].z), __uint_as_float(t[q].w)};
              if (e4 < 256) {
                const int d = e4 >> 4, e = e4 & 15;
#pragma unroll
                for (int c = 0; c < 4; c++)
                  reinterpret_cast<__nv_bfloat16*>(sgen + OFF_KVT)[(hh * 16 + e + c) * 16 + d] = __float2bfloat16(vals[c]);
              } else {
#pragma unroll
                for (int c = 0; c < 4; c++)
                  reinterpret_cast<__nv_bfloat16*>(sgen + OFF_ZB)[hh * 16 + (e4 - 256) + c] = __float2bfloat16(vals[c]);
              }
            }
          }
        }
        __syncwarp();
        PROF(3);
        mbar_wait(bar0 + 8 * BAR_PQ, 0);
        const int g = lane >> 2, t = lane & 3;
#pragma unroll 1
        for (int hh = 0; hh < 4; hh++) {
          const uint32_t kb = sb + OFF_KVT + ((hh * 16 + g) * 16 + 2 * t) * 2;
          const uint32_t zb = sb + OFF_ZB + (hh * 16 + 2 * t) * 2;
          const uint32_t b00 = lds_u32(kb), b01 = lds_u32(kb + 16), b10 = lds_u32(kb + 256), b11 = lds_u32(kb + 256 + 16);
          const uint32_t z0 = lds_u32(zb), z1 = lds_u32(zb + 16);
#pragma unroll 2
          for (int w = 0; w < 8; w++) {
            const uint4 a = lds_v4(sb + OFF_D + (w * 4 + hh) * 512 + lane * 16);
            float n0[4] = {0.f, 0.f, 0.f, 0.f}, n1[4] = {0.f, 0.f, 0.f, 0.f}, dn[4] = {0.f, 0.f, 0.f, 0.f};
            mma16816(n0, a.x, a.y, a.z, a.w, b00, b01);
            mma16816(n1, a.x, a.y, a.z, a.w, b10, b11);
            mma16816(dn, a.x, a.y, a.z, a.w, z0, z1);
            const float i0 = __fdividef(1.f, dn[0] + 1e-6f), i1 = __fdividef(1.f, dn[2] + 1e-6f);
            stg_v4(g_o + (size_t)((rb * 8 + w) * 32 + 4 * j + hh) * 32 + lane,
                   pack2(n0[0] * i0, n0[1] * i0), pack2(n0[2] * i1, n0[3] * i1), pack2(n1[0] * i0, n1[1] * i0), pack2(n1[2] * i1, n1[3] * i1));
          }
        }
        __syncwarp();
        if (lane == 0) { __threadfence(); red_inc(&g_cntO[rb * 8]); }
        PROF(4);
      }
    }
  } else {
    asm volatile("setmaxnreg.inc.sync.aligned.u32 232;");
    const int wg = warp >> 2;
    const int g = lane >> 2, t = lane & 3;
    const int lr0 = warp * 16 + g;
    const int slab = rb * 8 + warp;
    {
      uint4 q[16], p[16];
      const __nv_bfloat16* xr0 = x + (size_t)(rb * 128 + lr0) * DM + 8 * t;
      const __nv_bfloat16* xr1 = xr0 + 8 * DM;
      const int par = g & 1;
#pragma unroll
      for (int c = 0; c < 16; c++) { q[c] = ldg_nc(xr0 + 32 * (c ^ par)); p[c] = ldg_nc(xr1 + 32 * (c ^ par)); }
      named_bar_sync(0, 384);
      float sm4[4][4];
#pragma unroll
      for (int a = 0; a < 4; a++) { sm4[a][0] = sm4[a][1] = sm4[a][2] = sm4[a][3] = 0.f; }
      const uint32_t ones = 0x3F803F80u;
#pragma unroll
      for (int c = 0; c < 16; c++) {
        mma16816(sm4[(2 * c) & 3], q[c].x, p[c].x, q[c].y, p[c].y, ones, ones);
        mma16816(sm4[(2 * c + 1) & 3], q[c].z, p[c].z, q[c].w, p[c].w, ones, ones);
      }
      const float m0 = (sm4[0][0] + sm4[1][0] + sm4[2][0] + sm4[3][0]) * (1.f / DM);
      const float m1 = (sm4[0][2] + sm4[1][2] + sm4[2][2] + sm4[3][2]) * (1.f / DM);
      const uint32_t mb0 = pack2(m0, m0), mb1 = pack2(m1, m1);
      const uint32_t rowa = sb + OFF_D + lr0 * 128, rowb = rowa + 1024;
#pragma unroll
      for (int c = 0; c < 16; c++) {
        const int cc = c ^ par;
        const uint32_t u = (uint32_t)(((cc & 1) * 4 + t) ^ g) * 16;
        const uint32_t off = (uint32_t)(cc >> 1) * 16384 + u;
        sts_v4(rowa + off, hsub2_bf16(q[c].x, mb0), hsub2_bf16(q[c].y, mb0), hsub2_bf16(q[c].z, mb0), hsub2_bf16(q[c].w, mb0));
        sts_v4(rowb + off, hsub2_bf16(p[c].x, mb1), hsub2_bf16(p[c].y, mb1), hsub2_bf16(p[c].z, mb1), hsub2_bf16(p[c].w, mb1));
      }
      if (t == 0) {
        sts_f32(sb + OFF_DELTA + lr0 * 4, m0 - bf_lo(mb0));
        sts_f32(sb + OFF_DELTA + (lr0 + 8) * 4, m1 - bf_lo(mb1));
      }
      asm volatile("fence.proxy.async.shared::cta;" ::: "memory");
      __syncwarp();
      if (lane == 0) mbar_arrive(bar0 + 8 * BAR_DREADY);
      named_bar_sync(1 + wg, 128);
      PROF(1);
    }
    Ring r{0, 0};
    const uint32_t a_base = sb + OFF_D + wg * 8192;
    const uint32_t ring_base = sb + OFF_RING;
    uint32_t prev_empty = 0;
    uint32_t bs;
#define STAGE_BEGIN() do { mbar_wait(bar0 + 8 * (BAR_FULL + r.slot), r.phase); bs = ring_base + r.slot * SLOT_BYTES; wg_fence(); } while (0)
#define STAGE_END() do { wg_commit(); wg_wait<1>(); if (lane == 0 && prev_empty) mbar_arrive(prev_empty); prev_empty = bar0 + 8 * (BAR_EMPTY + r.slot); r.next(); } while (0)
#define WARP_ARRIVE(b) do { __syncwarp(); if (lane == 0) mbar_arrive(bar0 + 8 * (b)); } while (0)

    uint4* act_out = g_act + (size_t)(slab * 112 + 14 * j) * 32 + lane;
    const uint32_t bias_addr = sb + OFF_B1 + 8 * t;
    float rs0, rs1;
    uint32_t pq[16];
    float pool[160];
    zero_regs(pool);
    float (&acca)[64] = reinterpret_cast<float (&)[64]>(pool[0]);
    float (&accq)[96] = reinterpret_cast<float (&)[96]>(pool[64]);
    float (&accb)[48] = reinterpret_cast<float (&)[48]>(pool[0]);
    float (&accy)[64] = reinterpret_cast<float (&)[64]>(pool[64]);
    float (&accs)[32] = reinterpret_cast<float (&)[32]>(pool[0]);

    for (int st = 0; st < 8; st++) {
      STAGE_BEGIN();
      const uint32_t as = a_base + st * 16384;
#pragma unroll
      for (int kk = 0; kk < 4; kk++)
        wgmma_ss_n128(acca, make_desc(as + kk * 32, 16, 1024), make_desc(bs + kk * 2048, 8192, 1024), 1);
      STAGE_END();
    }
    PROF(2);
#pragma unroll
    for (int st = 0; st < 8; st++) {
      STAGE_BEGIN();
      const uint32_t as = a_base + (st >> 1) * 16384 + (st & 1) * 64;
      wgmma_ss_n192(accq, make_desc(as, 16, 1024), make_desc(bs, 4096, 1024), 1);
      wgmma_ss_n192(accq, make_desc(as + 32, 16, 1024), make_desc(bs + 2048, 4096, 1024), 1);
      STAGE_END();
      if (st == 0) {
        fence_regs(acca);
        mbar_wait(bar0 + 8 * BAR_STATS, 0);
        rs0 = lds_f32(sb + OFF_RSTD + lr0 * 4);
        rs1 = lds_f32(sb + OFF_RSTD + (lr0 + 8) * 4);
      }
      mish_tile(acca + 8 * st, bias_addr + 64 * st, rs0, rs1, act_out + st * 32);
    }
    WARP_ARRIVE(BAR_PUB_A);
    PROF(3);
    for (int st = 8; st < 16; st++) {
      STAGE_BEGIN();
      const uint32_t as = a_base + (st >> 1) * 16384 + (st & 1) * 64;
      wgmma_ss_n192(accq, make_desc(as, 16, 1024), make_desc(bs, 4096, 1024), 1);
      wgmma_ss_n192(accq, make_desc(as + 32, 16, 1024), make_desc(bs + 2048, 4096, 1024), 1);
      STAGE_END();
    }
    PROF(4);
    {
      const unsigned ep1 = *reinterpret_cast<volatile unsigned*>(sgen + OFF_EPOCH);
      float* kvdst = &g_kv[(ep1 & 1) ^ 1][4 * j * 272];
      const uint32_t ones = 0x3F803F80u;
#pragma unroll
      for (int st = 0; st < 8; st++) {
        STAGE_BEGIN();
        const uint32_t as = a_base + st * 16384;
#pragma unroll
        for (int kk = 0; kk < 4; kk++)
          wgmma_ss_n96(accb, make_desc(as + kk * 32, 16, 1024), make_desc(bs + kk * 2048, 8192, 1024), (st | kk) != 0);
        STAGE_END();
        if (st == 0) fence_regs(accq);
        if (st < 4) {
          const int hh = st;
          uint32_t kt[2][2], vt[2][2];
#pragma unroll
          for (int db = 0; db < 2; db++) {
            const int nb = 8 + 2 * hh + db;
            kt[db][0] = movmat(pack2(phi_f(accq[4 * nb] * rs0), phi_f(accq[4 * nb + 1] * rs0)));
            kt[db][1] = movmat(pack2(phi_f(accq[4 * nb + 2] * rs1), phi_f(accq[4 * nb + 3] * rs1)));
            const int nv = 16 + 2 * hh + db;
            vt[db][0] = movmat(pack2(accq[4 * nv] * rs0, accq[4 * nv + 1] * rs0));
            vt[db][1] = movmat(pack2(accq[4 * nv + 2] * rs1, accq[4 * nv + 3] * rs1));
          }
          float* hb = kvdst + hh * 272;
#pragma unroll
          for (int eb = 0; eb < 2; eb++) {
            float c[4] = {0.f, 0.f, 0.f, 0.f};
            mma16816(c, kt[0][0], kt[1][0], kt[0][1], kt[1][1], vt[eb][0], vt[eb][1]);
            float* a0 = hb + g * 16 + eb * 8 + 2 * t;
            red_add_v2(a0, c[0], c[1]);
            red_add_v2(a0 + 128, c[2], c[3]);
          }
          float cz[4] = {0.f, 0.f, 0.f, 0.f};
          mma16816(cz, kt[0][0], kt[1][0], kt[0][1], kt[1][1], ones, ones);
          if (t == 0) { red_add_f32(hb + 256 + g, cz[0]); red_add_f32(hb + 264 + g, cz[2]); }
          if (st == 3) WARP_ARRIVE(BAR_PUB_KV);
        } else if (st < 6) {
#pragma unroll
          for (int nb = 4 * (st - 4); nb < 4 * (st - 4) + 4; nb++) {
            pq[2 * nb] = pack2(phi_f(accq[4 * nb] * rs0), phi_f(accq[4 * nb + 1] * rs0));
            pq[2 * nb + 1] = pack2(phi_f(accq[4 * nb + 2] * rs1), phi_f(accq[4 * nb + 3] * rs1));
          }
        }
      }
    }
    PROF(5);
    const uint4* act_in = g_act + (size_t)(slab * 112 + 56 * khalf) * 32 + lane;
    uint4 ab[3][4];
#pragma unroll
    for (int kk = 0; kk < 4; kk++) ab[2][kk] = make_uint4(0u, 0u, 0u, 0u);
    mbar_wait(bar0 + 8 * BAR_RDY_A, 0);
    PROF(6);
#pragma unroll
    for (int kk = 0; kk < 4; kk++) { ab[0][kk] = ldg_cg(act_in + kk * 32); ab[1][kk] = ldg_cg(act_in + (4 + kk) * 32); }
#pragma unroll
    for (int st = 0; st < 8; st++) {
      STAGE_BEGIN();
#pragma unroll
      for (int kk = 0; kk < 4; kk++) {
        const uint4 a = ab[st % 3][kk];
        wgmma_rs_n128(accy, a.x, a.y, a.z, a.w, make_desc(bs + kk * 2048, 8192, 1024), (st | kk) != 0);
      }
      STAGE_END();
      if (st == 0) {
        fence_regs(accb);
#pragma unroll
        for (int hh = 0; hh < 4; hh++)
          sts_v4(sb + OFF_D + (warp * 4 + hh) * 512 + lane * 16, pq[4 * hh], pq[4 * hh + 1], pq[4 * hh + 2], pq[4 * hh + 3]);
        WARP_ARRIVE(BAR_PQ);
      }
      if (st > 0) {
#pragma unroll
        for (int kk = 0; kk < 4; kk++) fence_u4(ab[(st + 2) % 3][kk]);
      }
      if (st + 2 < 8) {
        const int kt = 14 * ((st + 2) >> 1) + 4 * ((st + 2) & 1);
#pragma unroll
        for (int kk = 0; kk < 4; kk++) ab[(st + 2) % 3][kk] = ldg_cg(act_in + (kt + kk) * 32);
      } else {
        if (st == 6) mbar_wait(bar0 + 8 * BAR_RDY_B, 0);
        const int kt = 8 + 3 * (st - 6);
#pragma unroll
        for (int kk = 0; kk < 3; kk++) ab[(st + 2) % 3][kk] = ldg_cg(act_in + (kt + kk) * 32);
      }
      if (st < 3) {
        mish_tile(accb + 16 * st, bias_addr + 512 + 128 * st, rs0, rs1, act_out + (8 + 2 * st) * 32);
        mish_tile(accb + 16 * st + 8, bias_addr + 512 + 128 * st + 64, rs0, rs1, act_out + (9 + 2 * st) * 32);
        if (st == 2) WARP_ARRIVE(BAR_PUB_B);
      }
    }
    PROF(7);
    const uint4* o_in = g_o + (size_t)(slab * 32) * 32 + lane;
#pragma unroll
    for (int st = 0; st < 8; st++) {
      STAGE_BEGIN();
#pragma unroll
      for (int kk = 0; kk < 3; kk++) {
        const uint4 a = ab[(st + 8) % 3][kk];
        wgmma_rs_n128(accy, a.x, a.y, a.z, a.w, make_desc(bs + kk * 2048, 6144, 1024), 1);
      }
      STAGE_END();
#pragma unroll
      for (int kk = 0; kk < 4; kk++) fence_u4(ab[(st + 10) % 3][kk]);
      if (st + 2 < 8) {
        const int kt = 14 * ((st + 2) >> 1) + 8 + 3 * ((st + 2) & 1);
#pragma unroll
        for (int kk = 0; kk < 3; kk++) ab[(st + 10) % 3][kk] = ldg_cg(act_in + (kt + kk) * 32);
      } else {
        if (st == 6) mbar_wait(bar0 + 8 * BAR_RDY_O, 0);
#pragma unroll
        for (int kk = 0; kk < 4; kk++) ab[(st + 10) % 3][kk] = ldg_cg(o_in + (4 * (st - 6) + kk) * 32);
      }
    }
    PROF(8);
    const int c0 = 128 * nt + 64 * khalf + 2 * t;
    const size_t ro0 = (size_t)(rb * 128 + lr0) * DM + c0, ro1 = ro0 + 8 * DM;
    uint32_t xv[16];
#pragma unroll
    for (int st = 0; st < 8; st++) {
      STAGE_BEGIN();
#pragma unroll
      for (int kk = 0; kk < 4; kk++) {
        const uint4 a = ab[(st + 16) % 3][kk];
        wgmma_rs_n64(accs, a.x, a.y, a.z, a.w, make_desc(bs + kk * 2048, 8192, 1024), (st | kk) != 0);
      }
      STAGE_END();
#pragma unroll
      for (int kk = 0; kk < 4; kk++) fence_u4(ab[(st + 18) % 3][kk]);
      if (st + 2 < 8) {
#pragma unroll
        for (int kk = 0; kk < 4; kk++) ab[(st + 18) % 3][kk] = ldg_cg(o_in + (4 * (st + 2) + kk) * 32);
      }
      if (st == 0) {
        fence_regs(accy);
        float4* yp = g_yp + (size_t)((bid * 8 + warp) * 8) * 32 + lane;
#pragma unroll
        for (int q = 0; q < 8; q++)
          stg_v4(yp + q * 32, __float_as_uint(accy[32 + 4 * q]), __float_as_uint(accy[33 + 4 * q]), __float_as_uint(accy[34 + 4 * q]), __float_as_uint(accy[35 + 4 * q]));
        WARP_ARRIVE(BAR_PUB_Y);
      }
      if (st == 1) {
#pragma unroll
        for (int q = 0; q < 8; q++) { xv[2 * q] = ldg_nc32(x + ro0 + 8 * q); xv[2 * q + 1] = ldg_nc32(x + ro1 + 8 * q); }
      }
    }
    PROF(9);
    {
      mbar_wait(bar0 + 8 * BAR_RDY_Y, 0);
      PROF(10);
      const float4* yp = g_yp + (size_t)(((bid ^ 16) * 8 + warp) * 8) * 32 + lane;
      uint4 pv[8];
#pragma unroll
      for (int q = 0; q < 8; q++) pv[q] = ldg_cg(yp + q * 32);
      wg_wait<0>();
      fence_regs(accs);
#pragma unroll
      for (int q = 0; q < 8; q++) {
        const float y0 = accy[4 * q] + __uint_as_float(pv[q].x), y1 = accy[4 * q + 1] + __uint_as_float(pv[q].y);
        const float y2 = accy[4 * q + 2] + __uint_as_float(pv[q].z), y3 = accy[4 * q + 3] + __uint_as_float(pv[q].w);
        const float o0 = fmaf(accs[4 * q], silu_f(y0), bf_lo(xv[2 * q])), o1 = fmaf(accs[4 * q + 1], silu_f(y1), bf_hi(xv[2 * q]));
        const float o2 = fmaf(accs[4 * q + 2], silu_f(y2), bf_lo(xv[2 * q + 1])), o3 = fmaf(accs[4 * q + 3], silu_f(y3), bf_hi(xv[2 * q + 1]));
        *reinterpret_cast<uint32_t*>(out + ro0 + 8 * q) = pack2(o0, o1);
        *reinterpret_cast<uint32_t*>(out + ro1 + 8 * q) = pack2(o2, o3);
      }
    }
    PROF(11);
    if (tid == 0) red_inc(&g_done);
  }
}

typedef CUresult (*EncodeFn)(CUtensorMap*, CUtensorMapDataType, cuuint32_t, void*, const cuuint64_t*, const cuuint64_t*,
                             const cuuint32_t*, const cuuint32_t*, CUtensorMapInterleave, CUtensorMapSwizzle,
                             CUtensorMapL2promotion, CUtensorMapFloatOOBfill);

void make_map(EncodeFn enc, CUtensorMap* tm, const void* ptr, int rows, int cols, int box_rows) {
  cuuint64_t gd[2] = {(cuuint64_t)cols, (cuuint64_t)rows};
  cuuint64_t gs[1] = {(cuuint64_t)cols * 2};
  cuuint32_t bd[2] = {64, (cuuint32_t)box_rows};
  cuuint32_t es[2] = {1, 1};
  enc(tm, CU_TENSOR_MAP_DATA_TYPE_BFLOAT16, 2, const_cast<void*>(ptr), gd, gs, bd, es, CU_TENSOR_MAP_INTERLEAVE_NONE,
      CU_TENSOR_MAP_SWIZZLE_128B, CU_TENSOR_MAP_L2_PROMOTION_L2_128B, CU_TENSOR_MAP_FLOAT_OOB_FILL_NONE);
}

}

extern "C" void kernel_launch(void* const* d_in, const int* in_sizes, int n_in, void* d_out, int out_size) {
  const __nv_bfloat16* x = (const __nv_bfloat16*)d_in[0];
  const void* wqkv = d_in[1];
  const void* wo = d_in[2];
  const void* w1 = d_in[4];
  const __nv_bfloat16* b1 = (const __nv_bfloat16*)d_in[5];
  const void* w2 = d_in[6];
  static EncodeFn enc = nullptr;
  if (!enc) {
    cudaDriverEntryPointQueryResult qr;
    void* fn = nullptr;
    cudaGetDriverEntryPoint("cuTensorMapEncodeTiled", &fn, cudaEnableDefault, &qr);
    enc = (EncodeFn)fn;
    cudaFuncSetAttribute(fused_kernel, cudaFuncAttributeMaxDynamicSharedMemorySize, SMEM_ALLOC);
  }
  CUtensorMap tq, t1, t2a, t2b, to;
  make_map(enc, &tq, wqkv, DM, 3 * DM, 32);
  make_map(enc, &t1, w1, DM, FF, 64);
  make_map(enc, &t2a, w2, FF, DM, 64);
  make_map(enc, &t2b, w2, FF, DM, 48);
  make_map(enc, &to, wo, DM, DM, 64);
  fused_kernel<<<NCTA, 384, SMEM_ALLOC>>>(tq, t1, t2a, t2b, to, x, b1, (__nv_bfloat16*)d_out);
}
```

```cpp
#include <cuda_runtime.h>
#include <cuda_bf16.h>
#include <cuda.h>
#include <stdint.h>

namespace {

constexpr int DM = 512, FF = 1792;
constexpr int NCTA = 128;
constexpr int NSLOT = 5;
constexpr int SLOT_BYTES = 16384;
constexpr int OFF_D = 0;
constexpr int OFF_RING = 131072;
constexpr int OFF_MISC = OFF_RING + NSLOT * SLOT_BYTES;
constexpr int OFF_BAR = OFF_MISC;
constexpr int OFF_EPOCH = OFF_MISC + 256;
constexpr int OFF_RSTD = OFF_MISC + 512;
constexpr int OFF_DELTA = OFF_MISC + 1024;
constexpr int OFF_B1 = OFF_MISC + 1536;
constexpr int OFF_KVT = OFF_MISC + 2560;
constexpr int OFF_ZB = OFF_MISC + 4608;
constexpr int SMEM_USED = OFF_MISC + 4864;
constexpr int SMEM_ALLOC = SMEM_USED + 1024;

enum { BAR_FULL = 0, BAR_EMPTY = NSLOT, BAR_BIAS = 2 * NSLOT,
       BAR_PUB_A, BAR_PUB_B, BAR_PUB_Y, BAR_PQ,
       BAR_RDY_A, BAR_RDY_B, BAR_RDY_O, BAR_RDY_Y, BAR_COUNT };

constexpr int NSTAGES = 56;

__device__ uint4 g_act[128 * 112 * 32];
__device__ uint4 g_o[128 * 32 * 32];
__device__ float4 g_yp[NCTA * 8 * 8 * 32];
__device__ float g_kv[2][32 * 272];
__device__ unsigned g_cntA[16 * 2 * 8];
__device__ unsigned g_cntB[16 * 2 * 8];
__device__ unsigned g_cntO[16 * 8];
__device__ unsigned g_flagY[NCTA * 8];
__device__ unsigned g_cntKV[16 * 8];
__device__ unsigned g_done;

#define PROF(i)

__device__ __forceinline__ uint32_t smem_u32(const void* p) { return (uint32_t)__cvta_generic_to_shared(p); }
__device__ __forceinline__ void mbar_init(uint32_t bar, uint32_t cnt) { asm volatile("mbarrier.init.shared::cta.b64 [%0], %1;" ::"r"(bar), "r"(cnt)); }
__device__ __forceinline__ void mbar_expect_tx(uint32_t bar, uint32_t bytes) { asm volatile("mbarrier.arrive.expect_tx.shared::cta.b64 _, [%0], %1;" ::"r"(bar), "r"(bytes) : "memory"); }
__device__ __forceinline__ void mbar_arrive(uint32_t bar) { asm volatile("mbarrier.arrive.shared::cta.b64 _, [%0];" ::"r"(bar) : "memory"); }
__device__ __forceinline__ void mbar_wait(uint32_t bar, uint32_t parity) {
  asm volatile("{\n.reg .pred P1;\n.reg .u32 cnt;\n"
               "mbarrier.try_wait.parity.shared::cta.b64 P1, [%0], %1;\n@P1 bra DONE;\n"
               "mov.u32 cnt, 0;\n"
               "LAB_WAIT:\n"
               "mbarrier.try_wait.parity.shared::cta.b64 P1, [%0], %1;\n@P1 bra DONE;\n"
               "add.u32 cnt, cnt, 1;\nsetp.lt.u32 P1, cnt, 16777216;\n@P1 bra LAB_WAIT;\ntrap;\n"
               "DONE:\n}" ::"r"(bar), "r"(parity) : "memory");
}
__device__ __forceinline__ bool mbar_test(uint32_t bar, uint32_t parity) {
  uint32_t done;
  asm volatile("{\n.reg .pred p;\nmbarrier.test_wait.parity.shared::cta.b64 p, [%1], %2;\nselp.u32 %0, 1, 0, p;\n}" : "=r"(done) : "r"(bar), "r"(parity) : "memory");
  return done != 0;
}
__device__ __forceinline__ unsigned ld_acquire(const unsigned* p) {
  unsigned v; asm volatile("ld.acquire.gpu.global.u32 %0, [%1];" : "=r"(v) : "l"(p) : "memory"); return v;
}
__device__ __forceinline__ void tma2d(uint32_t dst, const CUtensorMap* tm, int c0, int c1, uint32_t bar) {
  asm volatile("cp.async.bulk.tensor.2d.shared::cluster.global.mbarrier::complete_tx::bytes [%0], [%1, {%3, %4}], [%2];" ::"r"(dst), "l"(tm), "r"(bar), "r"(c0), "r"(c1) : "memory");
}
__device__ __forceinline__ void wg_fence() { asm volatile("wgmma.fence.sync.aligned;" ::: "memory"); }
__device__ __forceinline__ void wg_commit() { asm volatile("wgmma.commit_group.sync.aligned;" ::: "memory"); }
template <int N> __device__ __forceinline__ void wg_wait() { asm volatile("wgmma.wait_group.sync.aligned %0;" ::"n"(N) : "memory"); }
template <int N> __device__ __forceinline__ void zero_regs(float (&d)[N]) {
#pragma unroll
  for (int i = 0; i < N; i++) d[i] = 0.f;
}
template <int N> __device__ __forceinline__ void fence_regs(float (&d)[N]) {
#pragma unroll
  for (int i = 0; i < N; i++) asm volatile("" : "+f"(d[i])::"memory");
}
__device__ __forceinline__ void fence_u4(uint4& v) { asm volatile("" : "+r"(v.x), "+r"(v.y), "+r"(v.z), "+r"(v.w)::"memory"); }
__device__ __forceinline__ void named_bar_sync(int id, int n) { asm volatile("bar.sync %0, %1;" ::"r"(id), "r"(n) : "memory"); }
__device__ __forceinline__ uint64_t make_desc(uint32_t addr, uint32_t lbo_bytes, uint32_t sbo_bytes) {
  return (uint64_t)((addr & 0x3FFFF) >> 4) | ((uint64_t)(lbo_bytes >> 4) << 16) | ((uint64_t)(sbo_bytes >> 4) << 32) | (1ull << 62);
}
__device__ __forceinline__ void mma16816(float (&c)[4], uint32_t a0, uint32_t a1, uint32_t a2, uint32_t a3, uint32_t b0, uint32_t b1) {
  asm volatile("mma.sync.aligned.m16n8k16.row.col.f32.bf16.bf16.f32 {%0,%1,%2,%3}, {%4,%5,%6,%7}, {%8,%9}, {%0,%1,%2,%3};"
               : "+f"(c[0]), "+f"(c[1]), "+f"(c[2]), "+f"(c[3]) : "r"(a0), "r"(a1), "r"(a2), "r"(a3), "r"(b0), "r"(b1));
}
__device__ __forceinline__ uint32_t movmat(uint32_t a) { uint32_t d; asm volatile("movmatrix.sync.aligned.m8n8.trans.b16 %0, %1;" : "=r"(d) : "r"(a)); return d; }
__device__ __forceinline__ uint32_t pack2(float lo, float hi) { uint32_t r; asm("cvt.rn.bf16x2.f32 %0, %1, %2;" : "=r"(r) : "f"(hi), "f"(lo)); return r; }
__device__ __forceinline__ float ex2(float x) { float r; asm("ex2.approx.ftz.f32 %0, %1;" : "=f"(r) : "f"(x)); return r; }
__device__ __forceinline__ float rcp(float x) { float r; asm("rcp.approx.ftz.f32 %0, %1;" : "=f"(r) : "f"(x)); return r; }
__device__ __forceinline__ float bf_lo(uint32_t v) { return __uint_as_float(v << 16); }
__device__ __forceinline__ float bf_hi(uint32_t v) { return __uint_as_float(v & 0xffff0000u); }
__device__ __forceinline__ uint32_t hsub2_bf16(uint32_t a, uint32_t b) {
  __nv_bfloat162 x = *reinterpret_cast<__nv_bfloat162*>(&a), y = *reinterpret_cast<__nv_bfloat162*>(&b);
  __nv_bfloat162 r = __hsub2(x, y);
  return *reinterpret_cast<uint32_t*>(&r);
}
__device__ __forceinline__ uint4 ldg_nc(const void* p) {
  uint4 v; asm volatile("ld.global.nc.L1::no_allocate.v4.u32 {%0,%1,%2,%3}, [%4];" : "=r"(v.x), "=r"(v.y), "=r"(v.z), "=r"(v.w) : "l"(p)); return v;
}
__device__ __forceinline__ uint32_t ldg_nc32(const void* p) {
  uint32_t v; asm volatile("ld.global.nc.u32 %0, [%1];" : "=r"(v) : "l"(p)); return v;
}
__device__ __forceinline__ uint4 ldg_cg(const void* p) {
  uint4 v; asm volatile("ld.global.cg.v4.u32 {%0,%1,%2,%3}, [%4];" : "=r"(v.x), "=r"(v.y), "=r"(v.z), "=r"(v.w) : "l"(p) : "memory"); return v;
}
__device__ __forceinline__ void stg_v4(void* p, uint32_t a, uint32_t b, uint32_t c, uint32_t d) {
  asm volatile("st.global.v4.u32 [%0], {%1,%2,%3,%4};" ::"l"(p), "r"(a), "r"(b), "r"(c), "r"(d) : "memory");
}
__device__ __forceinline__ void sts_v4(uint32_t addr, uint32_t a, uint32_t b, uint32_t c, uint32_t d) {
  asm volatile("st.shared.v4.u32 [%0], {%1,%2,%3,%4};" ::"r"(addr), "r"(a), "r"(b), "r"(c), "r"(d) : "memory");
}
__device__ __forceinline__ void sts_f32(uint32_t addr, float v) { asm volatile("st.shared.f32 [%0], %1;" ::"r"(addr), "f"(v) : "memory"); }
__device__ __forceinline__ uint4 lds_v4(uint32_t addr) { uint4 v; asm volatile("ld.shared.v4.u32 {%0,%1,%2,%3}, [%4];" : "=r"(v.x), "=r"(v.y), "=r"(v.z), "=r"(v.w) : "r"(addr) : "memory"); return v; }
__device__ __forceinline__ float lds_f32(uint32_t addr) { float v; asm volatile("ld.shared.f32 %0, [%1];" : "=f"(v) : "r"(addr) : "memory"); return v; }
__device__ __forceinline__ float2 lds_f32x2(uint32_t addr) { float2 v; asm volatile("ld.shared.v2.f32 {%0,%1}, [%2];" : "=f"(v.x), "=f"(v.y) : "r"(addr) : "memory"); return v; }
__device__ __forceinline__ uint32_t lds_u32(uint32_t addr) { uint32_t v; asm volatile("ld.shared.u32 %0, [%1];" : "=r"(v) : "r"(addr) : "memory"); return v; }
__device__ __forceinline__ void red_add_v2(float* p, float a, float b) { asm volatile("red.relaxed.gpu.global.add.v2.f32 [%0], {%1,%2};" ::"l"(p), "f"(a), "f"(b) : "memory"); }
__device__ __forceinline__ void red_add_f32(float* p, float a) { asm volatile("red.relaxed.gpu.global.add.f32 [%0], %1;" ::"l"(p), "f"(a) : "memory"); }
__device__ __forceinline__ void red_inc(unsigned* cnt) { asm volatile("red.relaxed.gpu.global.add.u32 [%0], 1;" ::"l"(cnt) : "memory"); }
__device__ __forceinline__ void poll_ge(const unsigned* cnt, unsigned target) {
  asm volatile("{\n.reg .pred P1;\n.reg .u32 cnt, v;\n.reg .s32 d;\n"
               "mov.u32 cnt, 0;\n"
               "LAB_POLL:\n"
               "ld.acquire.gpu.global.u32 v, [%0];\nsub.s32 d, v, %1;\nsetp.ge.s32 P1, d, 0;\n@P1 bra DONE;\n"
               "add.u32 cnt, cnt, 1;\nsetp.lt.u32 P1, cnt, 4194304;\n@P1 bra LAB_POLL;\ntrap;\n"
               "DONE:\n}" ::"l"(cnt), "r"(target) : "memory");
}

__device__ __forceinline__ void wgmma_ss_n192(float (&d)[96], uint64_t da, uint64_t db, int scale_d) {
  asm volatile("{\n.reg .pred p;\nsetp.ne.b32 p, %98, 0;\n"
    "wgmma.mma_async.sync.aligned.m64n192k16.f32.bf16.bf16 {%0, %1, %2, %3, %4, %5, %6, %7, %8, %9, %10, %11, %12, %13, %14, %15, %16, %17, %18, %19, %20, %21, %22, %23, %24, %25, %26, %27, %28, %29, %30, %31, %32, %33, %34, %35, %36, %37, %38, %39, %40, %41, %42, %43, %44, %45, %46, %47, %48, %49, %50, %51, %52, %53, %54, %55, %56, %57, %58, %59, %60, %61, %62, %63, %64, %65, %66, %67, %68, %69, %70, %71, %72, %73, %74, %75, %76, %77, %78, %79, %80, %81, %82, %83, %84, %85, %86, %87, %88, %89, %90, %91, %92, %93, %94, %95}, %96, %97, p, 1, 1, 0, 1;\n}\n"
    : "+f"(d[0]), "+f"(d[1]), "+f"(d[2]), "+f"(d[3]), "+f"(d[4]), "+f"(d[5]), "+f"(d[6]), "+f"(d[7]), "+f"(d[8]), "+f"(d[9]), "+f"(d[10]), "+f"(d[11]), "+f"(d[12]), "+f"(d[13]), "+f"(d[14]), "+f"(d[15]), "+f"(d[16]), "+f"(d[17]), "+f"(d[18]), "+f"(d[19]), "+f"(d[20]), "+f"(d[21]), "+f"(d[22]), "+f"(d[23]), "+f"(d[24]), "+f"(d[25]), "+f"(d[26]), "+f"(d[27]), "+f"(d[28]), "+f"(d[29]), "+f"(d[30]), "+f"(d[31]), "+f"(d[32]), "+f"(d[33]), "+f"(d[34]), "+f"(d[35]), "+f"(d[36]), "+f"(d[37]), "+f"(d[38]), "+f"(d[39]), "+f"(d[40]), "+f"(d[41]), "+f"(d[42]), "+f"(d[43]), "+f"(d[44]), "+f"(d[45]), "+f"(d[46]), "+f"(d[47]), "+f"(d[48]), "+f"(d[49]), "+f"(d[50]), "+f"(d[51]), "+f"(d[52]), "+f"(d[53]), "+f"(d[54]), "+f"(d[55]), "+f"(d[56]), "+f"(d[57]), "+f"(d[58]), "+f"(d[59]), "+f"(d[60]), "+f"(d[61]), "+f"(d[62]), "+f"(d[63]), "+f"(d[64]), "+f"(d[65]), "+f"(d[66]), "+f"(d[67]), "+f"(d[68]), "+f"(d[69]), "+f"(d[70]), "+f"(d[71]), "+f"(d[72]), "+f"(d[73]), "+f"(d[74]), "+f"(d[75]), "+f"(d[76]), "+f"(d[77]), "+f"(d[78]), "+f"(d[79]), "+f"(d[80]), "+f"(d[81]), "+f"(d[82]), "+f"(d[83]), "+f"(d[84]), "+f"(d[85]), "+f"(d[86]), "+f"(d[87]), "+f"(d[88]), "+f"(d[89]), "+f"(d[90]), "+f"(d[91]), "+f"(d[92]), "+f"(d[93]), "+f"(d[94]), "+f"(d[95])
    : "l"(da), "l"(db), "r"(scale_d));
}
__device__ __forceinline__ void wgmma_ss_n128(float (&d)[64], uint64_t da, uint64_t db, int scale_d) {
  asm volatile("{\n.reg .pred p;\nsetp.ne.b32 p, %66, 0;\n"
    "wgmma.mma_async.sync.aligned.m64n128k16.f32.bf16.bf16 {%0, %1, %2, %3, %4, %5, %6, %7, %8, %9, %10, %11, %12, %13, %14, %15, %16, %17, %18, %19, %20, %21, %22, %23, %24, %25, %26, %27, %28, %29, %30, %31, %32, %33, %34, %35, %36, %37, %38, %39, %40, %41, %42, %43, %44, %45, %46, %47, %48, %49, %50, %51, %52, %53, %54, %55, %56, %57, %58, %59, %60, %61, %62, %63}, %64, %65, p, 1, 1, 0, 1;\n}\n"
    : "+f"(d[0]), "+f"(d[1]), "+f"(d[2]), "+f"(d[3]), "+f"(d[4]), "+f"(d[5]), "+f"(d[6]), "+f"(d[7]), "+f"(d[8]), "+f"(d[9]), "+f"(d[10]), "+f"(d[11]), "+f"(d[12]), "+f"(d[13]), "+f"(d[14]), "+f"(d[15]), "+f"(d[16]), "+f"(d[17]), "+f"(d[18]), "+f"(d[19]), "+f"(d[20]), "+f"(d[21]), "+f"(d[22]), "+f"(d[23]), "+f"(d[24]), "+f"(d[25]), "+f"(d[26]), "+f"(d[27]), "+f"(d[28]), "+f"(d[29]), "+f"(d[30]), "+f"(d[31]), "+f"(d[32]), "+f"(d[33]), "+f"(d[34]), "+f"(d[35]), "+f"(d[36]), "+f"(d[37]), "+f"(d[38]), "+f"(d[39]), "+f"(d[40]), "+f"(d[41]), "+f"(d[42]), "+f"(d[43]), "+f"(d[44]), "+f"(d[45]), "+f"(d[46]), "+f"(d[47]), "+f"(d[48]), "+f"(d[49]), "+f"(d[50]), "+f"(d[51]), "+f"(d[52]), "+f"(d[53]), "+f"(d[54]), "+f"(d[55]), "+f"(d[56]), "+f"(d[57]), "+f"(d[58]), "+f"(d[59]), "+f"(d[60]), "+f"(d[61]), "+f"(d[62]), "+f"(d[63])
    : "l"(da), "l"(db), "r"(scale_d));
}
__device__ __forceinline__ void wgmma_ss_n96(float (&d)[48], uint64_t da, uint64_t db, int scale_d) {
  asm volatile("{\n.reg .pred p;\nsetp.ne.b32 p, %50, 0;\n"
    "wgmma.mma_async.sync.aligned.m64n96k16.f32.bf16.bf16 {%0, %1, %2, %3, %4, %5, %6, %7, %8, %9, %10, %11, %12, %13, %14, %15, %16, %17, %18, %19, %20, %21, %22, %23, %24, %25, %26, %27, %28, %29, %30, %31, %32, %33, %34, %35, %36, %37, %38, %39, %40, %41, %42, %43, %44, %45, %46, %47}, %48, %49, p, 1, 1, 0, 1;\n}\n"
    : "+f"(d[0]), "+f"(d[1]), "+f"(d[2]), "+f"(d[3]), "+f"(d[4]), "+f"(d[5]), "+f"(d[6]), "+f"(d[7]), "+f"(d[8]), "+f"(d[9]), "+f"(d[10]), "+f"(d[11]), "+f"(d[12]), "+f"(d[13]), "+f"(d[14]), "+f"(d[15]), "+f"(d[16]), "+f"(d[17]), "+f"(d[18]), "+f"(d[19]), "+f"(d[20]), "+f"(d[21]), "+f"(d[22]), "+f"(d[23]), "+f"(d[24]), "+f"(d[25]), "+f"(d[26]), "+f"(d[27]), "+f"(d[28]), "+f"(d[29]), "+f"(d[30]), "+f"(d[31]), "+f"(d[32]), "+f"(d[33]), "+f"(d[34]), "+f"(d[35]), "+f"(d[36]), "+f"(d[37]), "+f"(d[38]), "+f"(d[39]), "+f"(d[40]), "+f"(d[41]), "+f"(d[42]), "+f"(d[43]), "+f"(d[44]), "+f"(d[45]), "+f"(d[46]), "+f"(d[47])
    : "l"(da), "l"(db), "r"(scale_d));
}
__device__ __forceinline__ void wgmma_rs_n128(float (&d)[64], uint32_t a0, uint32_t a1, uint32_t a2, uint32_t a3, uint64_t db, int scale_d) {
  asm volatile("{\n.reg .pred p;\nsetp.ne.b32 p, %69, 0;\n"
    "wgmma.mma_async.sync.aligned.m64n128k16.f32.bf16.bf16 {%0, %1, %2, %3, %4, %5, %6, %7, %8, %9, %10, %11, %12, %13, %14, %15, %16, %17, %18, %19, %20, %21, %22, %23, %24, %25, %26, %27, %28, %29, %30, %31, %32, %33, %34, %35, %36, %37, %38, %39, %40, %41, %42, %43, %44, %45, %46, %47, %48, %49, %50, %51, %52, %53, %54, %55, %56, %57, %58, %59, %60, %61, %62, %63}, {%64, %65, %66, %67}, %68, p, 1, 1, 1;\n}\n"
    : "+f"(d[0]), "+f"(d[1]), "+f"(d[2]), "+f"(d[3]), "+f"(d[4]), "+f"(d[5]), "+f"(d[6]), "+f"(d[7]), "+f"(d[8]), "+f"(d[9]), "+f"(d[10]), "+f"(d[11]), "+f"(d[12]), "+f"(d[13]), "+f"(d[14]), "+f"(d[15]), "+f"(d[16]), "+f"(d[17]), "+f"(d[18]), "+f"(d[19]), "+f"(d[20]), "+f"(d[21]), "+f"(d[22]), "+f"(d[23]), "+f"(d[24]), "+f"(d[25]), "+f"(d[26]), "+f"(d[27]), "+f"(d[28]), "+f"(d[29]), "+f"(d[30]), "+f"(d[31]), "+f"(d[32]), "+f"(d[33]), "+f"(d[34]), "+f"(d[35]), "+f"(d[36]), "+f"(d[37]), "+f"(d[38]), "+f"(d[39]), "+f"(d[40]), "+f"(d[41]), "+f"(d[42]), "+f"(d[43]), "+f"(d[44]), "+f"(d[45]), "+f"(d[46]), "+f"(d[47]), "+f"(d[48]), "+f"(d[49]), "+f"(d[50]), "+f"(d[51]), "+f"(d[52]), "+f"(d[53]), "+f"(d[54]), "+f"(d[55]), "+f"(d[56]), "+f"(d[57]), "+f"(d[58]), "+f"(d[59]), "+f"(d[60]), "+f"(d[61]), "+f"(d[62]), "+f"(d[63])
    : "r"(a0), "r"(a1), "r"(a2), "r"(a3), "l"(db), "r"(scale_d));
}
__device__ __forceinline__ void wgmma_rs_n64(float (&d)[32], uint32_t a0, uint32_t a1, uint32_t a2, uint32_t a3, uint64_t db, int scale_d) {
  asm volatile("{\n.reg .pred p;\nsetp.ne.b32 p, %37, 0;\n"
    "wgmma.mma_async.sync.aligned.m64n64k16.f32.bf16.bf16 {%0, %1, %2, %3, %4, %5, %6, %7, %8, %9, %10, %11, %12, %13, %14, %15, %16, %17, %18, %19, %20, %21, %22, %23, %24, %25, %26, %27, %28, %29, %30, %31}, {%32, %33, %34, %35}, %36, p, 1, 1, 1;\n}\n"
    : "+f"(d[0]), "+f"(d[1]), "+f"(d[2]), "+f"(d[3]), "+f"(d[4]), "+f"(d[5]), "+f"(d[6]), "+f"(d[7]), "+f"(d[8]), "+f"(d[9]), "+f"(d[10]), "+f"(d[11]), "+f"(d[12]), "+f"(d[13]), "+f"(d[14]), "+f"(d[15]), "+f"(d[16]), "+f"(d[17]), "+f"(d[18]), "+f"(d[19]), "+f"(d[20]), "+f"(d[21]), "+f"(d[22]), "+f"(d[23]), "+f"(d[24]), "+f"(d[25]), "+f"(d[26]), "+f"(d[27]), "+f"(d[28]), "+f"(d[29]), "+f"(d[30]), "+f"(d[31])
    : "r"(a0), "r"(a1), "r"(a2), "r"(a3), "l"(db), "r"(scale_d));
}

__device__ __forceinline__ float phi_f(float t) {
  float e = ex2(t * 1.4426950408889634f);
  return (t > 0.f ? t + 1.f : e) + 1e-6f;
}
__device__ __forceinline__ float mish_f(float h) {
  float u = ex2(fminf(h, 20.f) * 1.4426950408889634f);
  float n = u * (u + 2.f);
  return h * n * rcp(n + 2.f);
}
__device__ __forceinline__ float silu_f(float y) { return y * rcp(1.f + ex2(-y * 1.4426950408889634f)); }

struct Ring {
  int slot; uint32_t phase;
  __device__ __forceinline__ void next() { if (++slot == NSLOT) { slot = 0; phase ^= 1; } }
};

__device__ __forceinline__ void mish_tile(const float* c, uint32_t bias_addr, float rs0, float rs1, uint4* dst) {
  const float2 ba = lds_f32x2(bias_addr);
  const float2 bb = lds_f32x2(bias_addr + 32);
  uint32_t a0 = pack2(mish_f(fmaf(c[0], rs0, ba.x)), mish_f(fmaf(c[1], rs0, ba.y)));
  uint32_t a1 = pack2(mish_f(fmaf(c[2], rs1, ba.x)), mish_f(fmaf(c[3], rs1, ba.y)));
  uint32_t a2 = pack2(mish_f(fmaf(c[4], rs0, bb.x)), mish_f(fmaf(c[5], rs0, bb.y)));
  uint32_t a3 = pack2(mish_f(fmaf(c[6], rs1, bb.x)), mish_f(fmaf(c[7], rs1, bb.y)));
  stg_v4(dst, a0, a1, a2, a3);
}

__global__ void __launch_bounds__(384, 1)
fused_kernel(const __grid_constant__ CUtensorMap tm_qkv, const __grid_constant__ CUtensorMap tm_w1,
             const __grid_constant__ CUtensorMap tm_w2a, const __grid_constant__ CUtensorMap tm_w2b,
             const __grid_constant__ CUtensorMap tm_wo,
             const __nv_bfloat16* __restrict__ x, const __nv_bfloat16* __restrict__ b1, __nv_bfloat16* __restrict__ out) {
  extern __shared__ uint8_t smem_raw[];
  const uint32_t sb = (smem_u32(smem_raw) + 1023u) & ~1023u;
  uint8_t* sgen = smem_raw + (sb - smem_u32(smem_raw));
  const int tid = threadIdx.x, warp = tid >> 5, lane = tid & 31;
  const int bid = blockIdx.x;
  const int G = bid >> 4, gi = bid & 15;
  const int khalf = G & 1;
  const int rb = (G >> 1) * 4 + (gi >> 2);
  const int nt = gi & 3;
  const int j = khalf + 2 * nt;
  const uint32_t bar0 = sb + OFF_BAR;
  PROF(0);

  if (warp >= 8) {
    asm volatile("setmaxnreg.dec.sync.aligned.u32 40;");
    if (warp == 8) {
      if (lane == 0) {
        for (int i = 0; i < NSLOT; i++) { mbar_init(bar0 + 8 * (BAR_FULL + i), 1); mbar_init(bar0 + 8 * (BAR_EMPTY + i), 8); }
        mbar_init(bar0 + 8 * BAR_BIAS, 1);
        for (int i = BAR_PUB_A; i <= BAR_PQ; i++) mbar_init(bar0 + 8 * i, 8);
        for (int i = BAR_RDY_A; i <= BAR_RDY_Y; i++) mbar_init(bar0 + 8 * i, 1);
        asm volatile("fence.mbarrier_init.release.cluster;" ::: "memory");
        asm volatile("fence.proxy.async.shared::cta;" ::: "memory");
      }
      __syncwarp();
      const int c_own = 128 * nt + 64 * khalf, c_par = 128 * nt + 64 * (1 - khalf);
      Ring r{0, 1};
      for (int st = 0; st < NSTAGES; st++) {
        if (st == NSLOT) named_bar_sync(0, 384);
        if (lane == 0) {
          const uint32_t full = bar0 + 8 * (BAR_FULL + r.slot);
          const uint32_t dst = sb + OFF_RING + r.slot * SLOT_BYTES;
          mbar_wait(bar0 + 8 * (BAR_EMPTY + r.slot), r.phase);
          if (st < 8) {
            mbar_expect_tx(full, 16384);
            const int k0 = 64 * st, c0 = 224 * j;
            tma2d(dst, &tm_w1, c0, k0, full);
            tma2d(dst + 8192, &tm_w1, c0 + 64, k0, full);
          } else if (st < 24) {
            mbar_expect_tx(full, 12288);
            const int k0 = 32 * (st - 8);
            tma2d(dst, &tm_qkv, 64 * j, k0, full);
            tma2d(dst + 4096, &tm_qkv, 512 + 64 * j, k0, full);
            tma2d(dst + 8192, &tm_qkv, 1024 + 64 * j, k0, full);
          } else if (st < 32) {
            mbar_expect_tx(full, 16384);
            const int k0 = 64 * (st - 24), c0 = 224 * j + 128;
            tma2d(dst, &tm_w1, c0, k0, full);
            tma2d(dst + 8192, &tm_w1, c0 + 64, k0, full);
          } else if (st < 40) {
            mbar_expect_tx(full, 16384);
            const int i = st - 32;
            const int k0 = 224 * (4 * khalf + (i >> 1)) + 64 * (i & 1);
            tma2d(dst, &tm_w2a, c_own, k0, full);
            tma2d(dst + 8192, &tm_w2a, c_par, k0, full);
          } else if (st < 48) {
            mbar_expect_tx(full, 12288);
            const int i = st - 40;
            const int k0 = 224 * (4 * khalf + (i >> 1)) + 128 + 48 * (i & 1);
            tma2d(dst, &tm_w2b, c_own, k0, full);
            tma2d(dst + 6144, &tm_w2b, c_par, k0, full);
          } else {
            mbar_expect_tx(full, 8192);
            tma2d(dst, &tm_wo, c_own, 64 * (st - 48), full);
          }
        }
        __syncwarp();
        r.next();
      }
    } else {
      const int aw = warp - 9;
      unsigned dn; asm volatile("ld.relaxed.gpu.global.u32 %0, [%1];" : "=r"(dn) : "l"(&g_done) : "memory");
      named_bar_sync(0, 384);
      const unsigned ep1 = dn / NCTA + 1u;
      if (aw == 0) {
        for (int i = lane; i < 224; i += 32) reinterpret_cast<float*>(sgen + OFF_B1)[i] = __bfloat162float(b1[224 * j + i]);
        __syncwarp();
        if (lane == 0) {
          mbar_arrive(bar0 + 8 * BAR_BIAS);
          unsigned* const pub_cnt[3] = {&g_cntA[(rb * 2 + (j >> 2)) * 8], &g_cntB[(rb * 2 + (j >> 2)) * 8], &g_flagY[bid * 8]};
          const unsigned* const rdy_cnt[4] = {&g_cntA[(rb * 2 + khalf) * 8], &g_cntB[(rb * 2 + khalf) * 8], &g_cntO[rb * 8], &g_flagY[(bid ^ 16) * 8]};
          int pi = 0, ri = 0; uint32_t it = 0;
          while (pi < 3 || ri < 4) {
            if (pi < 3 && mbar_test(bar0 + 8 * (BAR_PUB_A + pi), 0)) {
              __threadfence();
              red_inc(pi == 0 ? pub_cnt[0] : pi == 1 ? pub_cnt[1] : pub_cnt[2]);
              pi++;
            }
            if (ri < 4) {
              const unsigned* c = ri == 0 ? rdy_cnt[0] : ri == 1 ? rdy_cnt[1] : ri == 2 ? rdy_cnt[2] : rdy_cnt[3];
              const unsigned tgt = (ri < 2 ? 4u : ri == 2 ? 16u : 1u) * ep1;
              if ((int)(ld_acquire(c) - tgt) >= 0) { mbar_arrive(bar0 + 8 * (BAR_RDY_A + ri)); ri++; }
            }
            if (++it > (1u << 22)) asm volatile("trap;");
          }
        }
      } else {
        const int h0 = 2 * (aw - 1);
        const int g = lane >> 2, t = lane & 3;
        if (rb == 0) {
          float4* z = reinterpret_cast<float4*>(&g_kv[ep1 & 1][(4 * j + h0) * 272]);
          for (int i = lane; i < 136; i += 32) z[i] = make_float4(0.f, 0.f, 0.f, 0.f);
        }
        float* kvbuf = &g_kv[(ep1 & 1) ^ 1][(4 * j + h0) * 272];
        const uint32_t ones = 0x3F803F80u;
        mbar_wait(bar0 + 8 * BAR_PQ, 0);
        PROF(1);
#pragma unroll 1
        for (int hh = 0; hh < 2; hh++) {
          float c0[4] = {0.f, 0.f, 0.f, 0.f}, c1[4] = {0.f, 0.f, 0.f, 0.f}, cz[4] = {0.f, 0.f, 0.f, 0.f};
#pragma unroll 2
          for (int w = 0; w < 8; w++) {
            const uint32_t off = (uint32_t)(w * 4 + h0 + hh) * 512 + lane * 16;
            const uint4 kk = lds_v4(sb + OFF_D + 16384 + off);
            const uint4 vv = lds_v4(sb + OFF_D + 32768 + off);
            const uint32_t a0 = movmat(kk.x), a2 = movmat(kk.y), a1 = movmat(kk.z), a3 = movmat(kk.w);
            const uint32_t b00 = movmat(vv.x), b01 = movmat(vv.y), b10 = movmat(vv.z), b11 = movmat(vv.w);
            mma16816(c0, a0, a1, a2, a3, b00, b01);
            mma16816(c1, a0, a1, a2, a3, b10, b11);
            mma16816(cz, a0, a1, a2, a3, ones, ones);
          }
          float* hb = kvbuf + hh * 272;
          float* a0p = hb + g * 16 + 2 * t;
          red_add_v2(a0p, c0[0], c0[1]); red_add_v2(a0p + 128, c0[2], c0[3]);
          red_add_v2(a0p + 8, c1[0], c1[1]); red_add_v2(a0p + 136, c1[2], c1[3]);
          if (t == 0) { red_add_f32(hb + 256 + g, cz[0]); red_add_f32(hb + 264 + g, cz[2]); }
        }
        __syncwarp();
        if (lane == 0) {
          __threadfence();
          red_inc(&g_cntKV[(j * 2 + aw - 1) * 8]);
          PROF(2);
          poll_ge(&g_cntKV[(j * 2 + aw - 1) * 8], 16u * ep1);
        }
        __syncwarp();
        PROF(3);
#pragma unroll 1
        for (int hh = 0; hh < 2; hh++) {
          const float* hb = kvbuf + hh * 272;
          float kvv[8], zz[4];
#pragma unroll
          for (int q = 0; q < 4; q++) {
            const int d = 2 * t + (q & 1) + (q >> 1) * 8;
            asm volatile("ld.global.cg.f32 %0, [%1];" : "=f"(kvv[q]) : "l"(hb + d * 16 + g) : "memory");
            asm volatile("ld.global.cg.f32 %0, [%1];" : "=f"(kvv[4 + q]) : "l"(hb + d * 16 + 8 + g) : "memory");
            asm volatile("ld.global.cg.f32 %0, [%1];" : "=f"(zz[q]) : "l"(hb + 256 + d) : "memory");
          }
          const uint32_t b00 = pack2(kvv[0], kvv[1]), b01 = pack2(kvv[2], kvv[3]);
          const uint32_t b10 = pack2(kvv[4], kvv[5]), b11 = pack2(kvv[6], kvv[7]);
          const uint32_t z0 = pack2(zz[0], zz[1]), z1 = pack2(zz[2], zz[3]);
#pragma unroll 2
          for (int w = 0; w < 8; w++) {
            const uint4 a = lds_v4(sb + OFF_D + (w * 4 + h0 + hh) * 512 + lane * 16);
            float n0[4] = {0.f, 0.f, 0.f, 0.f}, n1[4] = {0.f, 0.f, 0.f, 0.f}, dnn[4] = {0.f, 0.f, 0.f, 0.f};
            mma16816(n0, a.x, a.y, a.z, a.w, b00, b01);
            mma16816(n1, a.x, a.y, a.z, a.w, b10, b11);
            mma16816(dnn, a.x, a.y, a.z, a.w, z0, z1);
            const float i0 = __fdividef(1.f, dnn[0] + 1e-6f), i1 = __fdividef(1.f, dnn[2] + 1e-6f);
            stg_v4(g_o + (size_t)((rb * 8 + w) * 32 + 4 * j + h0 + hh) * 32 + lane,
                   pack2(n0[0] * i0, n0[1] * i0), pack2(n0[2] * i1, n0[3] * i1), pack2(n1[0] * i0, n1[1] * i0), pack2(n1[2] * i1, n1[3] * i1));
          }
        }
        __syncwarp();
        if (lane == 0) { __threadfence(); red_inc(&g_cntO[rb * 8]); }
        PROF(4);
      }
    }
  } else {
    asm volatile("setmaxnreg.inc.sync.aligned.u32 232;");
    const int wg = warp >> 2;
    const int g = lane >> 2, t = lane & 3;
    const int lr0 = warp * 16 + g;
    const int slab = rb * 8 + warp;
    Ring r{0, 0};
    const uint32_t a_base = sb + OFF_D + wg * 8192;
    const uint32_t ring_base = sb + OFF_RING;
    uint32_t prev_empty = 0;
    uint32_t bs;
#define STAGE_BEGIN() do { mbar_wait(bar0 + 8 * (BAR_FULL + r.slot), r.phase); bs = ring_base + r.slot * SLOT_BYTES; wg_fence(); } while (0)
#define STAGE_END() do { wg_commit(); wg_wait<1>(); if (lane == 0 && prev_empty) mbar_arrive(prev_empty); prev_empty = bar0 + 8 * (BAR_EMPTY + r.slot); r.next(); } while (0)
#define WARP_ARRIVE(b) do { __syncwarp(); if (lane == 0) mbar_arrive(bar0 + 8 * (b)); } while (0)

    uint4* act_out = g_act + (size_t)(slab * 112 + 14 * j) * 32 + lane;
    const uint32_t bias_addr = sb + OFF_B1 + 8 * t;
    float rs0, rs1;
    float pool[160];
    float (&acca)[64] = reinterpret_cast<float (&)[64]>(pool[0]);
    float (&accq)[96] = reinterpret_cast<float (&)[96]>(pool[64]);
    float (&accb)[48] = reinterpret_cast<float (&)[48]>(pool[0]);
    float (&accy)[64] = reinterpret_cast<float (&)[64]>(pool[64]);
    float (&accs)[32] = reinterpret_cast<float (&)[32]>(pool[0]);
    {
      uint4 q[16], p[16];
      const __nv_bfloat16* xr0 = x + (size_t)(rb * 128 + lr0) * DM + 8 * t;
      const __nv_bfloat16* xr1 = xr0 + 8 * DM;
      const int par = g & 1;
#pragma unroll
      for (int c = 0; c < 16; c++) { q[c] = ldg_nc(xr0 + 32 * (c ^ par)); p[c] = ldg_nc(xr1 + 32 * (c ^ par)); }
      named_bar_sync(0, 384);
      PROF(12);
      float sm4[4][4];
#pragma unroll
      for (int a = 0; a < 4; a++) { sm4[a][0] = sm4[a][1] = sm4[a][2] = sm4[a][3] = 0.f; }
      const uint32_t ones = 0x3F803F80u;
#pragma unroll
      for (int c = 0; c < 16; c++) {
        mma16816(sm4[(2 * c) & 3], q[c].x, p[c].x, q[c].y, p[c].y, ones, ones);
        mma16816(sm4[(2 * c + 1) & 3], q[c].z, p[c].z, q[c].w, p[c].w, ones, ones);
      }
      const float m0 = (sm4[0][0] + sm4[1][0] + sm4[2][0] + sm4[3][0]) * (1.f / DM);
      const float m1 = (sm4[0][2] + sm4[1][2] + sm4[2][2] + sm4[3][2]) * (1.f / DM);
      const uint32_t mb0 = pack2(m0, m0), mb1 = pack2(m1, m1);
      PROF(13);
      const uint32_t rowa = sb + OFF_D + lr0 * 128, rowb = rowa + 1024;
#pragma unroll
      for (int c = 0; c < 16; c++) {
        const int cc = c ^ par;
        const uint32_t u = (uint32_t)(((cc & 1) * 4 + t) ^ g) * 16;
        const uint32_t off = (uint32_t)(cc >> 1) * 16384 + u;
        q[c].x = hsub2_bf16(q[c].x, mb0); q[c].y = hsub2_bf16(q[c].y, mb0); q[c].z = hsub2_bf16(q[c].z, mb0); q[c].w = hsub2_bf16(q[c].w, mb0);
        p[c].x = hsub2_bf16(p[c].x, mb1); p[c].y = hsub2_bf16(p[c].y, mb1); p[c].z = hsub2_bf16(p[c].z, mb1); p[c].w = hsub2_bf16(p[c].w, mb1);
        sts_v4(rowa + off, q[c].x, q[c].y, q[c].z, q[c].w);
        sts_v4(rowb + off, p[c].x, p[c].y, p[c].z, p[c].w);
      }
      asm volatile("fence.proxy.async.shared::cta;" ::: "memory");
      named_bar_sync(1 + wg, 128);
      PROF(1);
      zero_regs(acca);
      float s0a = 0.f, s0b = 0.f, s1a = 0.f, s1b = 0.f;
#pragma unroll
      for (int st = 0; st < 8; st++) {
        STAGE_BEGIN();
        const uint32_t as = a_base + st * 16384;
#pragma unroll
        for (int kk = 0; kk < 4; kk++)
          wgmma_ss_n128(acca, make_desc(as + kk * 32, 16, 1024), make_desc(bs + kk * 2048, 8192, 1024), 1);
        STAGE_END();
#pragma unroll
        for (int c = 2 * st; c < 2 * st + 2; c++) {
          const uint32_t qv[4] = {q[c].x, q[c].y, q[c].z, q[c].w}, pv[4] = {p[c].x, p[c].y, p[c].z, p[c].w};
#pragma unroll
          for (int e = 0; e < 4; e++) {
            float f;
            f = bf_lo(qv[e]); s0a = fmaf(f, f, s0a); f = bf_hi(qv[e]); s0b = fmaf(f, f, s0b);
            f = bf_lo(pv[e]); s1a = fmaf(f, f, s1a); f = bf_hi(pv[e]); s1b = fmaf(f, f, s1b);
          }
        }
      }
      float s0 = s0a + s0b, s1 = s1a + s1b;
      s0 += __shfl_xor_sync(0xffffffffu, s0, 1); s1 += __shfl_xor_sync(0xffffffffu, s1, 1);
      s0 += __shfl_xor_sync(0xffffffffu, s0, 2); s1 += __shfl_xor_sync(0xffffffffu, s1, 2);
      const float dl0 = m0 - bf_lo(mb0), dl1 = m1 - bf_lo(mb1);
      rs0 = rsqrtf(fmaxf(s0 * (1.f / DM) - dl0 * dl0, 0.f) + 1e-5f);
      rs1 = rsqrtf(fmaxf(s1 * (1.f / DM) - dl1 * dl1, 0.f) + 1e-5f);
    }
    zero_regs(accq);
    PROF(2);
#pragma unroll
    for (int st = 0; st < 8; st++) {
      STAGE_BEGIN();
      const uint32_t as = a_base + (st >> 1) * 16384 + (st & 1) * 64;
      wgmma_ss_n192(accq, make_desc(as, 16, 1024), make_desc(bs, 4096, 1024), 1);
      wgmma_ss_n192(accq, make_desc(as + 32, 16, 1024), make_desc(bs + 2048, 4096, 1024), 1);
      STAGE_END();
      if (st == 0) {
        fence_regs(acca);
        mbar_wait(bar0 + 8 * BAR_BIAS, 0);
      }
      mish_tile(acca + 8 * st, bias_addr + 64 * st, rs0, rs1, act_out + st * 32);
    }
    WARP_ARRIVE(BAR_PUB_A);
    PROF(3);
    for (int st = 8; st < 16; st++) {
      STAGE_BEGIN();
      const uint32_t as = a_base + (st >> 1) * 16384 + (st & 1) * 64;
      wgmma_ss_n192(accq, make_desc(as, 16, 1024), make_desc(bs, 4096, 1024), 1);
      wgmma_ss_n192(accq, make_desc(as + 32, 16, 1024), make_desc(bs + 2048, 4096, 1024), 1);
      STAGE_END();
    }
    PROF(4);
    uint32_t pk[48];
#pragma unroll
    for (int st = 0; st < 8; st++) {
      STAGE_BEGIN();
      const uint32_t as = a_base + st * 16384;
#pragma unroll
      for (int kk = 0; kk < 4; kk++)
        wgmma_ss_n96(accb, make_desc(as + kk * 32, 16, 1024), make_desc(bs + kk * 2048, 8192, 1024), (st | kk) != 0);
      STAGE_END();
      if (st == 0) fence_regs(accq);
      if (st < 4) {
#pragma unroll
        for (int nb = 4 * st; nb < 4 * st + 4; nb++) {
          pk[2 * nb] = pack2(phi_f(accq[4 * nb] * rs0), phi_f(accq[4 * nb + 1] * rs0));
          pk[2 * nb + 1] = pack2(phi_f(accq[4 * nb + 2] * rs1), phi_f(accq[4 * nb + 3] * rs1));
        }
      } else if (st == 4) {
#pragma unroll
        for (int nb = 16; nb < 24; nb++) {
          pk[2 * nb] = pack2(accq[4 * nb] * rs0, accq[4 * nb + 1] * rs0);
          pk[2 * nb + 1] = pack2(accq[4 * nb + 2] * rs1, accq[4 * nb + 3] * rs1);
        }
      }
    }
    PROF(5);
    const uint4* act_in = g_act + (size_t)(slab * 112 + 56 * khalf) * 32 + lane;
    uint4 ab[3][4];
#pragma unroll
    for (int kk = 0; kk < 4; kk++) ab[2][kk] = make_uint4(0u, 0u, 0u, 0u);
    mbar_wait(bar0 + 8 * BAR_RDY_A, 0);
    PROF(6);
#pragma unroll
    for (int kk = 0; kk < 4; kk++) { ab[0][kk] = ldg_cg(act_in + kk * 32); ab[1][kk] = ldg_cg(act_in + (4 + kk) * 32); }
#pragma unroll
    for (int st = 0; st < 8; st++) {
      STAGE_BEGIN();
#pragma unroll
      for (int kk = 0; kk < 4; kk++) {
        const uint4 a = ab[st % 3][kk];
        wgmma_rs_n128(accy, a.x, a.y, a.z, a.w, make_desc(bs + kk * 2048, 8192, 1024), (st | kk) != 0);
      }
      STAGE_END();
      if (st == 0) {
        fence_regs(accb);
#pragma unroll
        for (int i = 0; i < 12; i++)
          sts_v4(sb + OFF_D + (i >> 2) * 16384 + (warp * 4 + (i & 3)) * 512 + lane * 16, pk[4 * i], pk[4 * i + 1], pk[4 * i + 2], pk[4 * i + 3]);
        WARP_ARRIVE(BAR_PQ);
      }
      if (st > 0) {
#pragma unroll
        for (int kk = 0; kk < 4; kk++) fence_u4(ab[(st + 2) % 3][kk]);
      }
      if (st + 2 < 8) {
        const int kt = 14 * ((st + 2) >> 1) + 4 * ((st + 2) & 1);
#pragma unroll
        for (int kk = 0; kk < 4; kk++) ab[(st + 2) % 3][kk] = ldg_cg(act_in + (kt + kk) * 32);
      } else {
        if (st == 6) mbar_wait(bar0 + 8 * BAR_RDY_B, 0);
        const int kt = 8 + 3 * (st - 6);
#pragma unroll
        for (int kk = 0; kk < 3; kk++) ab[(st + 2) % 3][kk] = ldg_cg(act_in + (kt + kk) * 32);
      }
      if (st < 3) {
        mish_tile(accb + 16 * st, bias_addr + 512 + 128 * st, rs0, rs1, act_out + (8 + 2 * st) * 32);
        mish_tile(accb + 16 * st + 8, bias_addr + 512 + 128 * st + 64, rs0, rs1, act_out + (9 + 2 * st) * 32);
        if (st == 2) WARP_ARRIVE(BAR_PUB_B);
      }
    }
    PROF(7);
    const uint4* o_in = g_o + (size_t)(slab * 32) * 32 + lane;
#pragma unroll
    for (int st = 0; st < 8; st++) {
      STAGE_BEGIN();
#pragma unroll
      for (int kk = 0; kk < 3; kk++) {
        const uint4 a = ab[(st + 8) % 3][kk];
        wgmma_rs_n128(accy, a.x, a.y, a.z, a.w, make_desc(bs + kk * 2048, 6144, 1024), 1);
      }
      STAGE_END();
#pragma unroll
      for (int kk = 0; kk < 4; kk++) fence_u4(ab[(st + 10) % 3][kk]);
      if (st + 2 < 8) {
        const int kt = 14 * ((st + 2) >> 1) + 8 + 3 * ((st + 2) & 1);
#pragma unroll
        for (int kk = 0; kk < 3; kk++) ab[(st + 10) % 3][kk] = ldg_cg(act_in + (kt + kk) * 32);
      } else {
        if (st == 6) mbar_wait(bar0 + 8 * BAR_RDY_O, 0);
#pragma unroll
        for (int kk = 0; kk < 4; kk++) ab[(st + 10) % 3][kk] = ldg_cg(o_in + (4 * (st - 6) + kk) * 32);
      }
    }
    PROF(8);
    const int c0 = 128 * nt + 64 * khalf + 2 * t;
    const size_t ro0 = (size_t)(rb * 128 + lr0) * DM + c0, ro1 = ro0 + 8 * DM;
    uint32_t xv[16];
#pragma unroll
    for (int st = 0; st < 8; st++) {
      STAGE_BEGIN();
#pragma unroll
      for (int kk = 0; kk < 4; kk++) {
        const uint4 a = ab[(st + 16) % 3][kk];
        wgmma_rs_n64(accs, a.x, a.y, a.z, a.w, make_desc(bs + kk * 2048, 8192, 1024), (st | kk) != 0);
      }
      STAGE_END();
#pragma unroll
      for (int kk = 0; kk < 4; kk++) fence_u4(ab[(st + 18) % 3][kk]);
      if (st + 2 < 8) {
#pragma unroll
        for (int kk = 0; kk < 4; kk++) ab[(st + 18) % 3][kk] = ldg_cg(o_in + (4 * (st + 2) + kk) * 32);
      }
      if (st == 0) {
        fence_regs(accy);
        float4* yp = g_yp + (size_t)((bid * 8 + warp) * 8) * 32 + lane;
#pragma unroll
        for (int q = 0; q < 8; q++)
          stg_v4(yp + q * 32, __float_as_uint(accy[32 + 4 * q]), __float_as_uint(accy[33 + 4 * q]), __float_as_uint(accy[34 + 4 * q]), __float_as_uint(accy[35 + 4 * q]));
        WARP_ARRIVE(BAR_PUB_Y);
      }
      if (st == 1) {
#pragma unroll
        for (int q = 0; q < 8; q++) { xv[2 * q] = ldg_nc32(x + ro0 + 8 * q); xv[2 * q + 1] = ldg_nc32(x + ro1 + 8 * q); }
      }
    }
    PROF(9);
    {
      mbar_wait(bar0 + 8 * BAR_RDY_Y, 0);
      PROF(10);
      const float4* yp = g_yp + (size_t)(((bid ^ 16) * 8 + warp) * 8) * 32 + lane;
      uint4 pv[8];
#pragma unroll
      for (int q = 0; q < 8; q++) pv[q] = ldg_cg(yp + q * 32);
      wg_wait<0>();
      fence_regs(accs);
#pragma unroll
      for (int q = 0; q < 8; q++) {
        const float y0 = accy[4 * q] + __uint_as_float(pv[q].x), y1 = accy[4 * q + 1] + __uint_as_float(pv[q].y);
        const float y2 = accy[4 * q + 2] + __uint_as_float(pv[q].z), y3 = accy[4 * q + 3] + __uint_as_float(pv[q].w);
        const float o0 = fmaf(accs[4 * q], silu_f(y0), bf_lo(xv[2 * q])), o1 = fmaf(accs[4 * q + 1], silu_f(y1), bf_hi(xv[2 * q]));
        const float o2 = fmaf(accs[4 * q + 2], silu_f(y2), bf_lo(xv[2 * q + 1])), o3 = fmaf(accs[4 * q + 3], silu_f(y3), bf_hi(xv[2 * q + 1]));
        *reinterpret_cast<uint32_t*>(out + ro0 + 8 * q) = pack2(o0, o1);
        *reinterpret_cast<uint32_t*>(out + ro1 + 8 * q) = pack2(o2, o3);
      }
    }
    PROF(11);
    if (tid == 0) red_inc(&g_done);
  }
}

typedef CUresult (*EncodeFn)(CUtensorMap*, CUtensorMapDataType, cuuint32_t, void*, const cuuint64_t*, const cuuint64_t*,
                             const cuuint32_t*, const cuuint32_t*, CUtensorMapInterleave, CUtensorMapSwizzle,
                             CUtensorMapL2promotion, CUtensorMapFloatOOBfill);

void make_map(EncodeFn enc, CUtensorMap* tm, const void* ptr, int rows, int cols, int box_rows) {
  cuuint64_t gd[2] = {(cuuint64_t)cols, (cuuint64_t)rows};
  cuuint64_t gs[1] = {(cuuint64_t)cols * 2};
  cuuint32_t bd[2] = {64, (cuuint32_t)box_rows};
  cuuint32_t es[2] = {1, 1};
  enc(tm, CU_TENSOR_MAP_DATA_TYPE_BFLOAT16, 2, const_cast<void*>(ptr), gd, gs, bd, es, CU_TENSOR_MAP_INTERLEAVE_NONE,
      CU_TENSOR_MAP_SWIZZLE_128B, CU_TENSOR_MAP_L2_PROMOTION_L2_128B, CU_TENSOR_MAP_FLOAT_OOB_FILL_NONE);
}

}

extern "C" void kernel_launch(void* const* d_in, const int* in_sizes, int n_in, void* d_out, int out_size) {
  const __nv_bfloat16* x = (const __nv_bfloat16*)d_in[0];
  const void* wqkv = d_in[1];
  const void* wo = d_in[2];
  const void* w1 = d_in[4];
  const __nv_bfloat16* b1 = (const __nv_bfloat16*)d_in[5];
  const void* w2 = d_in[6];
  static EncodeFn enc = nullptr;
  if (!enc) {
    cudaDriverEntryPointQueryResult qr;
    void* fn = nullptr;
    cudaGetDriverEntryPoint("cuTensorMapEncodeTiled", &fn, cudaEnableDefault, &qr);
    enc = (EncodeFn)fn;
    cudaFuncSetAttribute(fused_kernel, cudaFuncAttributeMaxDynamicSharedMemorySize, SMEM_ALLOC);
  }
  CUtensorMap tq, t1, t2a, t2b, to;
  make_map(enc, &tq, wqkv, DM, 3 * DM, 32);
  make_map(enc, &t1, w1, DM, FF, 64);
  make_map(enc, &t2a, w2, FF, DM, 64);
  make_map(enc, &t2b, w2, FF, DM, 48);
  make_map(enc, &to, wo, DM, DM, 64);
  fused_kernel<<<NCTA, 384, SMEM_ALLOC>>>(tq, t1, t2a, t2b, to, x, b1, (__nv_bfloat16*)d_out);
}
```

```cpp
#include <cuda_runtime.h>
#include <cuda_bf16.h>
#include <cuda.h>
#include <stdint.h>

namespace {

constexpr int DM = 512, FF = 1792;
constexpr int NCTA = 128;
constexpr int NSLOT = 5;
constexpr int SLOT_BYTES = 16384;
constexpr int OFF_D = 0;
constexpr int OFF_PQ = 0, OFF_PK = 16384, OFF_V = 32768, OFF_ONES = 49152, OFF_KVB = 65536;
constexpr int OFF_RING = 131072;
constexpr int OFF_MISC = OFF_RING + NSLOT * SLOT_BYTES;
constexpr int OFF_BAR = OFF_MISC;
constexpr int OFF_B1 = OFF_MISC + 256;
constexpr int SMEM_ALLOC = OFF_MISC + 1280;

enum { BAR_FULL = 0, BAR_EMPTY = NSLOT, BAR_X = 2 * NSLOT, BAR_BIAS = BAR_X + 4,
       BAR_PUB_A, BAR_PUB_B, BAR_PUB_KV, BAR_PUB_O, BAR_PUB_Y, BAR_DFREE,
       BAR_RDY_A, BAR_RDY_B, BAR_RDY_O, BAR_RDY_Y, BAR_RDY_KV, BAR_COUNT };
static_assert(BAR_COUNT <= 32, "too many barriers");

constexpr int NSTAGES = 56;

__device__ uint4 g_act[128 * 112 * 32];
__device__ uint4 g_o[128 * 32 * 32];
__device__ float4 g_yp[NCTA * 8 * 8 * 32];
__device__ float g_kv[2][32 * 272];
__device__ unsigned g_cntA[16 * 2 * 8];
__device__ unsigned g_cntB[16 * 2 * 8];
__device__ unsigned g_cntO[16 * 8];
__device__ unsigned g_flagY[NCTA * 8];
__device__ unsigned g_cntKV[8 * 8];
__device__ unsigned g_done;

#define PROF(i)

__device__ __forceinline__ uint32_t smem_u32(const void* p) { return (uint32_t)__cvta_generic_to_shared(p); }
__device__ __forceinline__ void mbar_init(uint32_t bar, uint32_t cnt) { asm volatile("mbarrier.init.shared::cta.b64 [%0], %1;" ::"r"(bar), "r"(cnt)); }
__device__ __forceinline__ void mbar_expect_tx(uint32_t bar, uint32_t bytes) { asm volatile("mbarrier.arrive.expect_tx.shared::cta.b64 _, [%0], %1;" ::"r"(bar), "r"(bytes) : "memory"); }
__device__ __forceinline__ void mbar_arrive(uint32_t bar) { asm volatile("mbarrier.arrive.shared::cta.b64 _, [%0];" ::"r"(bar) : "memory"); }
__device__ __forceinline__ void mbar_wait(uint32_t bar, uint32_t parity) {
  asm volatile("{\n.reg .pred P1;\n.reg .u32 cnt;\n"
               "mbarrier.try_wait.parity.shared::cta.b64 P1, [%0], %1;\n@P1 bra DONE;\n"
               "mov.u32 cnt, 0;\n"
               "LAB_WAIT:\n"
               "mbarrier.try_wait.parity.shared::cta.b64 P1, [%0], %1;\n@P1 bra DONE;\n"
               "add.u32 cnt, cnt, 1;\nsetp.lt.u32 P1, cnt, 16777216;\n@P1 bra LAB_WAIT;\ntrap;\n"
               "DONE:\n}" ::"r"(bar), "r"(parity) : "memory");
}
__device__ __forceinline__ bool mbar_test(uint32_t bar, uint32_t parity) {
  uint32_t done;
  asm volatile("{\n.reg .pred p;\nmbarrier.test_wait.parity.shared::cta.b64 p, [%1], %2;\nselp.u32 %0, 1, 0, p;\n}" : "=r"(done) : "r"(bar), "r"(parity) : "memory");
  return done != 0;
}
__device__ __forceinline__ unsigned ld_acquire(const unsigned* p) {
  unsigned v; asm volatile("ld.acquire.gpu.global.u32 %0, [%1];" : "=r"(v) : "l"(p) : "memory"); return v;
}
__device__ __forceinline__ void tma2d(uint32_t dst, const CUtensorMap* tm, int c0, int c1, uint32_t bar) {
  asm volatile("cp.async.bulk.tensor.2d.shared::cluster.global.mbarrier::complete_tx::bytes [%0], [%1, {%3, %4}], [%2];" ::"r"(dst), "l"(tm), "r"(bar), "r"(c0), "r"(c1) : "memory");
}
__device__ __forceinline__ void wg_fence() { asm volatile("wgmma.fence.sync.aligned;" ::: "memory"); }
__device__ __forceinline__ void wg_commit() { asm volatile("wgmma.commit_group.sync.aligned;" ::: "memory"); }
template <int N> __device__ __forceinline__ void wg_wait() { asm volatile("wgmma.wait_group.sync.aligned %0;" ::"n"(N) : "memory"); }
template <int N> __device__ __forceinline__ void zero_regs(float (&d)[N]) {
#pragma unroll
  for (int i = 0; i < N; i++) d[i] = 0.f;
}
template <int N> __device__ __forceinline__ void fence_regs(float (&d)[N]) {
#pragma unroll
  for (int i = 0; i < N; i++) asm volatile("" : "+f"(d[i])::"memory");
}
__device__ __forceinline__ void fence_u4(uint4& v) { asm volatile("" : "+r"(v.x), "+r"(v.y), "+r"(v.z), "+r"(v.w)::"memory"); }
__device__ __forceinline__ void named_bar_sync(int id, int n) { asm volatile("bar.sync %0, %1;" ::"r"(id), "r"(n) : "memory"); }
__device__ __forceinline__ void fence_async_smem() { asm volatile("fence.proxy.async.shared::cta;" ::: "memory"); }
__device__ __forceinline__ constexpr uint32_t dlo(uint32_t addr, uint32_t lbo_bytes) { return ((addr & 0x3FFFFu) >> 4) | ((lbo_bytes >> 4) << 16); }
__device__ __forceinline__ void mma16816(float (&c)[4], uint32_t a0, uint32_t a1, uint32_t a2, uint32_t a3, uint32_t b0, uint32_t b1) {
  asm volatile("mma.sync.aligned.m16n8k16.row.col.f32.bf16.bf16.f32 {%0,%1,%2,%3}, {%4,%5,%6,%7}, {%8,%9}, {%0,%1,%2,%3};"
               : "+f"(c[0]), "+f"(c[1]), "+f"(c[2]), "+f"(c[3]) : "r"(a0), "r"(a1), "r"(a2), "r"(a3), "r"(b0), "r"(b1));
}
__device__ __forceinline__ void stmatrix_x4(uint32_t addr, uint32_t a, uint32_t b, uint32_t c, uint32_t d) {
  asm volatile("stmatrix.sync.aligned.m8n8.x4.shared.b16 [%0], {%1,%2,%3,%4};" ::"r"(addr), "r"(a), "r"(b), "r"(c), "r"(d) : "memory");
}
__device__ __forceinline__ uint32_t pack2(float lo, float hi) { uint32_t r; asm("cvt.rn.bf16x2.f32 %0, %1, %2;" : "=r"(r) : "f"(hi), "f"(lo)); return r; }
__device__ __forceinline__ float ex2(float x) { float r; asm("ex2.approx.ftz.f32 %0, %1;" : "=f"(r) : "f"(x)); return r; }
__device__ __forceinline__ float rcp(float x) { float r; asm("rcp.approx.ftz.f32 %0, %1;" : "=f"(r) : "f"(x)); return r; }
__device__ __forceinline__ float bf_lo(uint32_t v) { return __uint_as_float(v << 16); }
__device__ __forceinline__ float bf_hi(uint32_t v) { return __uint_as_float(v & 0xffff0000u); }
__device__ __forceinline__ uint32_t hsub2_bf16(uint32_t a, uint32_t b) {
  __nv_bfloat162 x = *reinterpret_cast<__nv_bfloat162*>(&a), y = *reinterpret_cast<__nv_bfloat162*>(&b);
  __nv_bfloat162 r = __hsub2(x, y);
  return *reinterpret_cast<uint32_t*>(&r);
}
__device__ __forceinline__ uint32_t ldg_nc32(const void* p) {
  uint32_t v; asm volatile("ld.global.nc.u32 %0, [%1];" : "=r"(v) : "l"(p)); return v;
}
__device__ __forceinline__ uint4 ldg_cg(const void* p) {
  uint4 v; asm volatile("ld.global.cg.v4.u32 {%0,%1,%2,%3}, [%4];" : "=r"(v.x), "=r"(v.y), "=r"(v.z), "=r"(v.w) : "l"(p) : "memory"); return v;
}
__device__ __forceinline__ void stg_v4(void* p, uint32_t a, uint32_t b, uint32_t c, uint32_t d) {
  asm volatile("st.global.v4.u32 [%0], {%1,%2,%3,%4};" ::"l"(p), "r"(a), "r"(b), "r"(c), "r"(d) : "memory");
}
__device__ __forceinline__ void sts_v4(uint32_t addr, uint32_t a, uint32_t b, uint32_t c, uint32_t d) {
  asm volatile("st.shared.v4.u32 [%0], {%1,%2,%3,%4};" ::"r"(addr), "r"(a), "r"(b), "r"(c), "r"(d) : "memory");
}
__device__ __forceinline__ void sts_u16(uint32_t addr, uint16_t v) { asm volatile("st.shared.u16 [%0], %1;" ::"r"(addr), "h"(v) : "memory"); }
__device__ __forceinline__ void sts_f32(uint32_t addr, float v) { asm volatile("st.shared.f32 [%0], %1;" ::"r"(addr), "f"(v) : "memory"); }
__device__ __forceinline__ uint4 lds_v4(uint32_t addr) { uint4 v; asm volatile("ld.shared.v4.u32 {%0,%1,%2,%3}, [%4];" : "=r"(v.x), "=r"(v.y), "=r"(v.z), "=r"(v.w) : "r"(addr) : "memory"); return v; }
__device__ __forceinline__ float2 lds_f32x2(uint32_t addr) { float2 v; asm volatile("ld.shared.v2.f32 {%0,%1}, [%2];" : "=f"(v.x), "=f"(v.y) : "r"(addr) : "memory"); return v; }
__device__ __forceinline__ void red_add_v2(float* p, float a, float b) { asm volatile("red.relaxed.gpu.global.add.v2.f32 [%0], {%1,%2};" ::"l"(p), "f"(a), "f"(b) : "memory"); }
__device__ __forceinline__ void red_add_f32(float* p, float a) { asm volatile("red.relaxed.gpu.global.add.f32 [%0], %1;" ::"l"(p), "f"(a) : "memory"); }
__device__ __forceinline__ void red_inc(unsigned* cnt) { asm volatile("red.relaxed.gpu.global.add.u32 [%0], 1;" ::"l"(cnt) : "memory"); }
__device__ __forceinline__ void poll_ge(const unsigned* cnt, unsigned target) {
  asm volatile("{\n.reg .pred P1;\n.reg .u32 cnt, v;\n.reg .s32 d;\n"
               "mov.u32 cnt, 0;\n"
               "LAB_POLL:\n"
               "ld.acquire.gpu.global.u32 v, [%0];\nsub.s32 d, v, %1;\nsetp.ge.s32 P1, d, 0;\n@P1 bra DONE;\n"
               "add.u32 cnt, cnt, 1;\nsetp.lt.u32 P1, cnt, 4194304;\n@P1 bra LAB_POLL;\ntrap;\n"
               "DONE:\n}" ::"l"(cnt), "r"(target) : "memory");
}

template <int SCALE_D> __device__ __forceinline__ void wgmma_ss_n192(float (&d)[96], uint32_t da, uint32_t db) {
  asm volatile("{\n.reg .b64 da, db;\nmov.b64 da, {%96, %98};\nmov.b64 db, {%97, %98};\n"
    "wgmma.mma_async.sync.aligned.m64n192k16.f32.bf16.bf16 {%0, %1, %2, %3, %4, %5, %6, %7, %8, %9, %10, %11, %12, %13, %14, %15, %16, %17, %18, %19, %20, %21, %22, %23, %24, %25, %26, %27, %28, %29, %30, %31, %32, %33, %34, %35, %36, %37, %38, %39, %40, %41, %42, %43, %44, %45, %46, %47, %48, %49, %50, %51, %52, %53, %54, %55, %56, %57, %58, %59, %60, %61, %62, %63, %64, %65, %66, %67, %68, %69, %70, %71, %72, %73, %74, %75, %76, %77, %78, %79, %80, %81, %82, %83, %84, %85, %86, %87, %88, %89, %90, %91, %92, %93, %94, %95}, da, db, %99, 1, 1, 0, 1;\n}\n"
    : "+f"(d[0]), "+f"(d[1]), "+f"(d[2]), "+f"(d[3]), "+f"(d[4]), "+f"(d[5]), "+f"(d[6]), "+f"(d[7]), "+f"(d[8]), "+f"(d[9]), "+f"(d[10]), "+f"(d[11]), "+f"(d[12]), "+f"(d[13]), "+f"(d[14]), "+f"(d[15]), "+f"(d[16]), "+f"(d[17]), "+f"(d[18]), "+f"(d[19]), "+f"(d[20]), "+f"(d[21]), "+f"(d[22]), "+f"(d[23]), "+f"(d[24]), "+f"(d[25]), "+f"(d[26]), "+f"(d[27]), "+f"(d[28]), "+f"(d[29]), "+f"(d[30]), "+f"(d[31]), "+f"(d[32]), "+f"(d[33]), "+f"(d[34]), "+f"(d[35]), "+f"(d[36]), "+f"(d[37]), "+f"(d[38]), "+f"(d[39]), "+f"(d[40]), "+f"(d[41]), "+f"(d[42]), "+f"(d[43]), "+f"(d[44]), "+f"(d[45]), "+f"(d[46]), "+f"(d[47]), "+f"(d[48]), "+f"(d[49]), "+f"(d[50]), "+f"(d[51]), "+f"(d[52]), "+f"(d[53]), "+f"(d[54]), "+f"(d[55]), "+f"(d[56]), "+f"(d[57]), "+f"(d[58]), "+f"(d[59]), "+f"(d[60]), "+f"(d[61]), "+f"(d[62]), "+f"(d[63]), "+f"(d[64]), "+f"(d[65]), "+f"(d[66]), "+f"(d[67]), "+f"(d[68]), "+f"(d[69]), "+f"(d[70]), "+f"(d[71]), "+f"(d[72]), "+f"(d[73]), "+f"(d[74]), "+f"(d[75]), "+f"(d[76]), "+f"(d[77]), "+f"(d[78]), "+f"(d[79]), "+f"(d[80]), "+f"(d[81]), "+f"(d[82]), "+f"(d[83]), "+f"(d[84]), "+f"(d[85]), "+f"(d[86]), "+f"(d[87]), "+f"(d[88]), "+f"(d[89]), "+f"(d[90]), "+f"(d[91]), "+f"(d[92]), "+f"(d[93]), "+f"(d[94]), "+f"(d[95])
    : "r"(da), "r"(db), "r"(0x40000040u), "n"(SCALE_D));
}
template <int SCALE_D> __device__ __forceinline__ void wgmma_ss_n128(float (&d)[64], uint32_t da, uint32_t db) {
  asm volatile("{\n.reg .b64 da, db;\nmov.b64 da, {%64, %66};\nmov.b64 db, {%65, %66};\n"
    "wgmma.mma_async.sync.aligned.m64n128k16.f32.bf16.bf16 {%0, %1, %2, %3, %4, %5, %6, %7, %8, %9, %10, %11, %12, %13, %14, %15, %16, %17, %18, %19, %20, %21, %22, %23, %24, %25, %26, %27, %28, %29, %30, %31, %32, %33, %34, %35, %36, %37, %38, %39, %40, %41, %42, %43, %44, %45, %46, %47, %48, %49, %50, %51, %52, %53, %54, %55, %56, %57, %58, %59, %60, %61, %62, %63}, da, db, %67, 1, 1, 0, 1;\n}\n"
    : "+f"(d[0]), "+f"(d[1]), "+f"(d[2]), "+f"(d[3]), "+f"(d[4]), "+f"(d[5]), "+f"(d[6]), "+f"(d[7]), "+f"(d[8]), "+f"(d[9]), "+f"(d[10]), "+f"(d[11]), "+f"(d[12]), "+f"(d[13]), "+f"(d[14]), "+f"(d[15]), "+f"(d[16]), "+f"(d[17]), "+f"(d[18]), "+f"(d[19]), "+f"(d[20]), "+f"(d[21]), "+f"(d[22]), "+f"(d[23]), "+f"(d[24]), "+f"(d[25]), "+f"(d[26]), "+f"(d[27]), "+f"(d[28]), "+f"(d[29]), "+f"(d[30]), "+f"(d[31]), "+f"(d[32]), "+f"(d[33]), "+f"(d[34]), "+f"(d[35]), "+f"(d[36]), "+f"(d[37]), "+f"(d[38]), "+f"(d[39]), "+f"(d[40]), "+f"(d[41]), "+f"(d[42]), "+f"(d[43]), "+f"(d[44]), "+f"(d[45]), "+f"(d[46]), "+f"(d[47]), "+f"(d[48]), "+f"(d[49]), "+f"(d[50]), "+f"(d[51]), "+f"(d[52]), "+f"(d[53]), "+f"(d[54]), "+f"(d[55]), "+f"(d[56]), "+f"(d[57]), "+f"(d[58]), "+f"(d[59]), "+f"(d[60]), "+f"(d[61]), "+f"(d[62]), "+f"(d[63])
    : "r"(da), "r"(db), "r"(0x40000040u), "n"(SCALE_D));
}
template <int SCALE_D> __device__ __forceinline__ void wgmma_ss_n96(float (&d)[48], uint32_t da, uint32_t db) {
  asm volatile("{\n.reg .b64 da, db;\nmov.b64 da, {%48, %50};\nmov.b64 db, {%49, %50};\n"
    "wgmma.mma_async.sync.aligned.m64n96k16.f32.bf16.bf16 {%0, %1, %2, %3, %4, %5, %6, %7, %8, %9, %10, %11, %12, %13, %14, %15, %16, %17, %18, %19, %20, %21, %22, %23, %24, %25, %26, %27, %28, %29, %30, %31, %32, %33, %34, %35, %36, %37, %38, %39, %40, %41, %42, %43, %44, %45, %46, %47}, da, db, %51, 1, 1, 0, 1;\n}\n"
    : "+f"(d[0]), "+f"(d[1]), "+f"(d[2]), "+f"(d[3]), "+f"(d[4]), "+f"(d[5]), "+f"(d[6]), "+f"(d[7]), "+f"(d[8]), "+f"(d[9]), "+f"(d[10]), "+f"(d[11]), "+f"(d[12]), "+f"(d[13]), "+f"(d[14]), "+f"(d[15]), "+f"(d[16]), "+f"(d[17]), "+f"(d[18]), "+f"(d[19]), "+f"(d[20]), "+f"(d[21]), "+f"(d[22]), "+f"(d[23]), "+f"(d[24]), "+f"(d[25]), "+f"(d[26]), "+f"(d[27]), "+f"(d[28]), "+f"(d[29]), "+f"(d[30]), "+f"(d[31]), "+f"(d[32]), "+f"(d[33]), "+f"(d[34]), "+f"(d[35]), "+f"(d[36]), "+f"(d[37]), "+f"(d[38]), "+f"(d[39]), "+f"(d[40]), "+f"(d[41]), "+f"(d[42]), "+f"(d[43]), "+f"(d[44]), "+f"(d[45]), "+f"(d[46]), "+f"(d[47])
    : "r"(da), "r"(db), "r"(0x40000040u), "n"(SCALE_D));
}
template <int SCALE_D> __device__ __forceinline__ void wgmma_tt_n72(float (&d)[36], uint32_t da, uint32_t db) {
  asm volatile("{\n.reg .b64 da, db;\nmov.b64 da, {%36, %38};\nmov.b64 db, {%37, %38};\n"
    "wgmma.mma_async.sync.aligned.m64n72k16.f32.bf16.bf16 {%0, %1, %2, %3, %4, %5, %6, %7, %8, %9, %10, %11, %12, %13, %14, %15, %16, %17, %18, %19, %20, %21, %22, %23, %24, %25, %26, %27, %28, %29, %30, %31, %32, %33, %34, %35}, da, db, %39, 1, 1, 1, 1;\n}\n"
    : "+f"(d[0]), "+f"(d[1]), "+f"(d[2]), "+f"(d[3]), "+f"(d[4]), "+f"(d[5]), "+f"(d[6]), "+f"(d[7]), "+f"(d[8]), "+f"(d[9]), "+f"(d[10]), "+f"(d[11]), "+f"(d[12]), "+f"(d[13]), "+f"(d[14]), "+f"(d[15]), "+f"(d[16]), "+f"(d[17]), "+f"(d[18]), "+f"(d[19]), "+f"(d[20]), "+f"(d[21]), "+f"(d[22]), "+f"(d[23]), "+f"(d[24]), "+f"(d[25]), "+f"(d[26]), "+f"(d[27]), "+f"(d[28]), "+f"(d[29]), "+f"(d[30]), "+f"(d[31]), "+f"(d[32]), "+f"(d[33]), "+f"(d[34]), "+f"(d[35])
    : "r"(da), "r"(db), "r"(0x40000040u), "n"(SCALE_D));
}
template <int SCALE_D> __device__ __forceinline__ void wgmma_rs_n128(float (&d)[64], const uint4& a, uint32_t db) {
  asm volatile("{\n.reg .b64 db;\nmov.b64 db, {%68, %69};\n"
    "wgmma.mma_async.sync.aligned.m64n128k16.f32.bf16.bf16 {%0, %1, %2, %3, %4, %5, %6, %7, %8, %9, %10, %11, %12, %13, %14, %15, %16, %17, %18, %19, %20, %21, %22, %23, %24, %25, %26, %27, %28, %29, %30, %31, %32, %33, %34, %35, %36, %37, %38, %39, %40, %41, %42, %43, %44, %45, %46, %47, %48, %49, %50, %51, %52, %53, %54, %55, %56, %57, %58, %59, %60, %61, %62, %63}, {%64, %65, %66, %67}, db, %70, 1, 1, 1;\n}\n"
    : "+f"(d[0]), "+f"(d[1]), "+f"(d[2]), "+f"(d[3]), "+f"(d[4]), "+f"(d[5]), "+f"(d[6]), "+f"(d[7]), "+f"(d[8]), "+f"(d[9]), "+f"(d[10]), "+f"(d[11]), "+f"(d[12]), "+f"(d[13]), "+f"(d[14]), "+f"(d[15]), "+f"(d[16]), "+f"(d[17]), "+f"(d[18]), "+f"(d[19]), "+f"(d[20]), "+f"(d[21]), "+f"(d[22]), "+f"(d[23]), "+f"(d[24]), "+f"(d[25]), "+f"(d[26]), "+f"(d[27]), "+f"(d[28]), "+f"(d[29]), "+f"(d[30]), "+f"(d[31]), "+f"(d[32]), "+f"(d[33]), "+f"(d[34]), "+f"(d[35]), "+f"(d[36]), "+f"(d[37]), "+f"(d[38]), "+f"(d[39]), "+f"(d[40]), "+f"(d[41]), "+f"(d[42]), "+f"(d[43]), "+f"(d[44]), "+f"(d[45]), "+f"(d[46]), "+f"(d[47]), "+f"(d[48]), "+f"(d[49]), "+f"(d[50]), "+f"(d[51]), "+f"(d[52]), "+f"(d[53]), "+f"(d[54]), "+f"(d[55]), "+f"(d[56]), "+f"(d[57]), "+f"(d[58]), "+f"(d[59]), "+f"(d[60]), "+f"(d[61]), "+f"(d[62]), "+f"(d[63])
    : "r"(a.x), "r"(a.y), "r"(a.z), "r"(a.w), "r"(db), "r"(0x40000040u), "n"(SCALE_D));
}
template <int SCALE_D> __device__ __forceinline__ void wgmma_rs_n64(float (&d)[32], const uint4& a, uint32_t db) {
  asm volatile("{\n.reg .b64 db;\nmov.b64 db, {%36, %37};\n"
    "wgmma.mma_async.sync.aligned.m64n64k16.f32.bf16.bf16 {%0, %1, %2, %3, %4, %5, %6, %7, %8, %9, %10, %11, %12, %13, %14, %15, %16, %17, %18, %19, %20, %21, %22, %23, %24, %25, %26, %27, %28, %29, %30, %31}, {%32, %33, %34, %35}, db, %38, 1, 1, 1;\n}\n"
    : "+f"(d[0]), "+f"(d[1]), "+f"(d[2]), "+f"(d[3]), "+f"(d[4]), "+f"(d[5]), "+f"(d[6]), "+f"(d[7]), "+f"(d[8]), "+f"(d[9]), "+f"(d[10]), "+f"(d[11]), "+f"(d[12]), "+f"(d[13]), "+f"(d[14]), "+f"(d[15]), "+f"(d[16]), "+f"(d[17]), "+f"(d[18]), "+f"(d[19]), "+f"(d[20]), "+f"(d[21]), "+f"(d[22]), "+f"(d[23]), "+f"(d[24]), "+f"(d[25]), "+f"(d[26]), "+f"(d[27]), "+f"(d[28]), "+f"(d[29]), "+f"(d[30]), "+f"(d[31])
    : "r"(a.x), "r"(a.y), "r"(a.z), "r"(a.w), "r"(db), "r"(0x40000040u), "n"(SCALE_D));
}

constexpr float LOG2E = 1.4426950408889634f;
__device__ __forceinline__ float phi_f(float t) {
  float e = ex2(t * LOG2E);
  return (t > 0.f ? t + 1.f : e) + 1e-6f;
}
__device__ __forceinline__ float silu_f(float y) { return y * rcp(1.f + ex2(-y * LOG2E)); }

__device__ __forceinline__ void mish_tile(const float* c, uint32_t bias_addr, float rs0, float rs1, uint4* dst) {
  const float2 ba = lds_f32x2(bias_addr);
  const float2 bb = lds_f32x2(bias_addr + 32);
  float h[8], u[8], r[8];
  h[0] = fmaf(c[0], rs0, ba.x); h[1] = fmaf(c[1], rs0, ba.y); h[2] = fmaf(c[2], rs1, ba.x); h[3] = fmaf(c[3], rs1, ba.y);
  h[4] = fmaf(c[4], rs0, bb.x); h[5] = fmaf(c[5], rs0, bb.y); h[6] = fmaf(c[6], rs1, bb.x); h[7] = fmaf(c[7], rs1, bb.y);
#pragma unroll
  for (int i = 0; i < 8; i++) u[i] = ex2(fminf(h[i], 20.f) * LOG2E);
#pragma unroll
  for (int i = 0; i < 8; i++) { const float tt = u[i] + 2.f; r[i] = rcp(fmaf(u[i], tt, 2.f)); h[i] *= u[i] * tt; }
#pragma unroll
  for (int i = 0; i < 8; i++) h[i] *= r[i];
  stg_v4(dst, pack2(h[0], h[1]), pack2(h[2], h[3]), pack2(h[4], h[5]), pack2(h[6], h[7]));
}

__global__ void __launch_bounds__(384, 1)
fused_kernel(const __grid_constant__ CUtensorMap tm_x, const __grid_constant__ CUtensorMap tm_qkv,
             const __grid_constant__ CUtensorMap tm_w1, const __grid_constant__ CUtensorMap tm_w2a,
             const __grid_constant__ CUtensorMap tm_w2b, const __grid_constant__ CUtensorMap tm_wo,
             const __nv_bfloat16* __restrict__ x, const __nv_bfloat16* __restrict__ b1, __nv_bfloat16* __restrict__ out) {
  extern __shared__ __align__(1024) uint8_t smem_raw[];
  const uint32_t sb = smem_u32(smem_raw);
  const int tid = threadIdx.x, lane = tid & 31;
  const int warp = __shfl_sync(0xffffffffu, tid >> 5, 0);
  const int bid = blockIdx.x;
  const int G = bid >> 4, gi = bid & 15;
  const int khalf = G & 1;
  const int rb = (G >> 1) * 4 + (gi >> 2);
  const int nt = gi & 3;
  const int j = khalf + 2 * nt;
  const uint32_t bar0 = sb + OFF_BAR;
  PROF(0);

  if (warp >= 8) {
    asm volatile("setmaxnreg.dec.sync.aligned.u32 40;");
    if (warp == 8) {
      if (lane == 0) {
        if (sb & 1023u) asm volatile("trap;");
        for (int i = 0; i < NSLOT; i++) { mbar_init(bar0 + 8 * (BAR_FULL + i), 1); mbar_init(bar0 + 8 * (BAR_EMPTY + i), 8); }
        for (int i = 0; i < 4; i++) mbar_init(bar0 + 8 * (BAR_X + i), 1);
        mbar_init(bar0 + 8 * BAR_BIAS, 1);
        for (int i = BAR_PUB_A; i <= BAR_DFREE; i++) mbar_init(bar0 + 8 * i, 8);
        for (int i = BAR_RDY_A; i <= BAR_RDY_Y; i++) mbar_init(bar0 + 8 * i, 1);
        mbar_init(bar0 + 8 * BAR_RDY_KV, 2);
        asm volatile("fence.mbarrier_init.release.cluster;" ::: "memory");
        fence_async_smem();
        for (int i = 0; i < 4; i++) {
          mbar_expect_tx(bar0 + 8 * (BAR_X + i), 32768);
          tma2d(sb + OFF_D + (2 * i) * 16384, &tm_x, 128 * i, rb * 128, bar0 + 8 * (BAR_X + i));
          tma2d(sb + OFF_D + (2 * i + 1) * 16384, &tm_x, 128 * i + 64, rb * 128, bar0 + 8 * (BAR_X + i));
        }
      }
      __syncwarp();
      named_bar_sync(0, 384);
      if (lane == 0) {
        const int c_own = 128 * nt + 64 * khalf, c_par = 128 * nt + 64 * (1 - khalf);
        int slot = 0; uint32_t phase = 1;
        for (int st = 0; st < NSTAGES; st++) {
          const uint32_t full = bar0 + 8 * (BAR_FULL + slot);
          const uint32_t dst = sb + OFF_RING + slot * SLOT_BYTES;
          mbar_wait(bar0 + 8 * (BAR_EMPTY + slot), phase);
          if (st < 8) {
            mbar_expect_tx(full, 16384);
            const int k0 = 64 * st, c0 = 224 * j;
            tma2d(dst, &tm_w1, c0, k0, full);
            tma2d(dst + 8192, &tm_w1, c0 + 64, k0, full);
          } else if (st < 24) {
            mbar_expect_tx(full, 12288);
            const int k0 = 32 * (st - 8);
            tma2d(dst, &tm_qkv, 64 * j, k0, full);
            tma2d(dst + 4096, &tm_qkv, 512 + 64 * j, k0, full);
            tma2d(dst + 8192, &tm_qkv, 1024 + 64 * j, k0, full);
          } else if (st < 32) {
            mbar_expect_tx(full, 16384);
            const int k0 = 64 * (st - 24), c0 = 224 * j + 128;
            tma2d(dst, &tm_w1, c0, k0, full);
            tma2d(dst + 8192, &tm_w1, c0 + 64, k0, full);
          } else if (st < 40) {
            mbar_expect_tx(full, 16384);
            const int i = st - 32;
            const int k0 = 224 * (4 * khalf + (i >> 1)) + 64 * (i & 1);
            tma2d(dst, &tm_w2a, c_own, k0, full);
            tma2d(dst + 8192, &tm_w2a, c_par, k0, full);
          } else if (st < 48) {
            mbar_expect_tx(full, 12288);
            const int i = st - 40;
            const int k0 = 224 * (4 * khalf + (i >> 1)) + 128 + 48 * (i & 1);
            tma2d(dst, &tm_w2b, c_own, k0, full);
            tma2d(dst + 6144, &tm_w2b, c_par, k0, full);
          } else {
            mbar_expect_tx(full, 8192);
            tma2d(dst, &tm_wo, c_own, 64 * (st - 48), full);
          }
          if (++slot == NSLOT) { slot = 0; phase ^= 1; }
        }
      }
    } else {
      const int aw = warp - 9;
      unsigned dn; asm volatile("ld.relaxed.gpu.global.u32 %0, [%1];" : "=r"(dn) : "l"(&g_done) : "memory");
      named_bar_sync(0, 384);
      const unsigned ep1 = dn / NCTA + 1u;
      if (aw == 0) {
        for (int i = lane; i < 224; i += 32) sts_f32(sb + OFF_B1 + 4 * i, __bfloat162float(b1[224 * j + i]));
        __syncwarp();
        if (lane == 0) {
          mbar_arrive(bar0 + 8 * BAR_BIAS);
          uint32_t pend_pub = 31u, pend_rdy = 15u, it = 0;
          while (pend_pub | pend_rdy) {
#pragma unroll
            for (int i = 0; i < 5; i++) {
              if ((pend_pub >> i) & 1u) {
                if (mbar_test(bar0 + 8 * (BAR_PUB_A + i), 0)) {
                  __threadfence();
                  unsigned* c = i == 0 ? &g_cntA[(rb * 2 + (j >> 2)) * 8] : i == 1 ? &g_cntB[(rb * 2 + (j >> 2)) * 8]
                              : i == 2 ? &g_cntKV[j * 8] : i == 3 ? &g_cntO[rb * 8] : &g_flagY[bid * 8];
                  red_inc(c);
                  pend_pub &= ~(1u << i);
                }
              }
            }
            if (pend_rdy) {
              const int i = __ffs(pend_rdy) - 1;
              const unsigned* c = i == 0 ? &g_cntA[(rb * 2 + khalf) * 8] : i == 1 ? &g_cntB[(rb * 2 + khalf) * 8]
                                : i == 2 ? &g_cntO[rb * 8] : &g_flagY[(bid ^ 16) * 8];
              const unsigned tgt = (i < 2 ? 4u : i == 2 ? 8u : 1u) * ep1;
              if ((int)(ld_acquire(c) - tgt) >= 0) { mbar_arrive(bar0 + 8 * (BAR_RDY_A + i)); pend_rdy &= pend_rdy - 1; }
            }
            if (++it > (1u << 22)) asm volatile("trap;");
          }
        }
      } else {
        const int h0 = 2 * (aw - 1);
        if (rb == 0) {
          float4* z = reinterpret_cast<float4*>(&g_kv[ep1 & 1][(4 * j + h0) * 272]);
          for (int i = lane; i < 136; i += 32) z[i] = make_float4(0.f, 0.f, 0.f, 0.f);
        }
        const float* kvbuf = &g_kv[(ep1 & 1) ^ 1][(4 * j + h0) * 272];
        mbar_wait(bar0 + 8 * BAR_DFREE, 0);
#pragma unroll
        for (int i = 0; i < 8; i++) {
          const uint32_t a = sb + OFF_KVB + (aw - 1) * 4096 + (i * 32 + lane) * 16;
          sts_v4(a, 0u, 0u, 0u, 0u); sts_v4(a + 8192, 0u, 0u, 0u, 0u);
        }
        PROF(1);
        if (lane == 0) poll_ge(&g_cntKV[j * 8], 16u * ep1);
        __syncwarp();
        PROF(2);
        uint4 tv[5];
#pragma unroll
        for (int q = 0; q < 5; q++) { const int i = q * 32 + lane; if (i < 136) tv[q] = ldg_cg(reinterpret_cast<const float4*>(kvbuf) + i); }
#pragma unroll
        for (int q = 0; q < 5; q++) {
          const int i = q * 32 + lane;
          if (i < 136) {
            const int hh = h0 + (i >= 68), e4 = (i >= 68 ? i - 68 : i) * 4;
            const float vals[4] = {__uint_as_float(tv[q].x), __uint_as_float(tv[q].y), __uint_as_float(tv[q].z), __uint_as_float(tv[q].w)};
            if (e4 < 256) {
              const int k = hh * 16 + (e4 >> 4), n = hh * 16 + (e4 & 15);
              const uint32_t a = sb + OFF_KVB + k * 128 + (((n >> 3) ^ (k & 7)) << 4) + (n & 7) * 2;
              asm volatile("st.shared.v2.u32 [%0], {%1,%2};" ::"r"(a), "r"(pack2(vals[0], vals[1])), "r"(pack2(vals[2], vals[3])) : "memory");
            } else {
#pragma unroll
              for (int c = 0; c < 4; c++) {
                const int k = hh * 16 + (e4 - 256) + c;
                const uint32_t zz = pack2(vals[c], vals[c]);
                sts_v4(sb + OFF_KVB + 8192 + k * 128 + ((hh ^ (k & 7)) << 4), zz, zz, zz, zz);
              }
            }
          }
        }
        fence_async_smem();
        __syncwarp();
        if (lane == 0) mbar_arrive(bar0 + 8 * BAR_RDY_KV);
        PROF(3);
      }
    }
  } else {
    asm volatile("setmaxnreg.inc.sync.aligned.u32 232;");
    const int wg = warp >> 2;
    const int g = lane >> 2, t = lane & 3;
    const int lr0 = warp * 16 + g;
    const int slab = rb * 8 + warp;
    unsigned dn; asm volatile("ld.relaxed.gpu.global.u32 %0, [%1];" : "=r"(dn) : "l"(&g_done) : "memory");
    const uint32_t a_lo = dlo(sb + OFF_D + wg * 8192, 16);
    const uint32_t ring_lo = (sb + OFF_RING) >> 4;

#define SLOT(gs) ((gs) % NSLOT)
#define PHASE(gs) (((gs) / NSLOT) & 1)
#define B_LO(gs, off, lbo) (ring_lo + ((SLOT(gs) * SLOT_BYTES + (off)) >> 4) + (((lbo) >> 4) << 16))
#define STAGE_BEGIN(gs) do { mbar_wait(bar0 + 8 * (BAR_FULL + SLOT(gs)), PHASE(gs)); wg_fence(); } while (0)
#define STAGE_RELEASE(gs) do { wg_wait<1>(); if ((gs) > 0 && lane == 0) mbar_arrive(bar0 + 8 * (BAR_EMPTY + SLOT((gs) + NSLOT - 1))); } while (0)
#define WARP_ARRIVE(b) do { __syncwarp(); if (lane == 0) mbar_arrive(bar0 + 8 * (b)); } while (0)

    uint4* act_out = g_act + (size_t)(slab * 112 + 14 * j) * 32 + lane;
    const uint32_t bias_addr = sb + OFF_B1 + 8 * t;
    float rs0, rs1;
    float pool[160];
    float (&acca)[64] = reinterpret_cast<float (&)[64]>(pool[0]);
    float (&accq)[96] = reinterpret_cast<float (&)[96]>(pool[64]);
    float (&accb)[48] = reinterpret_cast<float (&)[48]>(pool[0]);
    float (&acck)[36] = reinterpret_cast<float (&)[36]>(pool[0]);
    float (&accy)[64] = reinterpret_cast<float (&)[64]>(pool[64]);
    float (&accs)[32] = reinterpret_cast<float (&)[32]>(pool[0]);
    {
      uint4 q[16], p[16];
      const int par = g & 1;
      const uint32_t rowa = sb + OFF_D + lr0 * 128;
      const uint32_t u0 = (uint32_t)(((par * 4 + t) ^ g) << 4), u1 = u0 ^ 64u;
      named_bar_sync(0, 384);
      float sm4[4][4];
#pragma unroll
      for (int a = 0; a < 4; a++) { sm4[a][0] = sm4[a][1] = sm4[a][2] = sm4[a][3] = 0.f; }
      const uint32_t ones = 0x3F803F80u;
#pragma unroll
      for (int c = 0; c < 8; c++) {
        if ((c & 1) == 0) mbar_wait(bar0 + 8 * (BAR_X + (c >> 1)), 0);
        q[2 * c] = lds_v4(rowa + c * 16384 + u0);     p[2 * c] = lds_v4(rowa + c * 16384 + 1024 + u0);
        q[2 * c + 1] = lds_v4(rowa + c * 16384 + u1); p[2 * c + 1] = lds_v4(rowa + c * 16384 + 1024 + u1);
#pragma unroll
        for (int h = 0; h < 2; h++) {
          const int i = 2 * c + h;
          mma16816(sm4[2 * h], q[i].x, p[i].x, q[i].y, p[i].y, ones, ones);
          mma16816(sm4[2 * h + 1], q[i].z, p[i].z, q[i].w, p[i].w, ones, ones);
        }
      }
      const float m0 = (sm4[0][0] + sm4[1][0] + sm4[2][0] + sm4[3][0]) * (1.f / DM);
      const float m1 = (sm4[0][2] + sm4[1][2] + sm4[2][2] + sm4[3][2]) * (1.f / DM);
      const uint32_t mb0 = pack2(m0, m0), mb1 = pack2(m1, m1);
      PROF(12);
#pragma unroll
      for (int i = 0; i < 16; i++) {
        const uint32_t off = (uint32_t)(i >> 1) * 16384 + ((i & 1) ? u1 : u0);
        q[i].x = hsub2_bf16(q[i].x, mb0); q[i].y = hsub2_bf16(q[i].y, mb0); q[i].z = hsub2_bf16(q[i].z, mb0); q[i].w = hsub2_bf16(q[i].w, mb0);
        p[i].x = hsub2_bf16(p[i].x, mb1); p[i].y = hsub2_bf16(p[i].y, mb1); p[i].z = hsub2_bf16(p[i].z, mb1); p[i].w = hsub2_bf16(p[i].w, mb1);
        sts_v4(rowa + off, q[i].x, q[i].y, q[i].z, q[i].w);
        sts_v4(rowa + 1024 + off, p[i].x, p[i].y, p[i].z, p[i].w);
      }
      fence_async_smem();
      named_bar_sync(1 + wg, 128);
      PROF(1);
      zero_regs(acca);
      float s0a = 0.f, s0b = 0.f, s1a = 0.f, s1b = 0.f;
#pragma unroll
      for (int st = 0; st < 8; st++) {
        STAGE_BEGIN(st);
#pragma unroll
        for (int kk = 0; kk < 4; kk++) wgmma_ss_n128<1>(acca, a_lo + ((st * 16384 + kk * 32) >> 4), B_LO(st, kk * 2048, 8192));
        wg_commit();
#pragma unroll
        for (int c = 2 * st; c < 2 * st + 2; c++) {
          const uint32_t qv[4] = {q[c].x, q[c].y, q[c].z, q[c].w}, pv[4] = {p[c].x, p[c].y, p[c].z, p[c].w};
#pragma unroll
          for (int e = 0; e < 4; e++) {
            float f;
            f = bf_lo(qv[e]); s0a = fmaf(f, f, s0a); f = bf_hi(qv[e]); s0b = fmaf(f, f, s0b);
            f = bf_lo(pv[e]); s1a = fmaf(f, f, s1a); f = bf_hi(pv[e]); s1b = fmaf(f, f, s1b);
          }
        }
        STAGE_RELEASE(st);
      }
      float s0 = s0a + s0b, s1 = s1a + s1b;
      s0 += __shfl_xor_sync(0xffffffffu, s0, 1); s1 += __shfl_xor_sync(0xffffffffu, s1, 1);
      s0 += __shfl_xor_sync(0xffffffffu, s0, 2); s1 += __shfl_xor_sync(0xffffffffu, s1, 2);
      const float dl0 = m0 - bf_lo(mb0), dl1 = m1 - bf_lo(mb1);
      rs0 = rsqrtf(fmaxf(s0 * (1.f / DM) - dl0 * dl0, 0.f) + 1e-5f);
      rs1 = rsqrtf(fmaxf(s1 * (1.f / DM) - dl1 * dl1, 0.f) + 1e-5f);
    }
    PROF(2);
    zero_regs(accq);
#pragma unroll
    for (int st = 0; st < 16; st++) {
      const int gs = 8 + st;
      STAGE_BEGIN(gs);
      const uint32_t as = a_lo + (((st >> 1) * 16384 + (st & 1) * 64) >> 4);
      wgmma_ss_n192<1>(accq, as, B_LO(gs, 0, 4096));
      wgmma_ss_n192<1>(accq, as + 2, B_LO(gs, 2048, 4096));
      wg_commit();
      if (st == 0) {
        STAGE_RELEASE(gs);
        fence_regs(acca);
        mbar_wait(bar0 + 8 * BAR_BIAS, 0);
      }
      if (st < 8) mish_tile(acca + 8 * st, bias_addr + 64 * st, rs0, rs1, act_out + st * 32);
      if (st == 7) { WARP_ARRIVE(BAR_PUB_A); PROF(3); }
      if (st != 0) STAGE_RELEASE(gs);
    }
    PROF(4);
    const uint4* act_in = g_act + (size_t)(slab * 112 + 56 * khalf) * 32 + lane;
    const uint4* o_in = g_o + (size_t)(slab * 32) * 32 + lane;
    uint4 ab[4][4];
    auto load_a = [&](int rs) {
      if (rs < 8) {
        const int kt = 14 * (rs >> 1) + 4 * (rs & 1);
#pragma unroll
        for (int kk = 0; kk < 4; kk++) ab[rs & 3][kk] = ldg_cg(act_in + (kt + kk) * 32);
      } else if (rs < 16) {
        const int kt = 14 * ((rs - 8) >> 1) + 8 + 3 * (rs & 1);
#pragma unroll
        for (int kk = 0; kk < 3; kk++) ab[rs & 3][kk] = ldg_cg(act_in + (kt + kk) * 32);
      } else if (rs < 24) {
#pragma unroll
        for (int kk = 0; kk < 4; kk++) ab[rs & 3][kk] = ldg_cg(o_in + (4 * (rs - 16) + kk) * 32);
      }
    };
    auto keep_a = [&](int rs) {
#pragma unroll
      for (int kk = 0; kk < 4; kk++) if (!(rs >= 8 && rs < 16 && kk == 3)) fence_u4(ab[rs & 3][kk]);
    };
    uint32_t pk[48];
#pragma unroll
    for (int st = 0; st < 8; st++) {
      const int gs = 24 + st;
      STAGE_BEGIN(gs);
#pragma unroll
      for (int kk = 0; kk < 4; kk++) {
        if (st == 0 && kk == 0) wgmma_ss_n96<0>(accb, a_lo + ((st * 16384 + kk * 32) >> 4), B_LO(gs, kk * 2048, 8192));
        else wgmma_ss_n96<1>(accb, a_lo + ((st * 16384 + kk * 32) >> 4), B_LO(gs, kk * 2048, 8192));
      }
      wg_commit();
      if (st == 0) { STAGE_RELEASE(gs); fence_regs(accq); }
      if (st < 4) {
#pragma unroll
        for (int nb = 4 * st; nb < 4 * st + 4; nb++) {
          pk[2 * nb] = pack2(phi_f(accq[4 * nb] * rs0), phi_f(accq[4 * nb + 1] * rs0));
          pk[2 * nb + 1] = pack2(phi_f(accq[4 * nb + 2] * rs1), phi_f(accq[4 * nb + 3] * rs1));
        }
      } else if (st == 4) {
#pragma unroll
        for (int nb = 16; nb < 24; nb++) {
          pk[2 * nb] = pack2(accq[4 * nb] * rs0, accq[4 * nb + 1] * rs0);
          pk[2 * nb + 1] = pack2(accq[4 * nb + 2] * rs1, accq[4 * nb + 3] * rs1);
        }
      } else if (st == 5) {
        mbar_wait(bar0 + 8 * BAR_RDY_A, 0);
        load_a(0); load_a(1);
      }
      if (st != 0) STAGE_RELEASE(gs);
    }
    PROF(5);
#pragma unroll
    for (int st = 0; st < 8; st++) {
      const int gs = 32 + st;
      STAGE_BEGIN(gs);
#pragma unroll
      for (int kk = 0; kk < 4; kk++) {
        if (st == 0 && kk == 0) wgmma_rs_n128<0>(accy, ab[st & 3][kk], B_LO(gs, kk * 2048, 8192));
        else wgmma_rs_n128<1>(accy, ab[st & 3][kk], B_LO(gs, kk * 2048, 8192));
      }
      if (st == 2) {
        const uint32_t ka = dlo(sb + OFF_PK + wg * 8192, 16);
        const uint32_t vb = dlo(sb + OFF_V + wg * 8192, OFF_ONES - OFF_V);
        wgmma_tt_n72<0>(acck, ka, vb);
#pragma unroll
        for (int kk = 1; kk < 4; kk++) wgmma_tt_n72<1>(acck, ka + kk * 128, vb + kk * 128);
      }
      wg_commit();
      if (st == 0) {
        STAGE_RELEASE(gs);
        fence_regs(accb);
        const int m = lane >> 3, rr = lane & 7;
        const uint32_t srow = sb + OFF_D + (warp * 16 + (m & 1) * 8 + rr) * 128;
#pragma unroll
        for (int i = 0; i < 12; i++) {
          const int cb = 2 * (i & 3) + (m >> 1);
          stmatrix_x4(srow + (i >> 2) * 16384 + ((cb ^ rr) << 4), pk[4 * i], pk[4 * i + 1], pk[4 * i + 2], pk[4 * i + 3]);
        }
        const uint32_t ones = 0x3F803F80u;
#pragma unroll
        for (int i = 0; i < 4; i++) sts_v4(sb + OFF_ONES + warp * 2048 + i * 512 + lane * 16, ones, ones, ones, ones);
        fence_async_smem();
        WARP_ARRIVE(BAR_DFREE);
        load_a(2);
      }
      if (st < 2) {
#pragma unroll
        for (int i = 3 * st; i < 3 * st + 3; i++)
          mish_tile(accb + 8 * i, bias_addr + 512 + 64 * i, rs0, rs1, act_out + (8 + i) * 32);
        if (st == 1) { WARP_ARRIVE(BAR_PUB_B); named_bar_sync(1 + wg, 128); }
      }
      if (st != 0) { STAGE_RELEASE(gs); keep_a(st - 1); }
      if (st == 1) { load_a(3); load_a(4); }
      else if (st >= 2) {
        if (st == 5) mbar_wait(bar0 + 8 * BAR_RDY_B, 0);
        load_a(st + 3);
      }
      if (st == 3) {
        fence_regs(acck);
        const unsigned ep1 = dn / NCTA + 1u;
        const int wq = warp & 3;
        float* hb = &g_kv[(ep1 & 1) ^ 1][(4 * j + wq) * 272];
        float* a0p = hb + g * 16 + 2 * t;
#pragma unroll
        for (int w = 0; w < 4; w++) {
          if (wq == w) {
            red_add_v2(a0p, acck[8 * w], acck[8 * w + 1]); red_add_v2(a0p + 128, acck[8 * w + 2], acck[8 * w + 3]);
            red_add_v2(a0p + 8, acck[8 * w + 4], acck[8 * w + 5]); red_add_v2(a0p + 136, acck[8 * w + 6], acck[8 * w + 7]);
          }
        }
        if (t == 0) { red_add_f32(hb + 256 + g, acck[32]); red_add_f32(hb + 264 + g, acck[34]); }
        WARP_ARRIVE(BAR_PUB_KV);
      }
    }
    PROF(6);
#pragma unroll
    for (int st = 0; st < 8; st++) {
      const int gs = 40 + st, rs = 8 + st;
      STAGE_BEGIN(gs);
#pragma unroll
      for (int kk = 0; kk < 3; kk++) wgmma_rs_n128<1>(accy, ab[rs & 3][kk], B_LO(gs, kk * 2048, 6144));
      if (st == 0) {
        mbar_wait(bar0 + 8 * BAR_RDY_KV, 0);
        PROF(7);
        const uint32_t qa = dlo(sb + OFF_PQ + wg * 8192, 16);
        const uint32_t kb = dlo(sb + OFF_KVB, 8192);
        wgmma_ss_n96<0>(accb, qa, kb);
#pragma unroll
        for (int kk = 1; kk < 4; kk++) wgmma_ss_n96<1>(accb, qa + kk * 2, kb + kk * 128);
      }
      wg_commit();
      STAGE_RELEASE(gs);
      keep_a(rs - 1);
      if (st == 5) mbar_wait(bar0 + 8 * BAR_RDY_O, 0);
      load_a(rs + 3);
      if (st == 1) {
        fence_regs(accb);
        uint4* o_out = g_o + (size_t)(slab * 32 + 4 * j) * 32 + lane;
#pragma unroll
        for (int hh = 0; hh < 4; hh++) {
          const float i0 = __fdividef(1.f, accb[32 + 4 * hh] + 1e-6f), i1 = __fdividef(1.f, accb[34 + 4 * hh] + 1e-6f);
          const float* n = accb + 8 * hh;
          stg_v4(o_out + hh * 32, pack2(n[0] * i0, n[1] * i0), pack2(n[2] * i1, n[3] * i1), pack2(n[4] * i0, n[5] * i0), pack2(n[6] * i1, n[7] * i1));
        }
        WARP_ARRIVE(BAR_PUB_O);
      }
    }
    PROF(8);
    const int c0 = 128 * nt + 64 * khalf + 2 * t;
    const size_t ro0 = (size_t)(rb * 128 + lr0) * DM + c0, ro1 = ro0 + 8 * DM;
    uint32_t xv[16];
#pragma unroll
    for (int st = 0; st < 8; st++) {
      const int gs = 48 + st, rs = 16 + st;
      STAGE_BEGIN(gs);
#pragma unroll
      for (int kk = 0; kk < 4; kk++) {
        if (st == 0 && kk == 0) wgmma_rs_n64<0>(accs, ab[rs & 3][kk], B_LO(gs, kk * 2048, 8192));
        else wgmma_rs_n64<1>(accs, ab[rs & 3][kk], B_LO(gs, kk * 2048, 8192));
      }
      wg_commit();
      STAGE_RELEASE(gs);
      keep_a(rs - 1);
      load_a(rs + 3);
      if (st == 0) {
        fence_regs(accy);
        float4* yp = g_yp + (size_t)((bid * 8 + warp) * 8) * 32 + lane;
#pragma unroll
        for (int q = 0; q < 8; q++)
          stg_v4(yp + q * 32, __float_as_uint(accy[32 + 4 * q]), __float_as_uint(accy[33 + 4 * q]), __float_as_uint(accy[34 + 4 * q]), __float_as_uint(accy[35 + 4 * q]));
        WARP_ARRIVE(BAR_PUB_Y);
      }
      if (st == 1) {
#pragma unroll
        for (int q = 0; q < 8; q++) { xv[2 * q] = ldg_nc32(x + ro0 + 8 * q); xv[2 * q + 1] = ldg_nc32(x + ro1 + 8 * q); }
      }
    }
    PROF(9);
    {
      mbar_wait(bar0 + 8 * BAR_RDY_Y, 0);
      PROF(10);
      const float4* yp = g_yp + (size_t)(((bid ^ 16) * 8 + warp) * 8) * 32 + lane;
      uint4 pv[8];
#pragma unroll
      for (int q = 0; q < 8; q++) pv[q] = ldg_cg(yp + q * 32);
      wg_wait<0>();
      keep_a(23);
      fence_regs(accs);
#pragma unroll
      for (int q = 0; q < 8; q++) {
        const float y0 = accy[4 * q] + __uint_as_float(pv[q].x), y1 = accy[4 * q + 1] + __uint_as_float(pv[q].y);
        const float y2 = accy[4 * q + 2] + __uint_as_float(pv[q].z), y3 = accy[4 * q + 3] + __uint_as_float(pv[q].w);
        const float o0 = fmaf(accs[4 * q], silu_f(y0), bf_lo(xv[2 * q])), o1 = fmaf(accs[4 * q + 1], silu_f(y1), bf_hi(xv[2 * q]));
        const float o2 = fmaf(accs[4 * q + 2], silu_f(y2), bf_lo(xv[2 * q + 1])), o3 = fmaf(accs[4 * q + 3], silu_f(y3), bf_hi(xv[2 * q + 1]));
        *reinterpret_cast<uint32_t*>(out + ro0 + 8 * q) = pack2(o0, o1);
        *reinterpret_cast<uint32_t*>(out + ro1 + 8 * q) = pack2(o2, o3);
      }
    }
    PROF(11);
    if (tid == 0) red_inc(&g_done);
  }
}

typedef CUresult (*EncodeFn)(CUtensorMap*, CUtensorMapDataType, cuuint32_t, void*, const cuuint64_t*, const cuuint64_t*,
                             const cuuint32_t*, const cuuint32_t*, CUtensorMapInterleave, CUtensorMapSwizzle,
                             CUtensorMapL2promotion, CUtensorMapFloatOOBfill);

void make_map(EncodeFn enc, CUtensorMap* tm, const void* ptr, int rows, int cols, int box_rows) {
  cuuint64_t gd[2] = {(cuuint64_t)cols, (cuuint64_t)rows};
  cuuint64_t gs[1] = {(cuuint64_t)cols * 2};
  cuuint32_t bd[2] = {64, (cuuint32_t)box_rows};
  cuuint32_t es[2] = {1, 1};
  enc(tm, CU_TENSOR_MAP_DATA_TYPE_BFLOAT16, 2, const_cast<void*>(ptr), gd, gs, bd, es, CU_TENSOR_MAP_INTERLEAVE_NONE,
      CU_TENSOR_MAP_SWIZZLE_128B, CU_TENSOR_MAP_L2_PROMOTION_L2_128B, CU_TENSOR_MAP_FLOAT_OOB_FILL_NONE);
}

}

extern "C" void kernel_launch(void* const* d_in, const int* in_sizes, int n_in, void* d_out, int out_size) {
  const __nv_bfloat16* x = (const __nv_bfloat16*)d_in[0];
  const void* wqkv = d_in[1];
  const void* wo = d_in[2];
  const void* w1 = d_in[4];
  const __nv_bfloat16* b1 = (const __nv_bfloat16*)d_in[5];
  const void* w2 = d_in[6];
  static EncodeFn enc = nullptr;
  if (!enc) {
    cudaDriverEntryPointQueryResult qr;
    void* fn = nullptr;
    cudaGetDriverEntryPoint("cuTensorMapEncodeTiled", &fn, cudaEnableDefault, &qr);
    enc = (EncodeFn)fn;
    cudaFuncSetAttribute(fused_kernel, cudaFuncAttributeMaxDynamicSharedMemorySize, SMEM_ALLOC);
  }
  CUtensorMap tx, tq, t1, t2a, t2b, to;
  make_map(enc, &tx, x, 2048, DM, 128);
  make_map(enc, &tq, wqkv, DM, 3 * DM, 32);
  make_map(enc, &t1, w1, DM, FF, 64);
  make_map(enc, &t2a, w2, FF, DM, 64);
  make_map(enc, &t2b, w2, FF, DM, 48);
  make_map(enc, &to, wo, DM, DM, 64);
  fused_kernel<<<NCTA, 384, SMEM_ALLOC>>>(tx, tq, t1, t2a, t2b, to, x, b1, (__nv_bfloat16*)d_out);
}
```

```cpp
#include <cuda_runtime.h>
#include <cuda_bf16.h>
#include <cuda.h>
#include <stdint.h>

namespace {

constexpr int DM = 512, FF = 1792;
constexpr int NCTA = 128;
constexpr int NSLOT = 5;
constexpr int SLOT_BYTES = 16384;
constexpr int OFF_D = 0;
constexpr int OFF_KVB = 0;
constexpr int OFF_RING = 131072;
constexpr int OFF_MISC = OFF_RING + NSLOT * SLOT_BYTES;
constexpr int OFF_ONES = OFF_MISC;
constexpr int OFF_BAR = OFF_MISC + 8192;
constexpr int OFF_B1 = OFF_MISC + 8448;
constexpr int SMEM_ALLOC = OFF_MISC + 9472;

enum { BAR_FULL = 0, BAR_EMPTY = NSLOT, BAR_X = 2 * NSLOT, BAR_BIAS = BAR_X + 4,
       BAR_PUB_A, BAR_PUB_KV, BAR_PUB_B, BAR_PUB_O, BAR_DFREE,
       BAR_RDY_A, BAR_RDY_B, BAR_RDY_O, BAR_RDY_KV, BAR_COUNT };
static_assert(BAR_COUNT <= 32, "too many barriers");

constexpr int NSTAGES = 58;

__device__ uint4 g_act[128 * 112 * 32];
__device__ uint4 g_o[128 * 32 * 32];
__device__ float4 g_yp[NCTA * 8 * 8 * 32];
__device__ float g_kv[2][32 * 272];
__device__ unsigned g_cntA[16 * 2 * 8];
__device__ unsigned g_cntB[16 * 2 * 8];
__device__ unsigned g_cntO[16 * 8];
__device__ unsigned g_cntKV[8 * 8];
__device__ unsigned g_done;

#define PROF(i)

__device__ __forceinline__ uint32_t smem_u32(const void* p) { return (uint32_t)__cvta_generic_to_shared(p); }
__device__ __forceinline__ void mbar_init(uint32_t bar, uint32_t cnt) { asm volatile("mbarrier.init.shared::cta.b64 [%0], %1;" ::"r"(bar), "r"(cnt)); }
__device__ __forceinline__ void mbar_expect_tx(uint32_t bar, uint32_t bytes) { asm volatile("mbarrier.arrive.expect_tx.shared::cta.b64 _, [%0], %1;" ::"r"(bar), "r"(bytes) : "memory"); }
__device__ __forceinline__ void mbar_arrive(uint32_t bar) { asm volatile("mbarrier.arrive.shared::cta.b64 _, [%0];" ::"r"(bar) : "memory"); }
__device__ __forceinline__ void mbar_wait(uint32_t bar, uint32_t parity) {
  asm volatile("{\n.reg .pred P1;\n.reg .u32 cnt;\n"
               "mbarrier.try_wait.parity.shared::cta.b64 P1, [%0], %1;\n@P1 bra DONE;\n"
               "mov.u32 cnt, 0;\n"
               "LAB_WAIT:\n"
               "mbarrier.try_wait.parity.shared::cta.b64 P1, [%0], %1;\n@P1 bra DONE;\n"
               "add.u32 cnt, cnt, 1;\nsetp.lt.u32 P1, cnt, 16777216;\n@P1 bra LAB_WAIT;\ntrap;\n"
               "DONE:\n}" ::"r"(bar), "r"(parity) : "memory");
}
__device__ __forceinline__ void tma2d(uint32_t dst, const CUtensorMap* tm, int c0, int c1, uint32_t bar) {
  asm volatile("cp.async.bulk.tensor.2d.shared::cluster.global.mbarrier::complete_tx::bytes [%0], [%1, {%3, %4}], [%2];" ::"r"(dst), "l"(tm), "r"(bar), "r"(c0), "r"(c1) : "memory");
}
__device__ __forceinline__ void wg_fence() { asm volatile("wgmma.fence.sync.aligned;" ::: "memory"); }
__device__ __forceinline__ void wg_commit() { asm volatile("wgmma.commit_group.sync.aligned;" ::: "memory"); }
template <int N> __device__ __forceinline__ void wg_wait() { asm volatile("wgmma.wait_group.sync.aligned %0;" ::"n"(N) : "memory"); }
template <int N> __device__ __forceinline__ void zero_regs(float (&d)[N]) {
#pragma unroll
  for (int i = 0; i < N; i++) d[i] = 0.f;
}
template <int N> __device__ __forceinline__ void fence_regs(float (&d)[N]) {
#pragma unroll
  for (int i = 0; i < N; i++) asm volatile("" : "+f"(d[i])::"memory");
}
__device__ __forceinline__ void fence_u4(uint4& v) { asm volatile("" : "+r"(v.x), "+r"(v.y), "+r"(v.z), "+r"(v.w)::"memory"); }
__device__ __forceinline__ void named_bar_sync(int id, int n) { asm volatile("bar.sync %0, %1;" ::"r"(id), "r"(n) : "memory"); }
__device__ __forceinline__ void fence_async_smem() { asm volatile("fence.proxy.async.shared::cta;" ::: "memory"); }
__device__ __forceinline__ constexpr uint32_t dlo(uint32_t addr, uint32_t lbo_bytes) { return ((addr & 0x3FFFFu) >> 4) | ((lbo_bytes >> 4) << 16); }
__device__ __forceinline__ void mma16816(float (&c)[4], uint32_t a0, uint32_t a1, uint32_t a2, uint32_t a3, uint32_t b0, uint32_t b1) {
  asm volatile("mma.sync.aligned.m16n8k16.row.col.f32.bf16.bf16.f32 {%0,%1,%2,%3}, {%4,%5,%6,%7}, {%8,%9}, {%0,%1,%2,%3};"
               : "+f"(c[0]), "+f"(c[1]), "+f"(c[2]), "+f"(c[3]) : "r"(a0), "r"(a1), "r"(a2), "r"(a3), "r"(b0), "r"(b1));
}
__device__ __forceinline__ void stmatrix_x4(uint32_t addr, uint32_t a, uint32_t b, uint32_t c, uint32_t d) {
  asm volatile("stmatrix.sync.aligned.m8n8.x4.shared.b16 [%0], {%1,%2,%3,%4};" ::"r"(addr), "r"(a), "r"(b), "r"(c), "r"(d) : "memory");
}
__device__ __forceinline__ uint32_t pack2(float lo, float hi) { uint32_t r; asm("cvt.rn.bf16x2.f32 %0, %1, %2;" : "=r"(r) : "f"(hi), "f"(lo)); return r; }
__device__ __forceinline__ float ex2(float x) { float r; asm("ex2.approx.ftz.f32 %0, %1;" : "=f"(r) : "f"(x)); return r; }
__device__ __forceinline__ float rcp(float x) { float r; asm("rcp.approx.ftz.f32 %0, %1;" : "=f"(r) : "f"(x)); return r; }
__device__ __forceinline__ float bf_lo(uint32_t v) { return __uint_as_float(v << 16); }
__device__ __forceinline__ float bf_hi(uint32_t v) { return __uint_as_float(v & 0xffff0000u); }
__device__ __forceinline__ uint32_t hsub2_bf16(uint32_t a, uint32_t b) {
  __nv_bfloat162 x = *reinterpret_cast<__nv_bfloat162*>(&a), y = *reinterpret_cast<__nv_bfloat162*>(&b);
  __nv_bfloat162 r = __hsub2(x, y);
  return *reinterpret_cast<uint32_t*>(&r);
}
__device__ __forceinline__ uint32_t ldg_nc32(const void* p) {
  uint32_t v; asm volatile("ld.global.nc.u32 %0, [%1];" : "=r"(v) : "l"(p)); return v;
}
__device__ __forceinline__ uint4 ldg_cg(const void* p) {
  uint4 v; asm volatile("ld.global.cg.v4.u32 {%0,%1,%2,%3}, [%4];" : "=r"(v.x), "=r"(v.y), "=r"(v.z), "=r"(v.w) : "l"(p) : "memory"); return v;
}
__device__ __forceinline__ void stg_v4(void* p, uint32_t a, uint32_t b, uint32_t c, uint32_t d) {
  asm volatile("st.global.v4.u32 [%0], {%1,%2,%3,%4};" ::"l"(p), "r"(a), "r"(b), "r"(c), "r"(d) : "memory");
}
__device__ __forceinline__ void sts_v4(uint32_t addr, uint32_t a, uint32_t b, uint32_t c, uint32_t d) {
  asm volatile("st.shared.v4.u32 [%0], {%1,%2,%3,%4};" ::"r"(addr), "r"(a), "r"(b), "r"(c), "r"(d) : "memory");
}
__device__ __forceinline__ void sts_f32(uint32_t addr, float v) { asm volatile("st.shared.f32 [%0], %1;" ::"r"(addr), "f"(v) : "memory"); }
__device__ __forceinline__ uint4 lds_v4(uint32_t addr) { uint4 v; asm volatile("ld.shared.v4.u32 {%0,%1,%2,%3}, [%4];" : "=r"(v.x), "=r"(v.y), "=r"(v.z), "=r"(v.w) : "r"(addr) : "memory"); return v; }
__device__ __forceinline__ float2 lds_f32x2(uint32_t addr) { float2 v; asm volatile("ld.shared.v2.f32 {%0,%1}, [%2];" : "=f"(v.x), "=f"(v.y) : "r"(addr) : "memory"); return v; }
__device__ __forceinline__ void red_add_v2(float* p, float a, float b) { asm volatile("red.relaxed.gpu.global.add.v2.f32 [%0], {%1,%2};" ::"l"(p), "f"(a), "f"(b) : "memory"); }
__device__ __forceinline__ void red_add_f32(float* p, float a) { asm volatile("red.relaxed.gpu.global.add.f32 [%0], %1;" ::"l"(p), "f"(a) : "memory"); }
__device__ __forceinline__ void red_inc(unsigned* cnt) { asm volatile("red.relaxed.gpu.global.add.u32 [%0], 1;" ::"l"(cnt) : "memory"); }
__device__ __forceinline__ void poll_ge(const unsigned* cnt, unsigned target) {
  asm volatile("{\n.reg .pred P1;\n.reg .u32 cnt, v;\n.reg .s32 d;\n"
               "mov.u32 cnt, 0;\n"
               "LAB_POLL:\n"
               "ld.acquire.gpu.global.u32 v, [%0];\nsub.s32 d, v, %1;\nsetp.ge.s32 P1, d, 0;\n@P1 bra DONE;\n"
               "add.u32 cnt, cnt, 1;\nsetp.lt.u32 P1, cnt, 4194304;\n@P1 bra LAB_POLL;\ntrap;\n"
               "DONE:\n}" ::"l"(cnt), "r"(target) : "memory");
}

template <int SCALE_D> __device__ __forceinline__ void wgmma_ss_n192(float (&d)[96], uint32_t da, uint32_t db) {
  asm volatile("{\n.reg .b64 da, db;\nmov.b64 da, {%96, %98};\nmov.b64 db, {%97, %98};\n"
    "wgmma.mma_async.sync.aligned.m64n192k16.f32.bf16.bf16 {%0, %1, %2, %3, %4, %5, %6, %7, %8, %9, %10, %11, %12, %13, %14, %15, %16, %17, %18, %19, %20, %21, %22, %23, %24, %25, %26, %27, %28, %29, %30, %31, %32, %33, %34, %35, %36, %37, %38, %39, %40, %41, %42, %43, %44, %45, %46, %47, %48, %49, %50, %51, %52, %53, %54, %55, %56, %57, %58, %59, %60, %61, %62, %63, %64, %65, %66, %67, %68, %69, %70, %71, %72, %73, %74, %75, %76, %77, %78, %79, %80, %81, %82, %83, %84, %85, %86, %87, %88, %89, %90, %91, %92, %93, %94, %95}, da, db, %99, 1, 1, 0, 1;\n}\n"
    : "+f"(d[0]), "+f"(d[1]), "+f"(d[2]), "+f"(d[3]), "+f"(d[4]), "+f"(d[5]), "+f"(d[6]), "+f"(d[7]), "+f"(d[8]), "+f"(d[9]), "+f"(d[10]), "+f"(d[11]), "+f"(d[12]), "+f"(d[13]), "+f"(d[14]), "+f"(d[15]), "+f"(d[16]), "+f"(d[17]), "+f"(d[18]), "+f"(d[19]), "+f"(d[20]), "+f"(d[21]), "+f"(d[22]), "+f"(d[23]), "+f"(d[24]), "+f"(d[25]), "+f"(d[26]), "+f"(d[27]), "+f"(d[28]), "+f"(d[29]), "+f"(d[30]), "+f"(d[31]), "+f"(d[32]), "+f"(d[33]), "+f"(d[34]), "+f"(d[35]), "+f"(d[36]), "+f"(d[37]), "+f"(d[38]), "+f"(d[39]), "+f"(d[40]), "+f"(d[41]), "+f"(d[42]), "+f"(d[43]), "+f"(d[44]), "+f"(d[45]), "+f"(d[46]), "+f"(d[47]), "+f"(d[48]), "+f"(d[49]), "+f"(d[50]), "+f"(d[51]), "+f"(d[52]), "+f"(d[53]), "+f"(d[54]), "+f"(d[55]), "+f"(d[56]), "+f"(d[57]), "+f"(d[58]), "+f"(d[59]), "+f"(d[60]), "+f"(d[61]), "+f"(d[62]), "+f"(d[63]), "+f"(d[64]), "+f"(d[65]), "+f"(d[66]), "+f"(d[67]), "+f"(d[68]), "+f"(d[69]), "+f"(d[70]), "+f"(d[71]), "+f"(d[72]), "+f"(d[73]), "+f"(d[74]), "+f"(d[75]), "+f"(d[76]), "+f"(d[77]), "+f"(d[78]), "+f"(d[79]), "+f"(d[80]), "+f"(d[81]), "+f"(d[82]), "+f"(d[83]), "+f"(d[84]), "+f"(d[85]), "+f"(d[86]), "+f"(d[87]), "+f"(d[88]), "+f"(d[89]), "+f"(d[90]), "+f"(d[91]), "+f"(d[92]), "+f"(d[93]), "+f"(d[94]), "+f"(d[95])
    : "r"(da), "r"(db), "r"(0x40000040u), "n"(SCALE_D));
}
template <int SCALE_D> __device__ __forceinline__ void wgmma_ss_n128(float (&d)[64], uint32_t da, uint32_t db) {
  asm volatile("{\n.reg .b64 da, db;\nmov.b64 da, {%64, %66};\nmov.b64 db, {%65, %66};\n"
    "wgmma.mma_async.sync.aligned.m64n128k16.f32.bf16.bf16 {%0, %1, %2, %3, %4, %5, %6, %7, %8, %9, %10, %11, %12, %13, %14, %15, %16, %17, %18, %19, %20, %21, %22, %23, %24, %25, %26, %27, %28, %29, %30, %31, %32, %33, %34, %35, %36, %37, %38, %39, %40, %41, %42, %43, %44, %45, %46, %47, %48, %49, %50, %51, %52, %53, %54, %55, %56, %57, %58, %59, %60, %61, %62, %63}, da, db, %67, 1, 1, 0, 1;\n}\n"
    : "+f"(d[0]), "+f"(d[1]), "+f"(d[2]), "+f"(d[3]), "+f"(d[4]), "+f"(d[5]), "+f"(d[6]), "+f"(d[7]), "+f"(d[8]), "+f"(d[9]), "+f"(d[10]), "+f"(d[11]), "+f"(d[12]), "+f"(d[13]), "+f"(d[14]), "+f"(d[15]), "+f"(d[16]), "+f"(d[17]), "+f"(d[18]), "+f"(d[19]), "+f"(d[20]), "+f"(d[21]), "+f"(d[22]), "+f"(d[23]), "+f"(d[24]), "+f"(d[25]), "+f"(d[26]), "+f"(d[27]), "+f"(d[28]), "+f"(d[29]), "+f"(d[30]), "+f"(d[31]), "+f"(d[32]), "+f"(d[33]), "+f"(d[34]), "+f"(d[35]), "+f"(d[36]), "+f"(d[37]), "+f"(d[38]), "+f"(d[39]), "+f"(d[40]), "+f"(d[41]), "+f"(d[42]), "+f"(d[43]), "+f"(d[44]), "+f"(d[45]), "+f"(d[46]), "+f"(d[47]), "+f"(d[48]), "+f"(d[49]), "+f"(d[50]), "+f"(d[51]), "+f"(d[52]), "+f"(d[53]), "+f"(d[54]), "+f"(d[55]), "+f"(d[56]), "+f"(d[57]), "+f"(d[58]), "+f"(d[59]), "+f"(d[60]), "+f"(d[61]), "+f"(d[62]), "+f"(d[63])
    : "r"(da), "r"(db), "r"(0x40000040u), "n"(SCALE_D));
}
template <int SCALE_D> __device__ __forceinline__ void wgmma_ss_n96(float (&d)[48], uint32_t da, uint32_t db) {
  asm volatile("{\n.reg .b64 da, db;\nmov.b64 da, {%48, %50};\nmov.b64 db, {%49, %50};\n"
    "wgmma.mma_async.sync.aligned.m64n96k16.f32.bf16.bf16 {%0, %1, %2, %3, %4, %5, %6, %7, %8, %9, %10, %11, %12, %13, %14, %15, %16, %17, %18, %19, %20, %21, %22, %23, %24, %25, %26, %27, %28, %29, %30, %31, %32, %33, %34, %35, %36, %37, %38, %39, %40, %41, %42, %43, %44, %45, %46, %47}, da, db, %51, 1, 1, 0, 1;\n}\n"
    : "+f"(d[0]), "+f"(d[1]), "+f"(d[2]), "+f"(d[3]), "+f"(d[4]), "+f"(d[5]), "+f"(d[6]), "+f"(d[7]), "+f"(d[8]), "+f"(d[9]), "+f"(d[10]), "+f"(d[11]), "+f"(d[12]), "+f"(d[13]), "+f"(d[14]), "+f"(d[15]), "+f"(d[16]), "+f"(d[17]), "+f"(d[18]), "+f"(d[19]), "+f"(d[20]), "+f"(d[21]), "+f"(d[22]), "+f"(d[23]), "+f"(d[24]), "+f"(d[25]), "+f"(d[26]), "+f"(d[27]), "+f"(d[28]), "+f"(d[29]), "+f"(d[30]), "+f"(d[31]), "+f"(d[32]), "+f"(d[33]), "+f"(d[34]), "+f"(d[35]), "+f"(d[36]), "+f"(d[37]), "+f"(d[38]), "+f"(d[39]), "+f"(d[40]), "+f"(d[41]), "+f"(d[42]), "+f"(d[43]), "+f"(d[44]), "+f"(d[45]), "+f"(d[46]), "+f"(d[47])
    : "r"(da), "r"(db), "r"(0x40000040u), "n"(SCALE_D));
}
template <int SCALE_D> __device__ __forceinline__ void wgmma_tt_n72(float (&d)[36], uint32_t da, uint32_t db) {
  asm volatile("{\n.reg .b64 da, db;\nmov.b64 da, {%36, %38};\nmov.b64 db, {%37, %38};\n"
    "wgmma.mma_async.sync.aligned.m64n72k16.f32.bf16.bf16 {%0, %1, %2, %3, %4, %5, %6, %7, %8, %9, %10, %11, %12, %13, %14, %15, %16, %17, %18, %19, %20, %21, %22, %23, %24, %25, %26, %27, %28, %29, %30, %31, %32, %33, %34, %35}, da, db, %39, 1, 1, 1, 1;\n}\n"
    : "+f"(d[0]), "+f"(d[1]), "+f"(d[2]), "+f"(d[3]), "+f"(d[4]), "+f"(d[5]), "+f"(d[6]), "+f"(d[7]), "+f"(d[8]), "+f"(d[9]), "+f"(d[10]), "+f"(d[11]), "+f"(d[12]), "+f"(d[13]), "+f"(d[14]), "+f"(d[15]), "+f"(d[16]), "+f"(d[17]), "+f"(d[18]), "+f"(d[19]), "+f"(d[20]), "+f"(d[21]), "+f"(d[22]), "+f"(d[23]), "+f"(d[24]), "+f"(d[25]), "+f"(d[26]), "+f"(d[27]), "+f"(d[28]), "+f"(d[29]), "+f"(d[30]), "+f"(d[31]), "+f"(d[32]), "+f"(d[33]), "+f"(d[34]), "+f"(d[35])
    : "r"(da), "r"(db), "r"(0x40000040u), "n"(SCALE_D));
}
template <int SCALE_D> __device__ __forceinline__ void wgmma_rs_n128(float (&d)[64], const uint4& a, uint32_t db) {
  asm volatile("{\n.reg .b64 db;\nmov.b64 db, {%68, %69};\n"
    "wgmma.mma_async.sync.aligned.m64n128k16.f32.bf16.bf16 {%0, %1, %2, %3, %4, %5, %6, %7, %8, %9, %10, %11, %12, %13, %14, %15, %16, %17, %18, %19, %20, %21, %22, %23, %24, %25, %26, %27, %28, %29, %30, %31, %32, %33, %34, %35, %36, %37, %38, %39, %40, %41, %42, %43, %44, %45, %46, %47, %48, %49, %50, %51, %52, %53, %54, %55, %56, %57, %58, %59, %60, %61, %62, %63}, {%64, %65, %66, %67}, db, %70, 1, 1, 1;\n}\n"
    : "+f"(d[0]), "+f"(d[1]), "+f"(d[2]), "+f"(d[3]), "+f"(d[4]), "+f"(d[5]), "+f"(d[6]), "+f"(d[7]), "+f"(d[8]), "+f"(d[9]), "+f"(d[10]), "+f"(d[11]), "+f"(d[12]), "+f"(d[13]), "+f"(d[14]), "+f"(d[15]), "+f"(d[16]), "+f"(d[17]), "+f"(d[18]), "+f"(d[19]), "+f"(d[20]), "+f"(d[21]), "+f"(d[22]), "+f"(d[23]), "+f"(d[24]), "+f"(d[25]), "+f"(d[26]), "+f"(d[27]), "+f"(d[28]), "+f"(d[29]), "+f"(d[30]), "+f"(d[31]), "+f"(d[32]), "+f"(d[33]), "+f"(d[34]), "+f"(d[35]), "+f"(d[36]), "+f"(d[37]), "+f"(d[38]), "+f"(d[39]), "+f"(d[40]), "+f"(d[41]), "+f"(d[42]), "+f"(d[43]), "+f"(d[44]), "+f"(d[45]), "+f"(d[46]), "+f"(d[47]), "+f"(d[48]), "+f"(d[49]), "+f"(d[50]), "+f"(d[51]), "+f"(d[52]), "+f"(d[53]), "+f"(d[54]), "+f"(d[55]), "+f"(d[56]), "+f"(d[57]), "+f"(d[58]), "+f"(d[59]), "+f"(d[60]), "+f"(d[61]), "+f"(d[62]), "+f"(d[63])
    : "r"(a.x), "r"(a.y), "r"(a.z), "r"(a.w), "r"(db), "r"(0x40000040u), "n"(SCALE_D));
}
template <int SCALE_D> __device__ __forceinline__ void wgmma_rs_n96(float (&d)[48], const uint4& a, uint32_t db) {
  asm volatile("{\n.reg .b64 db;\nmov.b64 db, {%52, %53};\n"
    "wgmma.mma_async.sync.aligned.m64n96k16.f32.bf16.bf16 {%0, %1, %2, %3, %4, %5, %6, %7, %8, %9, %10, %11, %12, %13, %14, %15, %16, %17, %18, %19, %20, %21, %22, %23, %24, %25, %26, %27, %28, %29, %30, %31, %32, %33, %34, %35, %36, %37, %38, %39, %40, %41, %42, %43, %44, %45, %46, %47}, {%48, %49, %50, %51}, db, %54, 1, 1, 1;\n}\n"
    : "+f"(d[0]), "+f"(d[1]), "+f"(d[2]), "+f"(d[3]), "+f"(d[4]), "+f"(d[5]), "+f"(d[6]), "+f"(d[7]), "+f"(d[8]), "+f"(d[9]), "+f"(d[10]), "+f"(d[11]), "+f"(d[12]), "+f"(d[13]), "+f"(d[14]), "+f"(d[15]), "+f"(d[16]), "+f"(d[17]), "+f"(d[18]), "+f"(d[19]), "+f"(d[20]), "+f"(d[21]), "+f"(d[22]), "+f"(d[23]), "+f"(d[24]), "+f"(d[25]), "+f"(d[26]), "+f"(d[27]), "+f"(d[28]), "+f"(d[29]), "+f"(d[30]), "+f"(d[31]), "+f"(d[32]), "+f"(d[33]), "+f"(d[34]), "+f"(d[35]), "+f"(d[36]), "+f"(d[37]), "+f"(d[38]), "+f"(d[39]), "+f"(d[40]), "+f"(d[41]), "+f"(d[42]), "+f"(d[43]), "+f"(d[44]), "+f"(d[45]), "+f"(d[46]), "+f"(d[47])
    : "r"(a.x), "r"(a.y), "r"(a.z), "r"(a.w), "r"(db), "r"(0x40000040u), "n"(SCALE_D));
}
template <int SCALE_D> __device__ __forceinline__ void wgmma_rs_n64(float (&d)[32], const uint4& a, uint32_t db) {
  asm volatile("{\n.reg .b64 db;\nmov.b64 db, {%36, %37};\n"
    "wgmma.mma_async.sync.aligned.m64n64k16.f32.bf16.bf16 {%0, %1, %2, %3, %4, %5, %6, %7, %8, %9, %10, %11, %12, %13, %14, %15, %16, %17, %18, %19, %20, %21, %22, %23, %24, %25, %26, %27, %28, %29, %30, %31}, {%32, %33, %34, %35}, db, %38, 1, 1, 1;\n}\n"
    : "+f"(d[0]), "+f"(d[1]), "+f"(d[2]), "+f"(d[3]), "+f"(d[4]), "+f"(d[5]), "+f"(d[6]), "+f"(d[7]), "+f"(d[8]), "+f"(d[9]), "+f"(d[10]), "+f"(d[11]), "+f"(d[12]), "+f"(d[13]), "+f"(d[14]), "+f"(d[15]), "+f"(d[16]), "+f"(d[17]), "+f"(d[18]), "+f"(d[19]), "+f"(d[20]), "+f"(d[21]), "+f"(d[22]), "+f"(d[23]), "+f"(d[24]), "+f"(d[25]), "+f"(d[26]), "+f"(d[27]), "+f"(d[28]), "+f"(d[29]), "+f"(d[30]), "+f"(d[31])
    : "r"(a.x), "r"(a.y), "r"(a.z), "r"(a.w), "r"(db), "r"(0x40000040u), "n"(SCALE_D));
}

constexpr float LOG2E = 1.4426950408889634f;
__device__ __forceinline__ float phi_f(float t) {
  float e = ex2(t * LOG2E);
  return (t > 0.f ? t + 1.f : e) + 1e-6f;
}
__device__ __forceinline__ float silu_f(float y) { return y * rcp(1.f + ex2(-y * LOG2E)); }

__device__ __forceinline__ void mish_tile(const float* c, uint32_t bias_addr, float rs0, float rs1, uint4* dst) {
  const float2 ba = lds_f32x2(bias_addr);
  const float2 bb = lds_f32x2(bias_addr + 32);
  float h[8], u[8], r[8];
  h[0] = fmaf(c[0], rs0, ba.x); h[1] = fmaf(c[1], rs0, ba.y); h[2] = fmaf(c[2], rs1, ba.x); h[3] = fmaf(c[3], rs1, ba.y);
  h[4] = fmaf(c[4], rs0, bb.x); h[5] = fmaf(c[5], rs0, bb.y); h[6] = fmaf(c[6], rs1, bb.x); h[7] = fmaf(c[7], rs1, bb.y);
#pragma unroll
  for (int i = 0; i < 8; i++) u[i] = ex2(fminf(h[i], 20.f) * LOG2E);
#pragma unroll
  for (int i = 0; i < 8; i++) { const float tt = u[i] + 2.f; r[i] = rcp(fmaf(u[i], tt, 2.f)); h[i] *= u[i] * tt; }
#pragma unroll
  for (int i = 0; i < 8; i++) h[i] *= r[i];
  stg_v4(dst, pack2(h[0], h[1]), pack2(h[2], h[3]), pack2(h[4], h[5]), pack2(h[6], h[7]));
}

__global__ void __launch_bounds__(384, 1)
fused_kernel(const __grid_constant__ CUtensorMap tm_x, const __grid_constant__ CUtensorMap tm_qkv,
             const __grid_constant__ CUtensorMap tm_w1, const __grid_constant__ CUtensorMap tm_w2a,
             const __grid_constant__ CUtensorMap tm_w2b, const __grid_constant__ CUtensorMap tm_wo,
             const __nv_bfloat16* __restrict__ x, const __nv_bfloat16* __restrict__ b1, __nv_bfloat16* __restrict__ out) {
  extern __shared__ __align__(1024) uint8_t smem_raw[];
  const uint32_t sb = smem_u32(smem_raw);
  const int tid = threadIdx.x, lane = tid & 31;
  const int warp = __shfl_sync(0xffffffffu, tid >> 5, 0);
  const int bid = blockIdx.x;
  const int G = bid >> 4, gi = bid & 15;
  const int khalf = G & 1;
  const int rb = (G >> 1) * 4 + (gi >> 2);
  const int nt = gi & 3;
  const int j = khalf + 2 * nt;
  const uint32_t bar0 = sb + OFF_BAR;
  PROF(0);

  if (warp >= 8) {
    asm volatile("setmaxnreg.dec.sync.aligned.u32 40;");
    if (warp == 8) {
      if (lane == 0) {
        if (sb & 1023u) asm volatile("trap;");
        for (int i = 0; i < NSLOT; i++) { mbar_init(bar0 + 8 * (BAR_FULL + i), 1); mbar_init(bar0 + 8 * (BAR_EMPTY + i), 8); }
        for (int i = 0; i < 4; i++) mbar_init(bar0 + 8 * (BAR_X + i), 1);
        mbar_init(bar0 + 8 * BAR_BIAS, 1);
        for (int i = BAR_PUB_A; i <= BAR_DFREE; i++) mbar_init(bar0 + 8 * i, 8);
        for (int i = BAR_RDY_A; i <= BAR_RDY_KV; i++) mbar_init(bar0 + 8 * i, 1);
        asm volatile("fence.mbarrier_init.release.cluster;" ::: "memory");
        fence_async_smem();
        for (int i = 0; i < 4; i++) {
          mbar_expect_tx(bar0 + 8 * (BAR_X + i), 32768);
          tma2d(sb + OFF_D + (2 * i) * 16384, &tm_x, 128 * i, rb * 128, bar0 + 8 * (BAR_X + i));
          tma2d(sb + OFF_D + (2 * i + 1) * 16384, &tm_x, 128 * i + 64, rb * 128, bar0 + 8 * (BAR_X + i));
        }
      }
      __syncwarp();
      named_bar_sync(0, 384);
      if (lane == 0) {
        const int c_own = 128 * nt + 64 * khalf, c_par = 128 * nt + 64 * (1 - khalf);
        int slot = 0; uint32_t phase = 1;
        for (int st = 0; st < NSTAGES; st++) {
          const uint32_t full = bar0 + 8 * (BAR_FULL + slot);
          const uint32_t dst = sb + OFF_RING + slot * SLOT_BYTES;
          mbar_wait(bar0 + 8 * (BAR_EMPTY + slot), phase);
          if (st < 8) {
            mbar_expect_tx(full, 16384);
            const int k0 = 64 * st, c0 = 224 * j;
            tma2d(dst, &tm_w1, c0, k0, full);
            tma2d(dst + 8192, &tm_w1, c0 + 64, k0, full);
          } else if (st < 24) {
            mbar_expect_tx(full, 12288);
            const int k0 = 32 * (st - 8);
            tma2d(dst, &tm_qkv, 64 * j, k0, full);
            tma2d(dst + 4096, &tm_qkv, 512 + 64 * j, k0, full);
            tma2d(dst + 8192, &tm_qkv, 1024 + 64 * j, k0, full);
          } else if (st == 29 || st == 30) {
            mbar_arrive(full);
          } else if (st < 34) {
            mbar_expect_tx(full, 16384);
            const int k0 = 64 * (st < 29 ? st - 24 : st - 26), c0 = 224 * j + 128;
            tma2d(dst, &tm_w1, c0, k0, full);
            tma2d(dst + 8192, &tm_w1, c0 + 64, k0, full);
          } else if (st < 42) {
            mbar_expect_tx(full, 16384);
            const int i = st - 34;
            const int k0 = 224 * (4 * khalf + (i >> 1)) + 64 * (i & 1);
            tma2d(dst, &tm_w2a, c_own, k0, full);
            tma2d(dst + 8192, &tm_w2a, c_par, k0, full);
          } else if (st < 50) {
            mbar_expect_tx(full, 12288);
            const int i = st - 42;
            const int k0 = 224 * (4 * khalf + (i >> 1)) + 128 + 48 * (i & 1);
            tma2d(dst, &tm_w2b, c_own, k0, full);
            tma2d(dst + 6144, &tm_w2b, c_par, k0, full);
          } else {
            mbar_expect_tx(full, 8192);
            tma2d(dst, &tm_wo, c_own, 64 * (st - 50), full);
          }
          if (++slot == NSLOT) { slot = 0; phase ^= 1; }
        }
      }
    } else {
      const int aw = warp - 9;
      unsigned dn; asm volatile("ld.relaxed.gpu.global.u32 %0, [%1];" : "=r"(dn) : "l"(&g_done) : "memory");
      named_bar_sync(0, 384);
      const unsigned ep1 = dn / NCTA + 1u;
      if (aw == 0) {
        for (int i = lane; i < 224; i += 32) sts_f32(sb + OFF_B1 + 4 * i, __bfloat162float(b1[224 * j + i]));
#pragma unroll 4
        for (int i = 0; i < 16; i++) sts_v4(sb + OFF_ONES + (i * 32 + lane) * 16, 0x3F803F80u, 0x3F803F80u, 0x3F803F80u, 0x3F803F80u);
        fence_async_smem();
        __syncwarp();
        if (lane == 0) {
          mbar_arrive(bar0 + 8 * BAR_BIAS);
          mbar_wait(bar0 + 8 * BAR_PUB_A, 0);  __threadfence(); red_inc(&g_cntA[(rb * 2 + (j >> 2)) * 8]);
          mbar_wait(bar0 + 8 * BAR_PUB_KV, 0); __threadfence(); red_inc(&g_cntKV[j * 8]);
          mbar_wait(bar0 + 8 * BAR_PUB_B, 0);  __threadfence(); red_inc(&g_cntB[(rb * 2 + (j >> 2)) * 8]);
          mbar_wait(bar0 + 8 * BAR_PUB_O, 0);  __threadfence(); red_inc(&g_cntO[rb * 8]);
        }
      } else if (aw == 1) {
        if (lane == 0) {
          poll_ge(&g_cntA[(rb * 2 + khalf) * 8], 4u * ep1); mbar_arrive(bar0 + 8 * BAR_RDY_A);
          PROF(1);
          poll_ge(&g_cntB[(rb * 2 + khalf) * 8], 4u * ep1); mbar_arrive(bar0 + 8 * BAR_RDY_B);
          PROF(2);
          poll_ge(&g_cntO[rb * 8], 8u * ep1);               mbar_arrive(bar0 + 8 * BAR_RDY_O);
          PROF(3);
        }
      } else {
        if (rb == 0) {
          float4* z = reinterpret_cast<float4*>(&g_kv[ep1 & 1][4 * j * 272]);
          for (int i = lane; i < 272; i += 32) z[i] = make_float4(0.f, 0.f, 0.f, 0.f);
        }
        const float* kvbuf = &g_kv[(ep1 & 1) ^ 1][4 * j * 272];
        mbar_wait(bar0 + 8 * BAR_DFREE, 0);
#pragma unroll 4
        for (int i = 0; i < 32; i++) sts_v4(sb + OFF_KVB + (i * 32 + lane) * 16, 0u, 0u, 0u, 0u);
        PROF(1);
        if (lane == 0) poll_ge(&g_cntKV[j * 8], 16u * ep1);
        __syncwarp();
        PROF(2);
#pragma unroll 1
        for (int q0 = 0; q0 < 9; q0 += 5) {
          uint4 tv[5];
#pragma unroll
          for (int q = 0; q < 5; q++) { const int i = (q0 + q) * 32 + lane; if (i < 272) tv[q] = ldg_cg(reinterpret_cast<const float4*>(kvbuf) + i); }
#pragma unroll
          for (int q = 0; q < 5; q++) {
            const int i = (q0 + q) * 32 + lane;
            if (i < 272) {
              const int hh = i / 68, e4 = (i - hh * 68) * 4;
              const float vals[4] = {__uint_as_float(tv[q].x), __uint_as_float(tv[q].y), __uint_as_float(tv[q].z), __uint_as_float(tv[q].w)};
              if (e4 < 256) {
                const int k = hh * 16 + (e4 >> 4), n = hh * 16 + (e4 & 15);
                const uint32_t a = sb + OFF_KVB + k * 128 + (((n >> 3) ^ (k & 7)) << 4) + (n & 7) * 2;
                asm volatile("st.shared.v2.u32 [%0], {%1,%2};" ::"r"(a), "r"(pack2(vals[0], vals[1])), "r"(pack2(vals[2], vals[3])) : "memory");
              } else {
#pragma unroll
                for (int c = 0; c < 4; c++) {
                  const int k = hh * 16 + (e4 - 256) + c;
                  const uint32_t zz = pack2(vals[c], vals[c]);
                  sts_v4(sb + OFF_KVB + 8192 + k * 128 + ((hh ^ (k & 7)) << 4), zz, zz, zz, zz);
                }
              }
            }
          }
        }
        fence_async_smem();
        __syncwarp();
        if (lane == 0) mbar_arrive(bar0 + 8 * BAR_RDY_KV);
        PROF(3);
      }
    }
  } else {
    asm volatile("setmaxnreg.inc.sync.aligned.u32 232;");
    const int wg = warp >> 2;
    const int g = lane >> 2, t = lane & 3;
    const int lr0 = warp * 16 + g;
    const int slab = rb * 8 + warp;
    unsigned dn; asm volatile("ld.relaxed.gpu.global.u32 %0, [%1];" : "=r"(dn) : "l"(&g_done) : "memory");
    const uint32_t a_lo = dlo(sb + OFF_D + wg * 8192, 16);
    const uint32_t ring_lo = (sb + OFF_RING) >> 4;

#define SLOT(gs) ((gs) % NSLOT)
#define PHASE(gs) (((gs) / NSLOT) & 1)
#define B_LO(gs, off, lbo) (ring_lo + ((SLOT(gs) * SLOT_BYTES + (off)) >> 4) + (((lbo) >> 4) << 16))
#define STAGE_BEGIN(gs) do { mbar_wait(bar0 + 8 * (BAR_FULL + SLOT(gs)), PHASE(gs)); wg_fence(); } while (0)
#define RELEASE(gs) do { if (lane == 0) mbar_arrive(bar0 + 8 * (BAR_EMPTY + SLOT(gs))); } while (0)
#define STAGE_END(prev) do { wg_commit(); wg_wait<1>(); if ((prev) >= 0) RELEASE((prev) < 0 ? 0 : (prev)); } while (0)
#define WARP_ARRIVE(b) do { __syncwarp(); if (lane == 0) mbar_arrive(bar0 + 8 * (b)); } while (0)

    uint4* act_out = g_act + (size_t)(slab * 112 + 14 * j) * 32 + lane;
    const uint32_t bias_addr = sb + OFF_B1 + 8 * t;
    float rs0, rs1;
    float pool[160];
    float (&acca)[64] = reinterpret_cast<float (&)[64]>(pool[0]);
    float (&accq)[96] = reinterpret_cast<float (&)[96]>(pool[64]);
    float (&accb)[48] = reinterpret_cast<float (&)[48]>(pool[0]);
    float (&acck)[36] = reinterpret_cast<float (&)[36]>(pool[64]);
    float (&accy)[64] = reinterpret_cast<float (&)[64]>(pool[64]);
    float (&accs)[32] = reinterpret_cast<float (&)[32]>(pool[0]);
    {
      uint4 q[16], p[16];
      const int par = g & 1;
      const uint32_t rowa = sb + OFF_D + lr0 * 128;
      const uint32_t u0 = (uint32_t)(((par * 4 + t) ^ g) << 4), u1 = u0 ^ 64u;
      named_bar_sync(0, 384);
      float sm4[4][4];
#pragma unroll
      for (int a = 0; a < 4; a++) { sm4[a][0] = sm4[a][1] = sm4[a][2] = sm4[a][3] = 0.f; }
      const uint32_t ones = 0x3F803F80u;
#pragma unroll
      for (int c = 0; c < 8; c++) {
        if ((c & 1) == 0) mbar_wait(bar0 + 8 * (BAR_X + (c >> 1)), 0);
        q[2 * c] = lds_v4(rowa + c * 16384 + u0);     p[2 * c] = lds_v4(rowa + c * 16384 + 1024 + u0);
        q[2 * c + 1] = lds_v4(rowa + c * 16384 + u1); p[2 * c + 1] = lds_v4(rowa + c * 16384 + 1024 + u1);
#pragma unroll
        for (int h = 0; h < 2; h++) {
          const int i = 2 * c + h;
          mma16816(sm4[2 * h], q[i].x, p[i].x, q[i].y, p[i].y, ones, ones);
          mma16816(sm4[2 * h + 1], q[i].z, p[i].z, q[i].w, p[i].w, ones, ones);
        }
      }
      const float m0 = (sm4[0][0] + sm4[1][0] + sm4[2][0] + sm4[3][0]) * (1.f / DM);
      const float m1 = (sm4[0][2] + sm4[1][2] + sm4[2][2] + sm4[3][2]) * (1.f / DM);
      const uint32_t mb0 = pack2(m0, m0), mb1 = pack2(m1, m1);
      PROF(12);
#pragma unroll
      for (int i = 0; i < 16; i++) {
        const uint32_t off = (uint32_t)(i >> 1) * 16384 + ((i & 1) ? u1 : u0);
        q[i].x = hsub2_bf16(q[i].x, mb0); q[i].y = hsub2_bf16(q[i].y, mb0); q[i].z = hsub2_bf16(q[i].z, mb0); q[i].w = hsub2_bf16(q[i].w, mb0);
        p[i].x = hsub2_bf16(p[i].x, mb1); p[i].y = hsub2_bf16(p[i].y, mb1); p[i].z = hsub2_bf16(p[i].z, mb1); p[i].w = hsub2_bf16(p[i].w, mb1);
        sts_v4(rowa + off, q[i].x, q[i].y, q[i].z, q[i].w);
        sts_v4(rowa + 1024 + off, p[i].x, p[i].y, p[i].z, p[i].w);
      }
      fence_async_smem();
      named_bar_sync(1 + wg, 128);
      PROF(1);
      zero_regs(acca);
      float s0a = 0.f, s0b = 0.f, s1a = 0.f, s1b = 0.f;
#pragma unroll
      for (int st = 0; st < 8; st++) {
        STAGE_BEGIN(st);
#pragma unroll
        for (int kk = 0; kk < 4; kk++) wgmma_ss_n128<1>(acca, a_lo + ((st * 16384 + kk * 32) >> 4), B_LO(st, kk * 2048, 8192));
        STAGE_END(st - 1);
#pragma unroll
        for (int c = 2 * st; c < 2 * st + 2; c++) {
          const uint32_t qv[4] = {q[c].x, q[c].y, q[c].z, q[c].w}, pv[4] = {p[c].x, p[c].y, p[c].z, p[c].w};
#pragma unroll
          for (int e = 0; e < 4; e++) {
            float f;
            f = bf_lo(qv[e]); s0a = fmaf(f, f, s0a); f = bf_hi(qv[e]); s0b = fmaf(f, f, s0b);
            f = bf_lo(pv[e]); s1a = fmaf(f, f, s1a); f = bf_hi(pv[e]); s1b = fmaf(f, f, s1b);
          }
        }
      }
      float s0 = s0a + s0b, s1 = s1a + s1b;
      s0 += __shfl_xor_sync(0xffffffffu, s0, 1); s1 += __shfl_xor_sync(0xffffffffu, s1, 1);
      s0 += __shfl_xor_sync(0xffffffffu, s0, 2); s1 += __shfl_xor_sync(0xffffffffu, s1, 2);
      const float dl0 = m0 - bf_lo(mb0), dl1 = m1 - bf_lo(mb1);
      rs0 = rsqrtf(fmaxf(s0 * (1.f / DM) - dl0 * dl0, 0.f) + 1e-5f);
      rs1 = rsqrtf(fmaxf(s1 * (1.f / DM) - dl1 * dl1, 0.f) + 1e-5f);
    }
    PROF(2);
    zero_regs(accq);
#pragma unroll
    for (int st = 0; st < 16; st++) {
      const int gs = 8 + st;
      STAGE_BEGIN(gs);
      const uint32_t as = a_lo + (((st >> 1) * 16384 + (st & 1) * 64) >> 4);
      wgmma_ss_n192<1>(accq, as, B_LO(gs, 0, 4096));
      wgmma_ss_n192<1>(accq, as + 2, B_LO(gs, 2048, 4096));
      STAGE_END(gs - 1);
      if (st == 0) {
        fence_regs(acca);
        mbar_wait(bar0 + 8 * BAR_BIAS, 0);
      }
      if (st < 8) mish_tile(acca + 8 * st, bias_addr + 64 * st, rs0, rs1, act_out + st * 32);
      if (st == 7) { WARP_ARRIVE(BAR_PUB_A); PROF(3); }
    }
    PROF(4);
    const uint4* act_in = g_act + (size_t)(slab * 112 + 56 * khalf) * 32 + lane;
    const uint4* o_in = g_o + (size_t)(slab * 32) * 32 + lane;
    uint4 ab[4][4];
    auto load_a = [&](int rs) {
      if (rs < 8) {
        const int kt = 14 * (rs >> 1) + 4 * (rs & 1);
#pragma unroll
        for (int kk = 0; kk < 4; kk++) ab[rs & 3][kk] = ldg_cg(act_in + (kt + kk) * 32);
      } else if (rs < 16) {
        const int kt = 14 * ((rs - 8) >> 1) + 8 + 3 * (rs & 1);
#pragma unroll
        for (int kk = 0; kk < 3; kk++) ab[rs & 3][kk] = ldg_cg(act_in + (kt + kk) * 32);
      } else if (rs < 24) {
#pragma unroll
        for (int kk = 0; kk < 4; kk++) ab[rs & 3][kk] = ldg_cg(o_in + (4 * (rs - 16) + kk) * 32);
      }
    };
    auto keep_a = [&](int rs) {
#pragma unroll
      for (int kk = 0; kk < 4; kk++) if (!(rs >= 8 && rs < 16 && kk == 3)) fence_u4(ab[rs & 3][kk]);
    };
    uint4 pq[4];
    const unsigned ep1 = dn / NCTA + 1u;
    {
      const int m = lane >> 3, rr = lane & 7;
      const uint32_t srow = sb + OFF_RING + (warp * 16 + (m & 1) * 8 + rr) * 128;
      const uint32_t ka = dlo(sb + OFF_RING + SLOT(29) * SLOT_BYTES + wg * 8192, 16);
      const uint32_t vb = dlo(sb + OFF_RING + SLOT(30) * SLOT_BYTES + wg * 8192, OFF_ONES - (OFF_RING + SLOT(30) * SLOT_BYTES + wg * 8192));
#pragma unroll
      for (int st = 0; st < 8; st++) {
        const int gs = st < 5 ? 24 + st : 26 + st;
        STAGE_BEGIN(gs);
#pragma unroll
        for (int kk = 0; kk < 4; kk++) {
          if (st == 0 && kk == 0) wgmma_ss_n96<0>(accb, a_lo + ((st * 16384 + kk * 32) >> 4), B_LO(gs, kk * 2048, 8192));
          else wgmma_ss_n96<1>(accb, a_lo + ((st * 16384 + kk * 32) >> 4), B_LO(gs, kk * 2048, 8192));
        }
        if (st == 5) {
          wgmma_tt_n72<0>(acck, ka, vb);
#pragma unroll
          for (int kk = 1; kk < 4; kk++) wgmma_tt_n72<1>(acck, ka + kk * 128, vb + kk * 128);
        }
        STAGE_END(st == 5 ? 28 : gs - 1);
        if (st == 0) fence_regs(accq);
        if (st < 2) {
#pragma unroll
          for (int i = 2 * st; i < 2 * st + 2; i++) {
            const int nb = 2 * i;
            pq[i].x = pack2(phi_f(accq[4 * nb] * rs0), phi_f(accq[4 * nb + 1] * rs0));
            pq[i].y = pack2(phi_f(accq[4 * nb + 2] * rs1), phi_f(accq[4 * nb + 3] * rs1));
            pq[i].z = pack2(phi_f(accq[4 * nb + 4] * rs0), phi_f(accq[4 * nb + 5] * rs0));
            pq[i].w = pack2(phi_f(accq[4 * nb + 6] * rs1), phi_f(accq[4 * nb + 7] * rs1));
          }
        } else if (st < 4) {
          if (st == 2) mbar_wait(bar0 + 8 * (BAR_FULL + SLOT(29)), PHASE(29));
#pragma unroll
          for (int i = 2 * (st - 2); i < 2 * (st - 2) + 2; i++) {
            const int nb = 8 + 2 * i;
            const uint32_t r0 = pack2(phi_f(accq[4 * nb] * rs0), phi_f(accq[4 * nb + 1] * rs0));
            const uint32_t r1 = pack2(phi_f(accq[4 * nb + 2] * rs1), phi_f(accq[4 * nb + 3] * rs1));
            const uint32_t r2 = pack2(phi_f(accq[4 * nb + 4] * rs0), phi_f(accq[4 * nb + 5] * rs0));
            const uint32_t r3 = pack2(phi_f(accq[4 * nb + 6] * rs1), phi_f(accq[4 * nb + 7] * rs1));
            stmatrix_x4(srow + SLOT(29) * SLOT_BYTES + (((2 * i + (m >> 1)) ^ rr) << 4), r0, r1, r2, r3);
          }
        } else if (st == 4) {
          mbar_wait(bar0 + 8 * (BAR_FULL + SLOT(30)), PHASE(30));
#pragma unroll
          for (int i = 0; i < 4; i++) {
            const int nb = 16 + 2 * i;
            stmatrix_x4(srow + SLOT(30) * SLOT_BYTES + (((2 * i + (m >> 1)) ^ rr) << 4),
                        pack2(accq[4 * nb] * rs0, accq[4 * nb + 1] * rs0), pack2(accq[4 * nb + 2] * rs1, accq[4 * nb + 3] * rs1),
                        pack2(accq[4 * nb + 4] * rs0, accq[4 * nb + 5] * rs0), pack2(accq[4 * nb + 6] * rs1, accq[4 * nb + 7] * rs1));
          }
          fence_async_smem();
          named_bar_sync(1 + wg, 128);
        } else if (st == 5) {
          mbar_wait(bar0 + 8 * BAR_RDY_A, 0);
          load_a(0); load_a(1);
        } else if (st == 6) {
          RELEASE(29); RELEASE(30);
          fence_regs(acck);
          const int wq = warp & 3;
          float* hb = &g_kv[(ep1 & 1) ^ 1][(4 * j + wq) * 272];
          float* a0p = hb + g * 16 + 2 * t;
#pragma unroll
          for (int w = 0; w < 4; w++) {
            if (wq == w) {
              red_add_v2(a0p, acck[8 * w], acck[8 * w + 1]); red_add_v2(a0p + 128, acck[8 * w + 2], acck[8 * w + 3]);
              red_add_v2(a0p + 8, acck[8 * w + 4], acck[8 * w + 5]); red_add_v2(a0p + 136, acck[8 * w + 6], acck[8 * w + 7]);
            }
          }
          if (t == 0) { red_add_f32(hb + 256 + g, acck[32]); red_add_f32(hb + 264 + g, acck[34]); }
          WARP_ARRIVE(BAR_PUB_KV);
          load_a(2);
        }
      }
    }
    PROF(5);
#pragma unroll
    for (int st = 0; st < 8; st++) {
      const int gs = 34 + st;
      STAGE_BEGIN(gs);
#pragma unroll
      for (int kk = 0; kk < 4; kk++) {
        if (st == 0 && kk == 0) wgmma_rs_n128<0>(accy, ab[st & 3][kk], B_LO(gs, kk * 2048, 8192));
        else wgmma_rs_n128<1>(accy, ab[st & 3][kk], B_LO(gs, kk * 2048, 8192));
      }
      STAGE_END(gs - 1);
      if (st == 0) { fence_regs(accb); WARP_ARRIVE(BAR_DFREE); }
      else keep_a(st - 1);
      if (st == 5) mbar_wait(bar0 + 8 * BAR_RDY_B, 0);
      load_a(st + 3);
      if (st < 3) {
#pragma unroll
        for (int i = 2 * st; i < 2 * st + 2; i++)
          mish_tile(accb + 8 * i, bias_addr + 512 + 64 * i, rs0, rs1, act_out + (8 + i) * 32);
        if (st == 2) WARP_ARRIVE(BAR_PUB_B);
      }
      PROF(13 + st);
    }
    PROF(6);
#pragma unroll
    for (int st = 0; st < 8; st++) {
      const int gs = 42 + st, rs = 8 + st;
      STAGE_BEGIN(gs);
#pragma unroll
      for (int kk = 0; kk < 3; kk++) wgmma_rs_n128<1>(accy, ab[rs & 3][kk], B_LO(gs, kk * 2048, 6144));
      if (st == 0) {
        mbar_wait(bar0 + 8 * BAR_RDY_KV, 0);
        PROF(7);
        const uint32_t kb = dlo(sb + OFF_KVB, 8192);
        wgmma_rs_n96<0>(accb, pq[0], kb);
#pragma unroll
        for (int kk = 1; kk < 4; kk++) wgmma_rs_n96<1>(accb, pq[kk], kb + kk * 128);
      }
      STAGE_END(gs - 1);
      keep_a(rs - 1);
      if (st == 5) mbar_wait(bar0 + 8 * BAR_RDY_O, 0);
      load_a(rs + 3);
      if (st == 1) {
        fence_regs(accb);
#pragma unroll
        for (int kk = 0; kk < 4; kk++) fence_u4(pq[kk]);
        uint4* o_out = g_o + (size_t)(slab * 32 + 4 * j) * 32 + lane;
#pragma unroll
        for (int hh = 0; hh < 4; hh++) {
          const float i0 = __fdividef(1.f, accb[32 + 4 * hh] + 1e-6f), i1 = __fdividef(1.f, accb[34 + 4 * hh] + 1e-6f);
          const float* n = accb + 8 * hh;
          stg_v4(o_out + hh * 32, pack2(n[0] * i0, n[1] * i0), pack2(n[2] * i1, n[3] * i1), pack2(n[4] * i0, n[5] * i0), pack2(n[6] * i1, n[7] * i1));
        }
        WARP_ARRIVE(BAR_PUB_O);
      }
    }
    PROF(8);
    const int c0 = 128 * nt + 64 * khalf + 2 * t;
    const size_t ro0 = (size_t)(rb * 128 + lr0) * DM + c0, ro1 = ro0 + 8 * DM;
    const uint32_t tag = ep1 & 1u;
    uint32_t xv[16];
#pragma unroll
    for (int st = 0; st < 8; st++) {
      const int gs = 50 + st, rs = 16 + st;
      STAGE_BEGIN(gs);
#pragma unroll
      for (int kk = 0; kk < 4; kk++) {
        if (st == 0 && kk == 0) wgmma_rs_n64<0>(accs, ab[rs & 3][kk], B_LO(gs, kk * 2048, 8192));
        else wgmma_rs_n64<1>(accs, ab[rs & 3][kk], B_LO(gs, kk * 2048, 8192));
      }
      STAGE_END(gs - 1);
      keep_a(rs - 1);
      if (st == 0) {
        fence_regs(accy);
        float4* yp = g_yp + (size_t)((bid * 8 + warp) * 8) * 32 + lane;
#pragma unroll
        for (int q = 0; q < 8; q++) {
          const uint32_t v0 = (__float_as_uint(accy[32 + 4 * q]) & ~1u) | tag, v1 = (__float_as_uint(accy[33 + 4 * q]) & ~1u) | tag;
          const uint32_t v2 = (__float_as_uint(accy[34 + 4 * q]) & ~1u) | tag, v3 = (__float_as_uint(accy[35 + 4 * q]) & ~1u) | tag;
          asm volatile("st.relaxed.gpu.global.v4.u32 [%0], {%1,%2,%3,%4};" ::"l"(yp + q * 32), "r"(v0), "r"(v1), "r"(v2), "r"(v3) : "memory");
        }
      }
      load_a(rs + 3);
      if (st == 1) {
#pragma unroll
        for (int q = 0; q < 8; q++) { xv[2 * q] = ldg_nc32(x + ro0 + 8 * q); xv[2 * q + 1] = ldg_nc32(x + ro1 + 8 * q); }
      }
      PROF(21 + st);
    }
    PROF(9);
    {
      const float4* yp = g_yp + (size_t)(((bid ^ 16) * 8 + warp) * 8) * 32 + lane;
      uint4 pv[8];
      uint32_t it = 0;
      wg_wait<0>();
      keep_a(23);
      fence_regs(accs);
      while (true) {
        uint32_t bad = 0;
#pragma unroll
        for (int q = 0; q < 8; q++)
          asm volatile("ld.relaxed.gpu.global.v4.u32 {%0,%1,%2,%3}, [%4];" : "=r"(pv[q].x), "=r"(pv[q].y), "=r"(pv[q].z), "=r"(pv[q].w) : "l"(yp + q * 32) : "memory");
#pragma unroll
        for (int q = 0; q < 8; q++) bad |= (pv[q].x ^ tag) | (pv[q].y ^ tag) | (pv[q].z ^ tag) | (pv[q].w ^ tag);
        if (!__any_sync(0xffffffffu, bad & 1u)) break;
        if (++it > (1u << 20)) asm volatile("trap;");
      }
      PROF(10);
#pragma unroll
      for (int q = 0; q < 8; q++) {
        const float y0 = accy[4 * q] + __uint_as_float(pv[q].x), y1 = accy[4 * q + 1] + __uint_as_float(pv[q].y);
        const float y2 = accy[4 * q + 2] + __uint_as_float(pv[q].z), y3 = accy[4 * q + 3] + __uint_as_float(pv[q].w);
        const float o0 = fmaf(accs[4 * q], silu_f(y0), bf_lo(xv[2 * q])), o1 = fmaf(accs[4 * q + 1], silu_f(y1), bf_hi(xv[2 * q]));
        const float o2 = fmaf(accs[4 * q + 2], silu_f(y2), bf_lo(xv[2 * q + 1])), o3 = fmaf(accs[4 * q + 3], silu_f(y3), bf_hi(xv[2 * q + 1]));
        *reinterpret_cast<uint32_t*>(out + ro0 + 8 * q) = pack2(o0, o1);
        *reinterpret_cast<uint32_t*>(out + ro1 + 8 * q) = pack2(o2, o3);
      }
    }
    PROF(11);
    if (tid == 0) red_inc(&g_done);
  }
}

typedef CUresult (*EncodeFn)(CUtensorMap*, CUtensorMapDataType, cuuint32_t, void*, const cuuint64_t*, const cuuint64_t*,
                             const cuuint32_t*, const cuuint32_t*, CUtensorMapInterleave, CUtensorMapSwizzle,
                             CUtensorMapL2promotion, CUtensorMapFloatOOBfill);

void make_map(EncodeFn enc, CUtensorMap* tm, const void* ptr, int rows, int cols, int box_rows) {
  cuuint64_t gd[2] = {(cuuint64_t)cols, (cuuint64_t)rows};
  cuuint64_t gs[1] = {(cuuint64_t)cols * 2};
  cuuint32_t bd[2] = {64, (cuuint32_t)box_rows};
  cuuint32_t es[2] = {1, 1};
  enc(tm, CU_TENSOR_MAP_DATA_TYPE_BFLOAT16, 2, const_cast<void*>(ptr), gd, gs, bd, es, CU_TENSOR_MAP_INTERLEAVE_NONE,
      CU_TENSOR_MAP_SWIZZLE_128B, CU_TENSOR_MAP_L2_PROMOTION_L2_128B, CU_TENSOR_MAP_FLOAT_OOB_FILL_NONE);
}

}

extern "C" void kernel_launch(void* const* d_in, const int* in_sizes, int n_in, void* d_out, int out_size) {
  const __nv_bfloat16* x = (const __nv_bfloat16*)d_in[0];
  const void* wqkv = d_in[1];
  const void* wo = d_in[2];
  const void* w1 = d_in[4];
  const __nv_bfloat16* b1 = (const __nv_bfloat16*)d_in[5];
  const void* w2 = d_in[6];
  static EncodeFn enc = nullptr;
  if (!enc) {
    cudaDriverEntryPointQueryResult qr;
    void* fn = nullptr;
    cudaGetDriverEntryPoint("cuTensorMapEncodeTiled", &fn, cudaEnableDefault, &qr);
    enc = (EncodeFn)fn;
    cudaFuncSetAttribute(fused_kernel, cudaFuncAttributeMaxDynamicSharedMemorySize, SMEM_ALLOC);
  }
  CUtensorMap tx, tq, t1, t2a, t2b, to;
  make_map(enc, &tx, x, 2048, DM, 128);
  make_map(enc, &tq, wqkv, DM, 3 * DM, 32);
  make_map(enc, &t1, w1, DM, FF, 64);
  make_map(enc, &t2a, w2, FF, DM, 64);
  make_map(enc, &t2b, w2, FF, DM, 48);
  make_map(enc, &to, wo, DM, DM, 64);
  fused_kernel<<<NCTA, 384, SMEM_ALLOC>>>(tx, tq, t1, t2a, t2b, to, x, b1, (__nv_bfloat16*)d_out);
}
```

```cpp
#include <cuda_runtime.h>
#include <cuda_bf16.h>
#include <cuda.h>
#include <stdint.h>

namespace {

constexpr int DM = 512, FF = 1792;
constexpr int NCTA = 128;
constexpr int NSLOT = 5;
constexpr int SLOT_BYTES = 16384;
constexpr int OFF_D = 0;
constexpr int OFF_KVB = 0;
constexpr int OFF_RING = 131072;
constexpr int OFF_MISC = OFF_RING + NSLOT * SLOT_BYTES;
constexpr int OFF_ONES = OFF_MISC;
constexpr int OFF_BAR = OFF_MISC + 8192;
constexpr int OFF_B1 = OFF_MISC + 8448;
constexpr int SMEM_ALLOC = OFF_MISC + 9472;

enum { BAR_FULL = 0, BAR_EMPTY = NSLOT, BAR_X = 2 * NSLOT, BAR_BIAS = BAR_X + 4,
       BAR_PUB_A, BAR_PUB_KV, BAR_PUB_B, BAR_PUB_O, BAR_DFREE,
       BAR_RDY_A, BAR_RDY_B, BAR_RDY_O, BAR_RDY_KV, BAR_COUNT };
static_assert(BAR_COUNT <= 32, "too many barriers");

constexpr int NSTAGES = 58;

__device__ uint4 g_act[128 * 112 * 32];
__device__ uint4 g_o[128 * 32 * 32];
__device__ float4 g_yp[NCTA * 8 * 8 * 32];
__device__ float g_kv[2][32 * 272];
__device__ unsigned g_cntA[16 * 2 * 8];
__device__ unsigned g_cntB[16 * 2 * 8];
__device__ unsigned g_cntO[16 * 8];
__device__ unsigned g_cntKV[8 * 8];
__device__ unsigned g_done;

#define PROF(i)

__device__ __forceinline__ uint32_t smem_u32(const void* p) { return (uint32_t)__cvta_generic_to_shared(p); }
__device__ __forceinline__ void mbar_init(uint32_t bar, uint32_t cnt) { asm volatile("mbarrier.init.shared::cta.b64 [%0], %1;" ::"r"(bar), "r"(cnt)); }
__device__ __forceinline__ void mbar_expect_tx(uint32_t bar, uint32_t bytes) { asm volatile("mbarrier.arrive.expect_tx.shared::cta.b64 _, [%0], %1;" ::"r"(bar), "r"(bytes) : "memory"); }
__device__ __forceinline__ void mbar_arrive(uint32_t bar) { asm volatile("mbarrier.arrive.shared::cta.b64 _, [%0];" ::"r"(bar) : "memory"); }
__device__ __forceinline__ void mbar_wait(uint32_t bar, uint32_t parity) {
  asm volatile("{\n.reg .pred P1;\n.reg .u32 cnt;\n"
               "mbarrier.try_wait.parity.shared::cta.b64 P1, [%0], %1;\n@P1 bra DONE;\n"
               "mov.u32 cnt, 0;\n"
               "LAB_WAIT:\n"
               "mbarrier.try_wait.parity.shared::cta.b64 P1, [%0], %1;\n@P1 bra DONE;\n"
               "add.u32 cnt, cnt, 1;\nsetp.lt.u32 P1, cnt, 16777216;\n@P1 bra LAB_WAIT;\ntrap;\n"
               "DONE:\n}" ::"r"(bar), "r"(parity) : "memory");
}
__device__ __forceinline__ void tma2d(uint32_t dst, const CUtensorMap* tm, int c0, int c1, uint32_t bar) {
  asm volatile("cp.async.bulk.tensor.2d.shared::cluster.global.mbarrier::complete_tx::bytes [%0], [%1, {%3, %4}], [%2];" ::"r"(dst), "l"(tm), "r"(bar), "r"(c0), "r"(c1) : "memory");
}
__device__ __forceinline__ void wg_fence() { asm volatile("wgmma.fence.sync.aligned;" ::: "memory"); }
__device__ __forceinline__ void wg_commit() { asm volatile("wgmma.commit_group.sync.aligned;" ::: "memory"); }
template <int N> __device__ __forceinline__ void wg_wait() { asm volatile("wgmma.wait_group.sync.aligned %0;" ::"n"(N) : "memory"); }
template <int N> __device__ __forceinline__ void zero_regs(float (&d)[N]) {
#pragma unroll
  for (int i = 0; i < N; i++) d[i] = 0.f;
}
template <int N> __device__ __forceinline__ void fence_regs(float (&d)[N]) {
#pragma unroll
  for (int i = 0; i < N; i++) asm volatile("" : "+f"(d[i])::"memory");
}
__device__ __forceinline__ void fence_u4(uint4& v) { asm volatile("" : "+r"(v.x), "+r"(v.y), "+r"(v.z), "+r"(v.w)::"memory"); }
__device__ __forceinline__ void named_bar_sync(int id, int n) { asm volatile("bar.sync %0, %1;" ::"r"(id), "r"(n) : "memory"); }
__device__ __forceinline__ void fence_async_smem() { asm volatile("fence.proxy.async.shared::cta;" ::: "memory"); }
__device__ __forceinline__ constexpr uint32_t dlo(uint32_t addr, uint32_t lbo_bytes) { return ((addr & 0x3FFFFu) >> 4) | ((lbo_bytes >> 4) << 16); }
__device__ __forceinline__ void mma16816(float (&c)[4], uint32_t a0, uint32_t a1, uint32_t a2, uint32_t a3, uint32_t b0, uint32_t b1) {
  asm volatile("mma.sync.aligned.m16n8k16.row.col.f32.bf16.bf16.f32 {%0,%1,%2,%3}, {%4,%5,%6,%7}, {%8,%9}, {%0,%1,%2,%3};"
               : "+f"(c[0]), "+f"(c[1]), "+f"(c[2]), "+f"(c[3]) : "r"(a0), "r"(a1), "r"(a2), "r"(a3), "r"(b0), "r"(b1));
}
__device__ __forceinline__ void stmatrix_x4(uint32_t addr, uint32_t a, uint32_t b, uint32_t c, uint32_t d) {
  asm volatile("stmatrix.sync.aligned.m8n8.x4.shared.b16 [%0], {%1,%2,%3,%4};" ::"r"(addr), "r"(a), "r"(b), "r"(c), "r"(d) : "memory");
}
__device__ __forceinline__ uint32_t pack2(float lo, float hi) { uint32_t r; asm("cvt.rn.bf16x2.f32 %0, %1, %2;" : "=r"(r) : "f"(hi), "f"(lo)); return r; }
__device__ __forceinline__ float ex2(float x) { float r; asm("ex2.approx.ftz.f32 %0, %1;" : "=f"(r) : "f"(x)); return r; }
__device__ __forceinline__ float rcp(float x) { float r; asm("rcp.approx.ftz.f32 %0, %1;" : "=f"(r) : "f"(x)); return r; }
__device__ __forceinline__ float bf_lo(uint32_t v) { return __uint_as_float(v << 16); }
__device__ __forceinline__ float bf_hi(uint32_t v) { return __uint_as_float(v & 0xffff0000u); }
__device__ __forceinline__ uint32_t hsub2_bf16(uint32_t a, uint32_t b) {
  __nv_bfloat162 x = *reinterpret_cast<__nv_bfloat162*>(&a), y = *reinterpret_cast<__nv_bfloat162*>(&b);
  __nv_bfloat162 r = __hsub2(x, y);
  return *reinterpret_cast<uint32_t*>(&r);
}
__device__ __forceinline__ uint32_t ldg_nc32(const void* p) {
  uint32_t v; asm volatile("ld.global.nc.u32 %0, [%1];" : "=r"(v) : "l"(p)); return v;
}
__device__ __forceinline__ uint4 ldg_cg(const void* p) {
  uint4 v; asm volatile("ld.global.cg.v4.u32 {%0,%1,%2,%3}, [%4];" : "=r"(v.x), "=r"(v.y), "=r"(v.z), "=r"(v.w) : "l"(p) : "memory"); return v;
}
__device__ __forceinline__ void stg_v4(void* p, uint32_t a, uint32_t b, uint32_t c, uint32_t d) {
  asm volatile("st.global.v4.u32 [%0], {%1,%2,%3,%4};" ::"l"(p), "r"(a), "r"(b), "r"(c), "r"(d) : "memory");
}
__device__ __forceinline__ void sts_v4(uint32_t addr, uint32_t a, uint32_t b, uint32_t c, uint32_t d) {
  asm volatile("st.shared.v4.u32 [%0], {%1,%2,%3,%4};" ::"r"(addr), "r"(a), "r"(b), "r"(c), "r"(d) : "memory");
}
__device__ __forceinline__ void sts_f32(uint32_t addr, float v) { asm volatile("st.shared.f32 [%0], %1;" ::"r"(addr), "f"(v) : "memory"); }
__device__ __forceinline__ uint4 lds_v4(uint32_t addr) { uint4 v; asm volatile("ld.shared.v4.u32 {%0,%1,%2,%3}, [%4];" : "=r"(v.x), "=r"(v.y), "=r"(v.z), "=r"(v.w) : "r"(addr) : "memory"); return v; }
__device__ __forceinline__ float2 lds_f32x2(uint32_t addr) { float2 v; asm volatile("ld.shared.v2.f32 {%0,%1}, [%2];" : "=f"(v.x), "=f"(v.y) : "r"(addr) : "memory"); return v; }
__device__ __forceinline__ void red_add_v2(float* p, float a, float b) { asm volatile("red.relaxed.gpu.global.add.v2.f32 [%0], {%1,%2};" ::"l"(p), "f"(a), "f"(b) : "memory"); }
__device__ __forceinline__ void red_add_f32(float* p, float a) { asm volatile("red.relaxed.gpu.global.add.f32 [%0], %1;" ::"l"(p), "f"(a) : "memory"); }
__device__ __forceinline__ void red_inc(unsigned* cnt) { asm volatile("red.relaxed.gpu.global.add.u32 [%0], 1;" ::"l"(cnt) : "memory"); }
__device__ __forceinline__ void poll_ge(const unsigned* cnt, unsigned target) {
  asm volatile("{\n.reg .pred P1;\n.reg .u32 cnt, v;\n.reg .s32 d;\n"
               "mov.u32 cnt, 0;\n"
               "LAB_POLL:\n"
               "ld.acquire.gpu.global.u32 v, [%0];\nsub.s32 d, v, %1;\nsetp.ge.s32 P1, d, 0;\n@P1 bra DONE;\n"
               "add.u32 cnt, cnt, 1;\nsetp.lt.u32 P1, cnt, 4194304;\n@P1 bra LAB_POLL;\ntrap;\n"
               "DONE:\n}" ::"l"(cnt), "r"(target) : "memory");
}

template <int SCALE_D> __device__ __forceinline__ void wgmma_ss_n192(float (&d)[96], uint32_t da, uint32_t db) {
  asm volatile("{\n.reg .b64 da, db;\nmov.b64 da, {%96, %98};\nmov.b64 db, {%97, %98};\n"
    "wgmma.mma_async.sync.aligned.m64n192k16.f32.bf16.bf16 {%0, %1, %2, %3, %4, %5, %6, %7, %8, %9, %10, %11, %12, %13, %14, %15, %16, %17, %18, %19, %20, %21, %22, %23, %24, %25, %26, %27, %28, %29, %30, %31, %32, %33, %34, %35, %36, %37, %38, %39, %40, %41, %42, %43, %44, %45, %46, %47, %48, %49, %50, %51, %52, %53, %54, %55, %56, %57, %58, %59, %60, %61, %62, %63, %64, %65, %66, %67, %68, %69, %70, %71, %72, %73, %74, %75, %76, %77, %78, %79, %80, %81, %82, %83, %84, %85, %86, %87, %88, %89, %90, %91, %92, %93, %94, %95}, da, db, %99, 1, 1, 0, 1;\n}\n"
    : "+f"(d[0]), "+f"(d[1]), "+f"(d[2]), "+f"(d[3]), "+f"(d[4]), "+f"(d[5]), "+f"(d[6]), "+f"(d[7]), "+f"(d[8]), "+f"(d[9]), "+f"(d[10]), "+f"(d[11]), "+f"(d[12]), "+f"(d[13]), "+f"(d[14]), "+f"(d[15]), "+f"(d[16]), "+f"(d[17]), "+f"(d[18]), "+f"(d[19]), "+f"(d[20]), "+f"(d[21]), "+f"(d[22]), "+f"(d[23]), "+f"(d[24]), "+f"(d[25]), "+f"(d[26]), "+f"(d[27]), "+f"(d[28]), "+f"(d[29]), "+f"(d[30]), "+f"(d[31]), "+f"(d[32]), "+f"(d[33]), "+f"(d[34]), "+f"(d[35]), "+f"(d[36]), "+f"(d[37]), "+f"(d[38]), "+f"(d[39]), "+f"(d[40]), "+f"(d[41]), "+f"(d[42]), "+f"(d[43]), "+f"(d[44]), "+f"(d[45]), "+f"(d[46]), "+f"(d[47]), "+f"(d[48]), "+f"(d[49]), "+f"(d[50]), "+f"(d[51]), "+f"(d[52]), "+f"(d[53]), "+f"(d[54]), "+f"(d[55]), "+f"(d[56]), "+f"(d[57]), "+f"(d[58]), "+f"(d[59]), "+f"(d[60]), "+f"(d[61]), "+f"(d[62]), "+f"(d[63]), "+f"(d[64]), "+f"(d[65]), "+f"(d[66]), "+f"(d[67]), "+f"(d[68]), "+f"(d[69]), "+f"(d[70]), "+f"(d[71]), "+f"(d[72]), "+f"(d[73]), "+f"(d[74]), "+f"(d[75]), "+f"(d[76]), "+f"(d[77]), "+f"(d[78]), "+f"(d[79]), "+f"(d[80]), "+f"(d[81]), "+f"(d[82]), "+f"(d[83]), "+f"(d[84]), "+f"(d[85]), "+f"(d[86]), "+f"(d[87]), "+f"(d[88]), "+f"(d[89]), "+f"(d[90]), "+f"(d[91]), "+f"(d[92]), "+f"(d[93]), "+f"(d[94]), "+f"(d[95])
    : "r"(da), "r"(db), "r"(0x40000040u), "n"(SCALE_D));
}
template <int SCALE_D> __device__ __forceinline__ void wgmma_ss_n128(float (&d)[64], uint32_t da, uint32_t db) {
  asm volatile("{\n.reg .b64 da, db;\nmov.b64 da, {%64, %66};\nmov.b64 db, {%65, %66};\n"
    "wgmma.mma_async.sync.aligned.m64n128k16.f32.bf16.bf16 {%0, %1, %2, %3, %4, %5, %6, %7, %8, %9, %10, %11, %12, %13, %14, %15, %16, %17, %18, %19, %20, %21, %22, %23, %24, %25, %26, %27, %28, %29, %30, %31, %32, %33, %34, %35, %36, %37, %38, %39, %40, %41, %42, %43, %44, %45, %46, %47, %48, %49, %50, %51, %52, %53, %54, %55, %56, %57, %58, %59, %60, %61, %62, %63}, da, db, %67, 1, 1, 0, 1;\n}\n"
    : "+f"(d[0]), "+f"(d[1]), "+f"(d[2]), "+f"(d[3]), "+f"(d[4]), "+f"(d[5]), "+f"(d[6]), "+f"(d[7]), "+f"(d[8]), "+f"(d[9]), "+f"(d[10]), "+f"(d[11]), "+f"(d[12]), "+f"(d[13]), "+f"(d[14]), "+f"(d[15]), "+f"(d[16]), "+f"(d[17]), "+f"(d[18]), "+f"(d[19]), "+f"(d[20]), "+f"(d[21]), "+f"(d[22]), "+f"(d[23]), "+f"(d[24]), "+f"(d[25]), "+f"(d[26]), "+f"(d[27]), "+f"(d[28]), "+f"(d[29]), "+f"(d[30]), "+f"(d[31]), "+f"(d[32]), "+f"(d[33]), "+f"(d[34]), "+f"(d[35]), "+f"(d[36]), "+f"(d[37]), "+f"(d[38]), "+f"(d[39]), "+f"(d[40]), "+f"(d[41]), "+f"(d[42]), "+f"(d[43]), "+f"(d[44]), "+f"(d[45]), "+f"(d[46]), "+f"(d[47]), "+f"(d[48]), "+f"(d[49]), "+f"(d[50]), "+f"(d[51]), "+f"(d[52]), "+f"(d[53]), "+f"(d[54]), "+f"(d[55]), "+f"(d[56]), "+f"(d[57]), "+f"(d[58]), "+f"(d[59]), "+f"(d[60]), "+f"(d[61]), "+f"(d[62]), "+f"(d[63])
    : "r"(da), "r"(db), "r"(0x40000040u), "n"(SCALE_D));
}
template <int SCALE_D> __device__ __forceinline__ void wgmma_ss_n96(float (&d)[48], uint32_t da, uint32_t db) {
  asm volatile("{\n.reg .b64 da, db;\nmov.b64 da, {%48, %50};\nmov.b64 db, {%49, %50};\n"
    "wgmma.mma_async.sync.aligned.m64n96k16.f32.bf16.bf16 {%0, %1, %2, %3, %4, %5, %6, %7, %8, %9, %10, %11, %12, %13, %14, %15, %16, %17, %18, %19, %20, %21, %22, %23, %24, %25, %26, %27, %28, %29, %30, %31, %32, %33, %34, %35, %36, %37, %38, %39, %40, %41, %42, %43, %44, %45, %46, %47}, da, db, %51, 1, 1, 0, 1;\n}\n"
    : "+f"(d[0]), "+f"(d[1]), "+f"(d[2]), "+f"(d[3]), "+f"(d[4]), "+f"(d[5]), "+f"(d[6]), "+f"(d[7]), "+f"(d[8]), "+f"(d[9]), "+f"(d[10]), "+f"(d[11]), "+f"(d[12]), "+f"(d[13]), "+f"(d[14]), "+f"(d[15]), "+f"(d[16]), "+f"(d[17]), "+f"(d[18]), "+f"(d[19]), "+f"(d[20]), "+f"(d[21]), "+f"(d[22]), "+f"(d[23]), "+f"(d[24]), "+f"(d[25]), "+f"(d[26]), "+f"(d[27]), "+f"(d[28]), "+f"(d[29]), "+f"(d[30]), "+f"(d[31]), "+f"(d[32]), "+f"(d[33]), "+f"(d[34]), "+f"(d[35]), "+f"(d[36]), "+f"(d[37]), "+f"(d[38]), "+f"(d[39]), "+f"(d[40]), "+f"(d[41]), "+f"(d[42]), "+f"(d[43]), "+f"(d[44]), "+f"(d[45]), "+f"(d[46]), "+f"(d[47])
    : "r"(da), "r"(db), "r"(0x40000040u), "n"(SCALE_D));
}
template <int SCALE_D> __device__ __forceinline__ void wgmma_tt_n72(float (&d)[36], uint32_t da, uint32_t db) {
  asm volatile("{\n.reg .b64 da, db;\nmov.b64 da, {%36, %38};\nmov.b64 db, {%37, %38};\n"
    "wgmma.mma_async.sync.aligned.m64n72k16.f32.bf16.bf16 {%0, %1, %2, %3, %4, %5, %6, %7, %8, %9, %10, %11, %12, %13, %14, %15, %16, %17, %18, %19, %20, %21, %22, %23, %24, %25, %26, %27, %28, %29, %30, %31, %32, %33, %34, %35}, da, db, %39, 1, 1, 1, 1;\n}\n"
    : "+f"(d[0]), "+f"(d[1]), "+f"(d[2]), "+f"(d[3]), "+f"(d[4]), "+f"(d[5]), "+f"(d[6]), "+f"(d[7]), "+f"(d[8]), "+f"(d[9]), "+f"(d[10]), "+f"(d[11]), "+f"(d[12]), "+f"(d[13]), "+f"(d[14]), "+f"(d[15]), "+f"(d[16]), "+f"(d[17]), "+f"(d[18]), "+f"(d[19]), "+f"(d[20]), "+f"(d[21]), "+f"(d[22]), "+f"(d[23]), "+f"(d[24]), "+f"(d[25]), "+f"(d[26]), "+f"(d[27]), "+f"(d[28]), "+f"(d[29]), "+f"(d[30]), "+f"(d[31]), "+f"(d[32]), "+f"(d[33]), "+f"(d[34]), "+f"(d[35])
    : "r"(da), "r"(db), "r"(0x40000040u), "n"(SCALE_D));
}
template <int SCALE_D> __device__ __forceinline__ void wgmma_rs_n128(float (&d)[64], const uint4& a, uint32_t db) {
  asm volatile("{\n.reg .b64 db;\nmov.b64 db, {%68, %69};\n"
    "wgmma.mma_async.sync.aligned.m64n128k16.f32.bf16.bf16 {%0, %1, %2, %3, %4, %5, %6, %7, %8, %9, %10, %11, %12, %13, %14, %15, %16, %17, %18, %19, %20, %21, %22, %23, %24, %25, %26, %27, %28, %29, %30, %31, %32, %33, %34, %35, %36, %37, %38, %39, %40, %41, %42, %43, %44, %45, %46, %47, %48, %49, %50, %51, %52, %53, %54, %55, %56, %57, %58, %59, %60, %61, %62, %63}, {%64, %65, %66, %67}, db, %70, 1, 1, 1;\n}\n"
    : "+f"(d[0]), "+f"(d[1]), "+f"(d[2]), "+f"(d[3]), "+f"(d[4]), "+f"(d[5]), "+f"(d[6]), "+f"(d[7]), "+f"(d[8]), "+f"(d[9]), "+f"(d[10]), "+f"(d[11]), "+f"(d[12]), "+f"(d[13]), "+f"(d[14]), "+f"(d[15]), "+f"(d[16]), "+f"(d[17]), "+f"(d[18]), "+f"(d[19]), "+f"(d[20]), "+f"(d[21]), "+f"(d[22]), "+f"(d[23]), "+f"(d[24]), "+f"(d[25]), "+f"(d[26]), "+f"(d[27]), "+f"(d[28]), "+f"(d[29]), "+f"(d[30]), "+f"(d[31]), "+f"(d[32]), "+f"(d[33]), "+f"(d[34]), "+f"(d[35]), "+f"(d[36]), "+f"(d[37]), "+f"(d[38]), "+f"(d[39]), "+f"(d[40]), "+f"(d[41]), "+f"(d[42]), "+f"(d[43]), "+f"(d[44]), "+f"(d[45]), "+f"(d[46]), "+f"(d[47]), "+f"(d[48]), "+f"(d[49]), "+f"(d[50]), "+f"(d[51]), "+f"(d[52]), "+f"(d[53]), "+f"(d[54]), "+f"(d[55]), "+f"(d[56]), "+f"(d[57]), "+f"(d[58]), "+f"(d[59]), "+f"(d[60]), "+f"(d[61]), "+f"(d[62]), "+f"(d[63])
    : "r"(a.x), "r"(a.y), "r"(a.z), "r"(a.w), "r"(db), "r"(0x40000040u), "n"(SCALE_D));
}
template <int SCALE_D> __device__ __forceinline__ void wgmma_rs_n96(float (&d)[48], const uint4& a, uint32_t db) {
  asm volatile("{\n.reg .b64 db;\nmov.b64 db, {%52, %53};\n"
    "wgmma.mma_async.sync.aligned.m64n96k16.f32.bf16.bf16 {%0, %1, %2, %3, %4, %5, %6, %7, %8, %9, %10, %11, %12, %13, %14, %15, %16, %17, %18, %19, %20, %21, %22, %23, %24, %25, %26, %27, %28, %29, %30, %31, %32, %33, %34, %35, %36, %37, %38, %39, %40, %41, %42, %43, %44, %45, %46, %47}, {%48, %49, %50, %51}, db, %54, 1, 1, 1;\n}\n"
    : "+f"(d[0]), "+f"(d[1]), "+f"(d[2]), "+f"(d[3]), "+f"(d[4]), "+f"(d[5]), "+f"(d[6]), "+f"(d[7]), "+f"(d[8]), "+f"(d[9]), "+f"(d[10]), "+f"(d[11]), "+f"(d[12]), "+f"(d[13]), "+f"(d[14]), "+f"(d[15]), "+f"(d[16]), "+f"(d[17]), "+f"(d[18]), "+f"(d[19]), "+f"(d[20]), "+f"(d[21]), "+f"(d[22]), "+f"(d[23]), "+f"(d[24]), "+f"(d[25]), "+f"(d[26]), "+f"(d[27]), "+f"(d[28]), "+f"(d[29]), "+f"(d[30]), "+f"(d[31]), "+f"(d[32]), "+f"(d[33]), "+f"(d[34]), "+f"(d[35]), "+f"(d[36]), "+f"(d[37]), "+f"(d[38]), "+f"(d[39]), "+f"(d[40]), "+f"(d[41]), "+f"(d[42]), "+f"(d[43]), "+f"(d[44]), "+f"(d[45]), "+f"(d[46]), "+f"(d[47])
    : "r"(a.x), "r"(a.y), "r"(a.z), "r"(a.w), "r"(db), "r"(0x40000040u), "n"(SCALE_D));
}
template <int SCALE_D> __device__ __forceinline__ void wgmma_rs_n64(float (&d)[32], const uint4& a, uint32_t db) {
  asm volatile("{\n.reg .b64 db;\nmov.b64 db, {%36, %37};\n"
    "wgmma.mma_async.sync.aligned.m64n64k16.f32.bf16.bf16 {%0, %1, %2, %3, %4, %5, %6, %7, %8, %9, %10, %11, %12, %13, %14, %15, %16, %17, %18, %19, %20, %21, %22, %23, %24, %25, %26, %27, %28, %29, %30, %31}, {%32, %33, %34, %35}, db, %38, 1, 1, 1;\n}\n"
    : "+f"(d[0]), "+f"(d[1]), "+f"(d[2]), "+f"(d[3]), "+f"(d[4]), "+f"(d[5]), "+f"(d[6]), "+f"(d[7]), "+f"(d[8]), "+f"(d[9]), "+f"(d[10]), "+f"(d[11]), "+f"(d[12]), "+f"(d[13]), "+f"(d[14]), "+f"(d[15]), "+f"(d[16]), "+f"(d[17]), "+f"(d[18]), "+f"(d[19]), "+f"(d[20]), "+f"(d[21]), "+f"(d[22]), "+f"(d[23]), "+f"(d[24]), "+f"(d[25]), "+f"(d[26]), "+f"(d[27]), "+f"(d[28]), "+f"(d[29]), "+f"(d[30]), "+f"(d[31])
    : "r"(a.x), "r"(a.y), "r"(a.z), "r"(a.w), "r"(db), "r"(0x40000040u), "n"(SCALE_D));
}

constexpr float LOG2E = 1.4426950408889634f;
__device__ __forceinline__ float silu_f(float y) { return y * rcp(1.f + ex2(-y * LOG2E)); }

__device__ __forceinline__ void mish_tile(const float* c, float rs0, float rs1, float rl0, float rl1, uint4* dst) {
  float h[8], u[8], r[8];
#pragma unroll
  for (int i = 0; i < 8; i++) {
    const bool hi = (i >> 1) & 1;
    h[i] = c[i] * (hi ? rs1 : rs0);
    u[i] = ex2(fminf(c[i] * (hi ? rl1 : rl0), 28.853900817779268f));
  }
#pragma unroll
  for (int i = 0; i < 8; i++) { const float tt = u[i] + 2.f; r[i] = rcp(fmaf(u[i], tt, 2.f)); h[i] *= u[i] * tt; }
#pragma unroll
  for (int i = 0; i < 8; i++) h[i] *= r[i];
  stg_v4(dst, pack2(h[0], h[1]), pack2(h[2], h[3]), pack2(h[4], h[5]), pack2(h[6], h[7]));
}
__device__ __forceinline__ float phi_c(float c, float rs, float rl) {
  const float e = ex2(c * rl) + 1e-6f;
  const float p = fmaf(c, rs, 1.000001f);
  return c > 0.f ? p : e;
}
__device__ __forceinline__ uint4 phi_tile(const float* c, float rs0, float rs1, float rl0, float rl1) {
  uint4 r;
  r.x = pack2(phi_c(c[0], rs0, rl0), phi_c(c[1], rs0, rl0)); r.y = pack2(phi_c(c[2], rs1, rl1), phi_c(c[3], rs1, rl1));
  r.z = pack2(phi_c(c[4], rs0, rl0), phi_c(c[5], rs0, rl0)); r.w = pack2(phi_c(c[6], rs1, rl1), phi_c(c[7], rs1, rl1));
  return r;
}
template <int NB> __device__ __forceinline__ void init_bias(float* acc, uint32_t bias_addr, float ir0, float ir1) {
#pragma unroll
  for (int nb = 0; nb < NB; nb++) {
    const float2 b = lds_f32x2(bias_addr + 32 * nb);
    acc[4 * nb] = b.x * ir0; acc[4 * nb + 1] = b.y * ir0; acc[4 * nb + 2] = b.x * ir1; acc[4 * nb + 3] = b.y * ir1;
  }
}

__global__ void __launch_bounds__(384, 1)
fused_kernel(const __grid_constant__ CUtensorMap tm_x, const __grid_constant__ CUtensorMap tm_qkv,
             const __grid_constant__ CUtensorMap tm_w1, const __grid_constant__ CUtensorMap tm_w2a,
             const __grid_constant__ CUtensorMap tm_w2b, const __grid_constant__ CUtensorMap tm_wo,
             const __nv_bfloat16* __restrict__ x, const __nv_bfloat16* __restrict__ b1, __nv_bfloat16* __restrict__ out) {
  extern __shared__ __align__(1024) uint8_t smem_raw[];
  const uint32_t sb = smem_u32(smem_raw);
  const int tid = threadIdx.x, lane = tid & 31;
  const int warp = __shfl_sync(0xffffffffu, tid >> 5, 0);
  const int bid = blockIdx.x;
  const int G = bid >> 4, gi = bid & 15;
  const int khalf = G & 1;
  const int rb = (G >> 1) * 4 + (gi >> 2);
  const int nt = gi & 3;
  const int j = khalf + 2 * nt;
  const uint32_t bar0 = sb + OFF_BAR;
  PROF(0);

  if (warp >= 8) {
    asm volatile("setmaxnreg.dec.sync.aligned.u32 40;");
    if (warp == 8) {
      if (lane == 0) {
        if (sb & 1023u) asm volatile("trap;");
        for (int i = 0; i < NSLOT; i++) { mbar_init(bar0 + 8 * (BAR_FULL + i), 1); mbar_init(bar0 + 8 * (BAR_EMPTY + i), 8); }
        for (int i = 0; i < 4; i++) mbar_init(bar0 + 8 * (BAR_X + i), 1);
        mbar_init(bar0 + 8 * BAR_BIAS, 1);
        for (int i = BAR_PUB_A; i <= BAR_DFREE; i++) mbar_init(bar0 + 8 * i, 8);
        for (int i = BAR_RDY_A; i <= BAR_RDY_KV; i++) mbar_init(bar0 + 8 * i, 1);
        asm volatile("fence.mbarrier_init.release.cluster;" ::: "memory");
        fence_async_smem();
        for (int i = 0; i < 4; i++) {
          mbar_expect_tx(bar0 + 8 * (BAR_X + i), 32768);
          tma2d(sb + OFF_D + (2 * i) * 16384, &tm_x, 128 * i, rb * 128, bar0 + 8 * (BAR_X + i));
          tma2d(sb + OFF_D + (2 * i + 1) * 16384, &tm_x, 128 * i + 64, rb * 128, bar0 + 8 * (BAR_X + i));
        }
      }
      __syncwarp();
      named_bar_sync(0, 384);
      if (lane == 0) {
        const int c_own = 128 * nt + 64 * khalf, c_par = 128 * nt + 64 * (1 - khalf);
        int slot = 0; uint32_t phase = 1;
        for (int st = 0; st < NSTAGES; st++) {
          const uint32_t full = bar0 + 8 * (BAR_FULL + slot);
          const uint32_t dst = sb + OFF_RING + slot * SLOT_BYTES;
          mbar_wait(bar0 + 8 * (BAR_EMPTY + slot), phase);
          if (st < 8) {
            mbar_expect_tx(full, 16384);
            const int k0 = 64 * st, c0 = 224 * j;
            tma2d(dst, &tm_w1, c0, k0, full);
            tma2d(dst + 8192, &tm_w1, c0 + 64, k0, full);
          } else if (st < 24) {
            mbar_expect_tx(full, 12288);
            const int k0 = 32 * (st - 8);
            tma2d(dst, &tm_qkv, 512 + 64 * j, k0, full);
            tma2d(dst + 4096, &tm_qkv, 1024 + 64 * j, k0, full);
            tma2d(dst + 8192, &tm_qkv, 64 * j, k0, full);
          } else if (st == 25 || st == 26) {
            mbar_arrive(full);
          } else if (st < 34) {
            mbar_expect_tx(full, 16384);
            const int k0 = st == 24 ? 0 : 64 * (st - 26), c0 = 224 * j + 128;
            tma2d(dst, &tm_w1, c0, k0, full);
            tma2d(dst + 8192, &tm_w1, c0 + 64, k0, full);
          } else if (st < 42) {
            mbar_expect_tx(full, 16384);
            const int i = st - 34;
            const int k0 = 224 * (4 * khalf + (i >> 1)) + 64 * (i & 1);
            tma2d(dst, &tm_w2a, c_own, k0, full);
            tma2d(dst + 8192, &tm_w2a, c_par, k0, full);
          } else if (st < 50) {
            mbar_expect_tx(full, 12288);
            const int i = st - 42;
            const int k0 = 224 * (4 * khalf + (i >> 1)) + 128 + 48 * (i & 1);
            tma2d(dst, &tm_w2b, c_own, k0, full);
            tma2d(dst + 6144, &tm_w2b, c_par, k0, full);
          } else {
            mbar_expect_tx(full, 8192);
            tma2d(dst, &tm_wo, c_own, 64 * (st - 50), full);
          }
          if (++slot == NSLOT) { slot = 0; phase ^= 1; }
        }
      }
    } else {
      const int aw = warp - 9;
      unsigned dn; asm volatile("ld.relaxed.gpu.global.u32 %0, [%1];" : "=r"(dn) : "l"(&g_done) : "memory");
      named_bar_sync(0, 384);
      const unsigned ep1 = dn / NCTA + 1u;
      if (aw == 0) {
        for (int i = lane; i < 224; i += 32) sts_f32(sb + OFF_B1 + 4 * i, __bfloat162float(b1[224 * j + i]));
#pragma unroll 4
        for (int i = 0; i < 16; i++) sts_v4(sb + OFF_ONES + (i * 32 + lane) * 16, 0x3F803F80u, 0x3F803F80u, 0x3F803F80u, 0x3F803F80u);
        fence_async_smem();
        __syncwarp();
        if (lane == 0) {
          mbar_arrive(bar0 + 8 * BAR_BIAS);
          mbar_wait(bar0 + 8 * BAR_PUB_A, 0);  __threadfence(); red_inc(&g_cntA[(rb * 2 + (j >> 2)) * 8]);
          mbar_wait(bar0 + 8 * BAR_PUB_KV, 0); __threadfence(); red_inc(&g_cntKV[j * 8]);
          mbar_wait(bar0 + 8 * BAR_PUB_B, 0);  __threadfence(); red_inc(&g_cntB[(rb * 2 + (j >> 2)) * 8]);
          mbar_wait(bar0 + 8 * BAR_PUB_O, 0);  __threadfence(); red_inc(&g_cntO[rb * 8]);
        }
      } else if (aw == 1) {
        if (lane == 0) {
          poll_ge(&g_cntA[(rb * 2 + khalf) * 8], 4u * ep1); mbar_arrive(bar0 + 8 * BAR_RDY_A);
          PROF(1);
          poll_ge(&g_cntB[(rb * 2 + khalf) * 8], 4u * ep1); mbar_arrive(bar0 + 8 * BAR_RDY_B);
          PROF(2);
          poll_ge(&g_cntO[rb * 8], 8u * ep1);               mbar_arrive(bar0 + 8 * BAR_RDY_O);
          PROF(3);
        }
      } else {
        if (rb == 0) {
          float4* z = reinterpret_cast<float4*>(&g_kv[ep1 & 1][4 * j * 272]);
          for (int i = lane; i < 272; i += 32) z[i] = make_float4(0.f, 0.f, 0.f, 0.f);
        }
        const float* kvbuf = &g_kv[(ep1 & 1) ^ 1][4 * j * 272];
        mbar_wait(bar0 + 8 * BAR_DFREE, 0);
#pragma unroll 4
        for (int i = 0; i < 32; i++) sts_v4(sb + OFF_KVB + (i * 32 + lane) * 16, 0u, 0u, 0u, 0u);
        PROF(1);
        if (lane == 0) poll_ge(&g_cntKV[j * 8], 16u * ep1);
        __syncwarp();
        PROF(2);
        {
          const int d = lane >> 1, hf = lane & 1;
          const float* src = kvbuf + d * 16 + hf * 8;
          const uint32_t dst = sb + OFF_KVB + d * 128;
#pragma unroll
          for (int hp = 0; hp < 2; hp++) {
            uint4 v[2][2]; float zz[2];
#pragma unroll
            for (int q = 0; q < 2; q++) {
              const int hh = 2 * hp + q;
              v[q][0] = ldg_cg(src + hh * 272); v[q][1] = ldg_cg(src + hh * 272 + 4);
              asm volatile("ld.global.cg.f32 %0, [%1];" : "=f"(zz[q]) : "l"(kvbuf + hh * 272 + 256 + d) : "memory");
            }
#pragma unroll
            for (int q = 0; q < 2; q++) {
              const int hh = 2 * hp + q;
              sts_v4(dst + hh * 2048 + (((2 * hh + hf) ^ (d & 7)) << 4),
                     pack2(__uint_as_float(v[q][0].x), __uint_as_float(v[q][0].y)), pack2(__uint_as_float(v[q][0].z), __uint_as_float(v[q][0].w)),
                     pack2(__uint_as_float(v[q][1].x), __uint_as_float(v[q][1].y)), pack2(__uint_as_float(v[q][1].z), __uint_as_float(v[q][1].w)));
              const uint32_t z2 = pack2(zz[q], zz[q]);
              if (hf == 0) sts_v4(dst + 8192 + hh * 2048 + ((hh ^ (d & 7)) << 4), z2, z2, z2, z2);
            }
          }
        }
        fence_async_smem();
        __syncwarp();
        if (lane == 0) mbar_arrive(bar0 + 8 * BAR_RDY_KV);
        PROF(3);
      }
    }
  } else {
    asm volatile("setmaxnreg.inc.sync.aligned.u32 232;");
    const int wg = warp >> 2;
    const int g = lane >> 2, t = lane & 3;
    const int lr0 = warp * 16 + g;
    const int slab = rb * 8 + warp;
    unsigned dn; asm volatile("ld.relaxed.gpu.global.u32 %0, [%1];" : "=r"(dn) : "l"(&g_done) : "memory");
    const uint32_t a_lo = dlo(sb + OFF_D + wg * 8192, 16);
    const uint32_t ring_lo = (sb + OFF_RING) >> 4;

#define SLOT(gs) ((gs) % NSLOT)
#define PHASE(gs) (((gs) / NSLOT) & 1)
#define B_LO(gs, off, lbo) (ring_lo + ((SLOT(gs) * SLOT_BYTES + (off)) >> 4) + (((lbo) >> 4) << 16))
#define STAGE_BEGIN(gs) do { mbar_wait(bar0 + 8 * (BAR_FULL + SLOT(gs)), PHASE(gs)); wg_fence(); } while (0)
#define RELEASE(gs) do { if (lane == 0) mbar_arrive(bar0 + 8 * (BAR_EMPTY + SLOT(gs))); } while (0)
#define STAGE_END(prev) do { wg_commit(); wg_wait<1>(); if ((prev) >= 0) RELEASE((prev) < 0 ? 0 : (prev)); } while (0)
#define WARP_ARRIVE(b) do { __syncwarp(); if (lane == 0) mbar_arrive(bar0 + 8 * (b)); } while (0)

    uint4* act_out = g_act + (size_t)(slab * 112 + 14 * j) * 32 + lane;
    const uint32_t bias_addr = sb + OFF_B1 + 8 * t;
    float rs0, rs1;
    float pool[160];
    float (&acca)[64] = reinterpret_cast<float (&)[64]>(pool[0]);
    float (&accq)[96] = reinterpret_cast<float (&)[96]>(pool[64]);
    float (&accb)[48] = reinterpret_cast<float (&)[48]>(pool[0]);
    float (&accy)[64] = reinterpret_cast<float (&)[64]>(pool[64]);
    float (&accs)[32] = reinterpret_cast<float (&)[32]>(pool[0]);
    float rl0, rl1, ir0, ir1;
    {
      uint4 q[16], p[16];
      const int par = g & 1;
      const uint32_t rowa = sb + OFF_D + lr0 * 128;
      const uint32_t u0 = (uint32_t)(((par * 4 + t) ^ g) << 4), u1 = u0 ^ 64u;
      named_bar_sync(0, 384);
      float sm[2][4], ga[2][4], gb[2][4];
#pragma unroll
      for (int a = 0; a < 2; a++) {
        sm[a][0] = sm[a][1] = sm[a][2] = sm[a][3] = 0.f;
        ga[a][0] = ga[a][1] = ga[a][2] = ga[a][3] = 0.f;
        gb[a][0] = gb[a][1] = gb[a][2] = gb[a][3] = 0.f;
      }
      const uint32_t ones = 0x3F803F80u;
#pragma unroll
      for (int c = 0; c < 8; c++) {
        if ((c & 1) == 0) mbar_wait(bar0 + 8 * (BAR_X + (c >> 1)), 0);
        q[2 * c] = lds_v4(rowa + c * 16384 + u0);     p[2 * c] = lds_v4(rowa + c * 16384 + 1024 + u0);
        q[2 * c + 1] = lds_v4(rowa + c * 16384 + u1); p[2 * c + 1] = lds_v4(rowa + c * 16384 + 1024 + u1);
#pragma unroll
        for (int h = 0; h < 2; h++) {
          const int i = 2 * c + h;
          mma16816(sm[0], q[i].x, p[i].x, q[i].y, p[i].y, ones, ones);
          mma16816(sm[1], q[i].z, p[i].z, q[i].w, p[i].w, ones, ones);
          mma16816(ga[0], q[i].x, p[i].x, q[i].y, p[i].y, q[i].x, q[i].y);
          mma16816(ga[1], q[i].z, p[i].z, q[i].w, p[i].w, q[i].z, q[i].w);
          mma16816(gb[0], q[i].x, p[i].x, q[i].y, p[i].y, p[i].x, p[i].y);
          mma16816(gb[1], q[i].z, p[i].z, q[i].w, p[i].w, p[i].z, p[i].w);
        }
      }
      const float m0 = (sm[0][0] + sm[1][0]) * (1.f / DM);
      const float m1 = (sm[0][2] + sm[1][2]) * (1.f / DM);
      const uint32_t mb0 = pack2(m0, m0), mb1 = pack2(m1, m1);
      PROF(12);
#pragma unroll
      for (int i = 0; i < 16; i++) {
        const uint32_t off = (uint32_t)(i >> 1) * 16384 + ((i & 1) ? u1 : u0);
        sts_v4(rowa + off, hsub2_bf16(q[i].x, mb0), hsub2_bf16(q[i].y, mb0), hsub2_bf16(q[i].z, mb0), hsub2_bf16(q[i].w, mb0));
        sts_v4(rowa + 1024 + off, hsub2_bf16(p[i].x, mb1), hsub2_bf16(p[i].y, mb1), hsub2_bf16(p[i].z, mb1), hsub2_bf16(p[i].w, mb1));
      }
      fence_async_smem();
      float d0 = par ? ga[0][1] + ga[1][1] : ga[0][0] + ga[1][0];
      float d1 = par ? gb[0][3] + gb[1][3] : gb[0][2] + gb[1][2];
      d0 = __shfl_sync(0xffffffffu, d0, (lane & ~3) | (g >> 1));
      d1 = __shfl_sync(0xffffffffu, d1, (lane & ~3) | (g >> 1));
      const float v0 = fmaxf(d0 * (1.f / DM) - m0 * m0, 0.f) + 1e-5f;
      const float v1 = fmaxf(d1 * (1.f / DM) - m1 * m1, 0.f) + 1e-5f;
      rs0 = rsqrtf(v0); rs1 = rsqrtf(v1);
      ir0 = v0 * rs0; ir1 = v1 * rs1;
      rl0 = rs0 * LOG2E; rl1 = rs1 * LOG2E;
      mbar_wait(bar0 + 8 * BAR_BIAS, 0);
      init_bias<16>(acca, bias_addr, ir0, ir1);
      named_bar_sync(1 + wg, 128);
      PROF(1);
    }
#pragma unroll
    for (int st = 0; st < 8; st++) {
      STAGE_BEGIN(st);
#pragma unroll
      for (int kk = 0; kk < 4; kk++) wgmma_ss_n128<1>(acca, a_lo + ((st * 16384 + kk * 32) >> 4), B_LO(st, kk * 2048, 8192));
      STAGE_END(st - 1);
      if (st == 0) zero_regs(accq);
    }
    PROF(2);
#pragma unroll
    for (int st = 0; st < 16; st++) {
      const int gs = 8 + st;
      STAGE_BEGIN(gs);
      const uint32_t as = a_lo + (((st >> 1) * 16384 + (st & 1) * 64) >> 4);
      wgmma_ss_n192<1>(accq, as, B_LO(gs, 0, 4096));
      wgmma_ss_n192<1>(accq, as + 2, B_LO(gs, 2048, 4096));
      STAGE_END(gs - 1);
      if (st == 0) fence_regs(acca);
      if (st < 8) mish_tile(acca + 8 * st, rs0, rs1, rl0, rl1, act_out + st * 32);
      if (st == 7) { WARP_ARRIVE(BAR_PUB_A); PROF(3); }
      if (st == 8) init_bias<12>(accb, bias_addr + 512, ir0, ir1);
    }
    PROF(4);
    const uint4* act_in = g_act + (size_t)(slab * 112 + 56 * khalf) * 32 + lane;
    const uint4* o_in = g_o + (size_t)(slab * 32) * 32 + lane;
    uint4 ab[4][4];
    auto load_a = [&](int rs) {
      if (rs < 8) {
        const int kt = 14 * (rs >> 1) + 4 * (rs & 1);
#pragma unroll
        for (int kk = 0; kk < 4; kk++) ab[rs & 3][kk] = ldg_cg(act_in + (kt + kk) * 32);
      } else if (rs < 16) {
        const int kt = 14 * ((rs - 8) >> 1) + 8 + 3 * (rs & 1);
#pragma unroll
        for (int kk = 0; kk < 3; kk++) ab[rs & 3][kk] = ldg_cg(act_in + (kt + kk) * 32);
      } else if (rs < 24) {
#pragma unroll
        for (int kk = 0; kk < 4; kk++) ab[rs & 3][kk] = ldg_cg(o_in + (4 * (rs - 16) + kk) * 32);
      }
    };
    auto keep_a = [&](int rs) {
#pragma unroll
      for (int kk = 0; kk < 4; kk++) if (!(rs >= 8 && rs < 16 && kk == 3)) fence_u4(ab[rs & 3][kk]);
    };
    uint4 pq[4];
    const unsigned ep1 = dn / NCTA + 1u;
    {
      const int m = lane >> 3, rr = lane & 7;
      const uint32_t srow = sb + OFF_RING + (warp * 16 + (m & 1) * 8 + rr) * 128;
      const uint32_t ka = dlo(sb + OFF_RING + SLOT(25) * SLOT_BYTES + wg * 8192, 16);
      const uint32_t vb = dlo(sb + OFF_RING + SLOT(26) * SLOT_BYTES + wg * 8192, OFF_ONES - (OFF_RING + SLOT(26) * SLOT_BYTES + wg * 8192));
      float (&acck)[36] = reinterpret_cast<float (&)[36]>(pool[64]);
#pragma unroll
      for (int st = 0; st < 8; st++) {
        const int gs = st == 0 ? 24 : 26 + st;
        STAGE_BEGIN(gs);
#pragma unroll
        for (int kk = 0; kk < 4; kk++) wgmma_ss_n96<1>(accb, a_lo + ((st * 16384 + kk * 32) >> 4), B_LO(gs, kk * 2048, 8192));
        if (st == 2) {
          wgmma_tt_n72<0>(acck, ka, vb);
#pragma unroll
          for (int kk = 1; kk < 4; kk++) wgmma_tt_n72<1>(acck, ka + kk * 128, vb + kk * 128);
        }
        STAGE_END(st == 1 ? 24 : gs - 1);
        if (st == 0) {
          fence_regs(accq);
          mbar_wait(bar0 + 8 * (BAR_FULL + SLOT(25)), PHASE(25));
#pragma unroll
          for (int i = 0; i < 4; i++) {
            const uint4 r = phi_tile(accq + 8 * i, rs0, rs1, rl0, rl1);
            stmatrix_x4(srow + SLOT(25) * SLOT_BYTES + (((2 * i + (m >> 1)) ^ rr) << 4), r.x, r.y, r.z, r.w);
          }
        } else if (st == 1) {
          mbar_wait(bar0 + 8 * (BAR_FULL + SLOT(26)), PHASE(26));
#pragma unroll
          for (int i = 0; i < 4; i++) {
            const float* c = accq + 32 + 8 * i;
            stmatrix_x4(srow + SLOT(26) * SLOT_BYTES + (((2 * i + (m >> 1)) ^ rr) << 4),
                        pack2(c[0] * rs0, c[1] * rs0), pack2(c[2] * rs1, c[3] * rs1), pack2(c[4] * rs0, c[5] * rs0), pack2(c[6] * rs1, c[7] * rs1));
          }
          fence_async_smem();
          named_bar_sync(1 + wg, 128);
        } else if (st == 2) {
          pq[0] = phi_tile(accq + 64, rs0, rs1, rl0, rl1); pq[1] = phi_tile(accq + 72, rs0, rs1, rl0, rl1);
        } else if (st == 3) {
          RELEASE(25); RELEASE(26);
          fence_regs(acck);
          const int wq = warp & 3;
          float* hb = &g_kv[(ep1 & 1) ^ 1][(4 * j + wq) * 272];
          float* a0p = hb + g * 16 + 2 * t;
#pragma unroll
          for (int w = 0; w < 4; w++) {
            if (wq == w) {
              red_add_v2(a0p, acck[8 * w], acck[8 * w + 1]); red_add_v2(a0p + 128, acck[8 * w + 2], acck[8 * w + 3]);
              red_add_v2(a0p + 8, acck[8 * w + 4], acck[8 * w + 5]); red_add_v2(a0p + 136, acck[8 * w + 6], acck[8 * w + 7]);
            }
          }
          if (t == 0) { red_add_f32(hb + 256 + g, acck[32]); red_add_f32(hb + 264 + g, acck[34]); }
          WARP_ARRIVE(BAR_PUB_KV);
        } else if (st == 4) {
          pq[2] = phi_tile(accq + 80, rs0, rs1, rl0, rl1); pq[3] = phi_tile(accq + 88, rs0, rs1, rl0, rl1);
        } else if (st == 5) {
          mbar_wait(bar0 + 8 * BAR_RDY_A, 0);
          load_a(0); load_a(1); load_a(2);
        }
      }
    }
    PROF(5);
#pragma unroll
    for (int st = 0; st < 8; st++) {
      const int gs = 34 + st;
      STAGE_BEGIN(gs);
#pragma unroll
      for (int kk = 0; kk < 4; kk++) {
        if (st == 0 && kk == 0) wgmma_rs_n128<0>(accy, ab[st & 3][kk], B_LO(gs, kk * 2048, 8192));
        else wgmma_rs_n128<1>(accy, ab[st & 3][kk], B_LO(gs, kk * 2048, 8192));
      }
      if (st == 7) {
        mbar_wait(bar0 + 8 * BAR_RDY_KV, 0);
        PROF(7);
        const uint32_t kb = dlo(sb + OFF_KVB, 8192);
        wgmma_rs_n96<0>(accb, pq[0], kb);
#pragma unroll
        for (int kk = 1; kk < 4; kk++) wgmma_rs_n96<1>(accb, pq[kk], kb + kk * 128);
      }
      STAGE_END(gs - 1);
      if (st == 0) { fence_regs(accb); WARP_ARRIVE(BAR_DFREE); }
      else keep_a(st - 1);
      if (st == 5) mbar_wait(bar0 + 8 * BAR_RDY_B, 0);
      load_a(st + 3);
      if (st < 3) {
#pragma unroll
        for (int i = 2 * st; i < 2 * st + 2; i++)
          mish_tile(accb + 8 * i, rs0, rs1, rl0, rl1, act_out + (8 + i) * 32);
        if (st == 2) WARP_ARRIVE(BAR_PUB_B);
      }
      PROF(13 + st);
    }
    PROF(6);
#pragma unroll
    for (int st = 0; st < 8; st++) {
      const int gs = 42 + st, rs = 8 + st;
      STAGE_BEGIN(gs);
#pragma unroll
      for (int kk = 0; kk < 3; kk++) wgmma_rs_n128<1>(accy, ab[rs & 3][kk], B_LO(gs, kk * 2048, 6144));
      STAGE_END(gs - 1);
      keep_a(rs - 1);
      if (st == 5) mbar_wait(bar0 + 8 * BAR_RDY_O, 0);
      load_a(rs + 3);
      if (st == 0) {
        fence_regs(accb);
#pragma unroll
        for (int kk = 0; kk < 4; kk++) fence_u4(pq[kk]);
        uint4* o_out = g_o + (size_t)(slab * 32 + 4 * j) * 32 + lane;
#pragma unroll
        for (int hh = 0; hh < 4; hh++) {
          const float i0 = __fdividef(1.f, accb[32 + 4 * hh] + 1e-6f), i1 = __fdividef(1.f, accb[34 + 4 * hh] + 1e-6f);
          const float* n = accb + 8 * hh;
          stg_v4(o_out + hh * 32, pack2(n[0] * i0, n[1] * i0), pack2(n[2] * i1, n[3] * i1), pack2(n[4] * i0, n[5] * i0), pack2(n[6] * i1, n[7] * i1));
        }
        WARP_ARRIVE(BAR_PUB_O);
      }
    }
    PROF(8);
    const int c0 = 128 * nt + 64 * khalf + 2 * t;
    const size_t ro0 = (size_t)(rb * 128 + lr0) * DM + c0, ro1 = ro0 + 8 * DM;
    const uint32_t tag = ep1 & 1u;
    uint32_t xv[16];
#pragma unroll
    for (int st = 0; st < 8; st++) {
      const int gs = 50 + st, rs = 16 + st;
      STAGE_BEGIN(gs);
#pragma unroll
      for (int kk = 0; kk < 4; kk++) {
        if (st == 0 && kk == 0) wgmma_rs_n64<0>(accs, ab[rs & 3][kk], B_LO(gs, kk * 2048, 8192));
        else wgmma_rs_n64<1>(accs, ab[rs & 3][kk], B_LO(gs, kk * 2048, 8192));
      }
      STAGE_END(gs - 1);
      keep_a(rs - 1);
      if (st == 0) {
        fence_regs(accy);
        float4* yp = g_yp + (size_t)((bid * 8 + warp) * 8) * 32 + lane;
#pragma unroll
        for (int q = 0; q < 8; q++) {
          const uint32_t v0 = (__float_as_uint(accy[32 + 4 * q]) & ~1u) | tag, v1 = (__float_as_uint(accy[33 + 4 * q]) & ~1u) | tag;
          const uint32_t v2 = (__float_as_uint(accy[34 + 4 * q]) & ~1u) | tag, v3 = (__float_as_uint(accy[35 + 4 * q]) & ~1u) | tag;
          asm volatile("st.relaxed.gpu.global.v4.u32 [%0], {%1,%2,%3,%4};" ::"l"(yp + q * 32), "r"(v0), "r"(v1), "r"(v2), "r"(v3) : "memory");
        }
      }
      load_a(rs + 3);
      if (st == 1) {
#pragma unroll
        for (int q = 0; q < 8; q++) { xv[2 * q] = ldg_nc32(x + ro0 + 8 * q); xv[2 * q + 1] = ldg_nc32(x + ro1 + 8 * q); }
      }
      PROF(21 + st);
    }
    PROF(9);
    {
      const float4* yp = g_yp + (size_t)(((bid ^ 16) * 8 + warp) * 8) * 32 + lane;
      uint4 pv[8];
      uint32_t it = 0;
      wg_wait<0>();
      keep_a(23);
      fence_regs(accs);
      while (true) {
        uint32_t bad = 0;
#pragma unroll
        for (int q = 0; q < 8; q++)
          asm volatile("ld.relaxed.gpu.global.v4.u32 {%0,%1,%2,%3}, [%4];" : "=r"(pv[q].x), "=r"(pv[q].y), "=r"(pv[q].z), "=r"(pv[q].w) : "l"(yp + q * 32) : "memory");
#pragma unroll
        for (int q = 0; q < 8; q++) bad |= (pv[q].x ^ tag) | (pv[q].y ^ tag) | (pv[q].z ^ tag) | (pv[q].w ^ tag);
        if (!__any_sync(0xffffffffu, bad & 1u)) break;
        if (++it > (1u << 20)) asm volatile("trap;");
      }
      PROF(10);
#pragma unroll
      for (int q = 0; q < 8; q++) {
        const float y0 = accy[4 * q] + __uint_as_float(pv[q].x), y1 = accy[4 * q + 1] + __uint_as_float(pv[q].y);
        const float y2 = accy[4 * q + 2] + __uint_as_float(pv[q].z), y3 = accy[4 * q + 3] + __uint_as_float(pv[q].w);
        const float o0 = fmaf(accs[4 * q], silu_f(y0), bf_lo(xv[2 * q])), o1 = fmaf(accs[4 * q + 1], silu_f(y1), bf_hi(xv[2 * q]));
        const float o2 = fmaf(accs[4 * q + 2], silu_f(y2), bf_lo(xv[2 * q + 1])), o3 = fmaf(accs[4 * q + 3], silu_f(y3), bf_hi(xv[2 * q + 1]));
        *reinterpret_cast<uint32_t*>(out + ro0 + 8 * q) = pack2(o0, o1);
        *reinterpret_cast<uint32_t*>(out + ro1 + 8 * q) = pack2(o2, o3);
      }
    }
    PROF(11);
    if (tid == 0) red_inc(&g_done);
  }
}

typedef CUresult (*EncodeFn)(CUtensorMap*, CUtensorMapDataType, cuuint32_t, void*, const cuuint64_t*, const cuuint64_t*,
                             const cuuint32_t*, const cuuint32_t*, CUtensorMapInterleave, CUtensorMapSwizzle,
                             CUtensorMapL2promotion, CUtensorMapFloatOOBfill);

void make_map(EncodeFn enc, CUtensorMap* tm, const void* ptr, int rows, int cols, int box_rows) {
  cuuint64_t gd[2] = {(cuuint64_t)cols, (cuuint64_t)rows};
  cuuint64_t gs[1] = {(cuuint64_t)cols * 2};
  cuuint32_t bd[2] = {64, (cuuint32_t)box_rows};
  cuuint32_t es[2] = {1, 1};
  enc(tm, CU_TENSOR_MAP_DATA_TYPE_BFLOAT16, 2, const_cast<void*>(ptr), gd, gs, bd, es, CU_TENSOR_MAP_INTERLEAVE_NONE,
      CU_TENSOR_MAP_SWIZZLE_128B, CU_TENSOR_MAP_L2_PROMOTION_L2_128B, CU_TENSOR_MAP_FLOAT_OOB_FILL_NONE);
}

}

extern "C" void kernel_launch(void* const* d_in, const int* in_sizes, int n_in, void* d_out, int out_size) {
  const __nv_bfloat16* x = (const __nv_bfloat16*)d_in[0];
  const void* wqkv = d_in[1];
  const void* wo = d_in[2];
  const void* w1 = d_in[4];
  const __nv_bfloat16* b1 = (const __nv_bfloat16*)d_in[5];
  const void* w2 = d_in[6];
  static EncodeFn enc = nullptr;
  if (!enc) {
    cudaDriverEntryPointQueryResult qr;
    void* fn = nullptr;
    cudaGetDriverEntryPoint("cuTensorMapEncodeTiled", &fn, cudaEnableDefault, &qr);
    enc = (EncodeFn)fn;
    cudaFuncSetAttribute(fused_kernel, cudaFuncAttributeMaxDynamicSharedMemorySize, SMEM_ALLOC);
  }
  CUtensorMap tx, tq, t1, t2a, t2b, to;
  make_map(enc, &tx, x, 2048, DM, 128);
  make_map(enc, &tq, wqkv, DM, 3 * DM, 32);
  make_map(enc, &t1, w1, DM, FF, 64);
  make_map(enc, &t2a, w2, FF, DM, 64);
  make_map(enc, &t2b, w2, FF, DM, 48);
  make_map(enc, &to, wo, DM, DM, 64);
  fused_kernel<<<NCTA, 384, SMEM_ALLOC>>>(tx, tq, t1, t2a, t2b, to, x, b1, (__nv_bfloat16*)d_out);
}
```

```cpp
#include <cuda_runtime.h>
#include <cuda_bf16.h>
#include <cuda.h>
#include <stdint.h>

namespace {

constexpr int DM = 512, FF = 1792;
constexpr int NCTA = 128;
constexpr int NRING = 5;
constexpr int NSLOT = 10;
constexpr int SLOT_BYTES = 16384;
constexpr int OFF_D = 0;
constexpr int OFF_PK = 0, OFF_V = 16384;
constexpr int OFF_KVB = 0;
constexpr int OFF_XT = 16384;
constexpr int OFF_RING = 131072;
constexpr int OFF_MISC = OFF_RING + NRING * SLOT_BYTES;
constexpr int OFF_ONES = OFF_MISC;
constexpr int OFF_BAR = OFF_MISC + 8192;
constexpr int OFF_B1 = OFF_MISC + 8704;
constexpr int SMEM_ALLOC = OFF_MISC + 9728;

enum { BAR_FULL = 0, BAR_EMPTY = NSLOT, BAR_X = 2 * NSLOT, BAR_BIAS = BAR_X + 4, BAR_XT,
       BAR_PUB_A, BAR_PUB_KV, BAR_PUB_B, BAR_PUB_O,
       BAR_RDY_A, BAR_RDY_B, BAR_RDY_O, BAR_RDY_KV, BAR_COUNT };
static_assert(BAR_COUNT <= 40, "too many barriers");

constexpr int NSTAGES = 56;
__host__ __device__ constexpr int slot_of(int gs) {
  if (gs < 32) return gs % 5;
  const int p = (gs - 32) % 10;
  return p < 5 ? 5 + p : (p - 3) % 5;
}
__host__ __device__ constexpr int use_of(int gs) {
  if (gs < 32) return gs / 5;
  const int sl = slot_of(gs);
  return (gs - 32) / 10 + (sl < 5 ? (sl < 2 ? 7 : 6) : 0);
}
__host__ __device__ constexpr int slot_off(int sl) { return sl < 5 ? OFF_RING + sl * SLOT_BYTES : OFF_D + (sl - 2) * SLOT_BYTES; }

__device__ uint4 g_act[128 * 112 * 32];
__device__ uint4 g_o[128 * 32 * 32];
__device__ float4 g_yp[NCTA * 8 * 8 * 32];
__device__ float g_kv[2][32 * 272];
__device__ unsigned g_cntA[16 * 2 * 8];
__device__ unsigned g_cntB[16 * 2 * 8];
__device__ unsigned g_cntO[16 * 8];
__device__ unsigned g_cntKV[8 * 8];
__device__ unsigned g_done;

#define PROF(i)

__device__ __forceinline__ uint32_t smem_u32(const void* p) { return (uint32_t)__cvta_generic_to_shared(p); }
__device__ __forceinline__ void mbar_init(uint32_t bar, uint32_t cnt) { asm volatile("mbarrier.init.shared::cta.b64 [%0], %1;" ::"r"(bar), "r"(cnt)); }
__device__ __forceinline__ void mbar_expect_tx(uint32_t bar, uint32_t bytes) { asm volatile("mbarrier.arrive.expect_tx.shared::cta.b64 _, [%0], %1;" ::"r"(bar), "r"(bytes) : "memory"); }
__device__ __forceinline__ void mbar_arrive(uint32_t bar) { asm volatile("mbarrier.arrive.shared::cta.b64 _, [%0];" ::"r"(bar) : "memory"); }
__device__ __forceinline__ void mbar_wait(uint32_t bar, uint32_t parity) {
  asm volatile("{\n.reg .pred P1;\n.reg .u32 cnt;\n"
               "mbarrier.try_wait.parity.shared::cta.b64 P1, [%0], %1;\n@P1 bra DONE;\n"
               "mov.u32 cnt, 0;\n"
               "LAB_WAIT:\n"
               "mbarrier.try_wait.parity.shared::cta.b64 P1, [%0], %1;\n@P1 bra DONE;\n"
               "add.u32 cnt, cnt, 1;\nsetp.lt.u32 P1, cnt, 16777216;\n@P1 bra LAB_WAIT;\ntrap;\n"
               "DONE:\n}" ::"r"(bar), "r"(parity) : "memory");
}
__device__ __forceinline__ void tma2d(uint32_t dst, const CUtensorMap* tm, int c0, int c1, uint32_t bar) {
  asm volatile("cp.async.bulk.tensor.2d.shared::cluster.global.mbarrier::complete_tx::bytes [%0], [%1, {%3, %4}], [%2];" ::"r"(dst), "l"(tm), "r"(bar), "r"(c0), "r"(c1) : "memory");
}
__device__ __forceinline__ void wg_fence() { asm volatile("wgmma.fence.sync.aligned;" ::: "memory"); }
__device__ __forceinline__ void wg_commit() { asm volatile("wgmma.commit_group.sync.aligned;" ::: "memory"); }
template <int N> __device__ __forceinline__ void wg_wait() { asm volatile("wgmma.wait_group.sync.aligned %0;" ::"n"(N) : "memory"); }
template <int N> __device__ __forceinline__ void zero_regs(float (&d)[N]) {
#pragma unroll
  for (int i = 0; i < N; i++) d[i] = 0.f;
}
template <int N> __device__ __forceinline__ void fence_regs(float (&d)[N]) {
#pragma unroll
  for (int i = 0; i < N; i++) asm volatile("" : "+f"(d[i])::"memory");
}
__device__ __forceinline__ void fence_u4(uint4& v) { asm volatile("" : "+r"(v.x), "+r"(v.y), "+r"(v.z), "+r"(v.w)::"memory"); }
__device__ __forceinline__ void named_bar_sync(int id, int n) { asm volatile("bar.sync %0, %1;" ::"r"(id), "r"(n) : "memory"); }
__device__ __forceinline__ void fence_async_smem() { asm volatile("fence.proxy.async.shared::cta;" ::: "memory"); }
__device__ __forceinline__ constexpr uint32_t dlo(uint32_t addr, uint32_t lbo_bytes) { return ((addr & 0x3FFFFu) >> 4) | ((lbo_bytes >> 4) << 16); }
__device__ __forceinline__ void mma16816(float (&c)[4], uint32_t a0, uint32_t a1, uint32_t a2, uint32_t a3, uint32_t b0, uint32_t b1) {
  asm volatile("mma.sync.aligned.m16n8k16.row.col.f32.bf16.bf16.f32 {%0,%1,%2,%3}, {%4,%5,%6,%7}, {%8,%9}, {%0,%1,%2,%3};"
               : "+f"(c[0]), "+f"(c[1]), "+f"(c[2]), "+f"(c[3]) : "r"(a0), "r"(a1), "r"(a2), "r"(a3), "r"(b0), "r"(b1));
}
__device__ __forceinline__ void stmatrix_x4(uint32_t addr, uint32_t a, uint32_t b, uint32_t c, uint32_t d) {
  asm volatile("stmatrix.sync.aligned.m8n8.x4.shared.b16 [%0], {%1,%2,%3,%4};" ::"r"(addr), "r"(a), "r"(b), "r"(c), "r"(d) : "memory");
}
__device__ __forceinline__ uint32_t pack2(float lo, float hi) { uint32_t r; asm("cvt.rn.bf16x2.f32 %0, %1, %2;" : "=r"(r) : "f"(hi), "f"(lo)); return r; }
__device__ __forceinline__ float ex2(float x) { float r; asm("ex2.approx.ftz.f32 %0, %1;" : "=f"(r) : "f"(x)); return r; }
__device__ __forceinline__ float rcp(float x) { float r; asm("rcp.approx.ftz.f32 %0, %1;" : "=f"(r) : "f"(x)); return r; }
__device__ __forceinline__ float bf_lo(uint32_t v) { return __uint_as_float(v << 16); }
__device__ __forceinline__ float bf_hi(uint32_t v) { return __uint_as_float(v & 0xffff0000u); }
__device__ __forceinline__ uint32_t hsub2_bf16(uint32_t a, uint32_t b) {
  __nv_bfloat162 x = *reinterpret_cast<__nv_bfloat162*>(&a), y = *reinterpret_cast<__nv_bfloat162*>(&b);
  __nv_bfloat162 r = __hsub2(x, y);
  return *reinterpret_cast<uint32_t*>(&r);
}
__device__ __forceinline__ uint4 ldg_cg(const void* p) {
  uint4 v; asm volatile("ld.global.cg.v4.u32 {%0,%1,%2,%3}, [%4];" : "=r"(v.x), "=r"(v.y), "=r"(v.z), "=r"(v.w) : "l"(p) : "memory"); return v;
}
__device__ __forceinline__ void stg_v4(void* p, uint32_t a, uint32_t b, uint32_t c, uint32_t d) {
  asm volatile("st.global.v4.u32 [%0], {%1,%2,%3,%4};" ::"l"(p), "r"(a), "r"(b), "r"(c), "r"(d) : "memory");
}
__device__ __forceinline__ void sts_v4(uint32_t addr, uint32_t a, uint32_t b, uint32_t c, uint32_t d) {
  asm volatile("st.shared.v4.u32 [%0], {%1,%2,%3,%4};" ::"r"(addr), "r"(a), "r"(b), "r"(c), "r"(d) : "memory");
}
__device__ __forceinline__ void sts_f32(uint32_t addr, float v) { asm volatile("st.shared.f32 [%0], %1;" ::"r"(addr), "f"(v) : "memory"); }
__device__ __forceinline__ uint4 lds_v4(uint32_t addr) { uint4 v; asm volatile("ld.shared.v4.u32 {%0,%1,%2,%3}, [%4];" : "=r"(v.x), "=r"(v.y), "=r"(v.z), "=r"(v.w) : "r"(addr) : "memory"); return v; }
__device__ __forceinline__ uint32_t lds_u32(uint32_t addr) { uint32_t v; asm volatile("ld.shared.u32 %0, [%1];" : "=r"(v) : "r"(addr) : "memory"); return v; }
__device__ __forceinline__ void sts_u32(uint32_t addr, uint32_t v) { asm volatile("st.shared.u32 [%0], %1;" ::"r"(addr), "r"(v) : "memory"); }
__device__ __forceinline__ float2 lds_f32x2(uint32_t addr) { float2 v; asm volatile("ld.shared.v2.f32 {%0,%1}, [%2];" : "=f"(v.x), "=f"(v.y) : "r"(addr) : "memory"); return v; }
__device__ __forceinline__ void red_add_v2(float* p, float a, float b) { asm volatile("red.relaxed.gpu.global.add.v2.f32 [%0], {%1,%2};" ::"l"(p), "f"(a), "f"(b) : "memory"); }
__device__ __forceinline__ void red_add_f32(float* p, float a) { asm volatile("red.relaxed.gpu.global.add.f32 [%0], %1;" ::"l"(p), "f"(a) : "memory"); }
__device__ __forceinline__ void red_inc(unsigned* cnt) { asm volatile("red.relaxed.gpu.global.add.u32 [%0], 1;" ::"l"(cnt) : "memory"); }
__device__ __forceinline__ void poll_ge(const unsigned* cnt, unsigned target) {
  asm volatile("{\n.reg .pred P1;\n.reg .u32 cnt, v;\n.reg .s32 d;\n"
               "mov.u32 cnt, 0;\n"
               "LAB_POLL:\n"
               "ld.acquire.gpu.global.u32 v, [%0];\nsub.s32 d, v, %1;\nsetp.ge.s32 P1, d, 0;\n@P1 bra DONE;\n"
               "add.u32 cnt, cnt, 1;\nsetp.lt.u32 P1, cnt, 4194304;\n@P1 bra LAB_POLL;\ntrap;\n"
               "DONE:\n}" ::"l"(cnt), "r"(target) : "memory");
}

template <int SCALE_D> __device__ __forceinline__ void wgmma_ss_n192(float (&d)[96], uint32_t da, uint32_t db) {
  asm volatile("{\n.reg .b64 da, db;\nmov.b64 da, {%96, %98};\nmov.b64 db, {%97, %98};\n"
    "wgmma.mma_async.sync.aligned.m64n192k16.f32.bf16.bf16 {%0, %1, %2, %3, %4, %5, %6, %7, %8, %9, %10, %11, %12, %13, %14, %15, %16, %17, %18, %19, %20, %21, %22, %23, %24, %25, %26, %27, %28, %29, %30, %31, %32, %33, %34, %35, %36, %37, %38, %39, %40, %41, %42, %43, %44, %45, %46, %47, %48, %49, %50, %51, %52, %53, %54, %55, %56, %57, %58, %59, %60, %61, %62, %63, %64, %65, %66, %67, %68, %69, %70, %71, %72, %73, %74, %75, %76, %77, %78, %79, %80, %81, %82, %83, %84, %85, %86, %87, %88, %89, %90, %91, %92, %93, %94, %95}, da, db, %99, 1, 1, 0, 1;\n}\n"
    : "+f"(d[0]), "+f"(d[1]), "+f"(d[2]), "+f"(d[3]), "+f"(d[4]), "+f"(d[5]), "+f"(d[6]), "+f"(d[7]), "+f"(d[8]), "+f"(d[9]), "+f"(d[10]), "+f"(d[11]), "+f"(d[12]), "+f"(d[13]), "+f"(d[14]), "+f"(d[15]), "+f"(d[16]), "+f"(d[17]), "+f"(d[18]), "+f"(d[19]), "+f"(d[20]), "+f"(d[21]), "+f"(d[22]), "+f"(d[23]), "+f"(d[24]), "+f"(d[25]), "+f"(d[26]), "+f"(d[27]), "+f"(d[28]), "+f"(d[29]), "+f"(d[30]), "+f"(d[31]), "+f"(d[32]), "+f"(d[33]), "+f"(d[34]), "+f"(d[35]), "+f"(d[36]), "+f"(d[37]), "+f"(d[38]), "+f"(d[39]), "+f"(d[40]), "+f"(d[41]), "+f"(d[42]), "+f"(d[43]), "+f"(d[44]), "+f"(d[45]), "+f"(d[46]), "+f"(d[47]), "+f"(d[48]), "+f"(d[49]), "+f"(d[50]), "+f"(d[51]), "+f"(d[52]), "+f"(d[53]), "+f"(d[54]), "+f"(d[55]), "+f"(d[56]), "+f"(d[57]), "+f"(d[58]), "+f"(d[59]), "+f"(d[60]), "+f"(d[61]), "+f"(d[62]), "+f"(d[63]), "+f"(d[64]), "+f"(d[65]), "+f"(d[66]), "+f"(d[67]), "+f"(d[68]), "+f"(d[69]), "+f"(d[70]), "+f"(d[71]), "+f"(d[72]), "+f"(d[73]), "+f"(d[74]), "+f"(d[75]), "+f"(d[76]), "+f"(d[77]), "+f"(d[78]), "+f"(d[79]), "+f"(d[80]), "+f"(d[81]), "+f"(d[82]), "+f"(d[83]), "+f"(d[84]), "+f"(d[85]), "+f"(d[86]), "+f"(d[87]), "+f"(d[88]), "+f"(d[89]), "+f"(d[90]), "+f"(d[91]), "+f"(d[92]), "+f"(d[93]), "+f"(d[94]), "+f"(d[95])
    : "r"(da), "r"(db), "r"(0x40000040u), "n"(SCALE_D));
}
template <int SCALE_D> __device__ __forceinline__ void wgmma_ss_n128(float (&d)[64], uint32_t da, uint32_t db) {
  asm volatile("{\n.reg .b64 da, db;\nmov.b64 da, {%64, %66};\nmov.b64 db, {%65, %66};\n"
    "wgmma.mma_async.sync.aligned.m64n128k16.f32.bf16.bf16 {%0, %1, %2, %3, %4, %5, %6, %7, %8, %9, %10, %11, %12, %13, %14, %15, %16, %17, %18, %19, %20, %21, %22, %23, %24, %25, %26, %27, %28, %29, %30, %31, %32, %33, %34, %35, %36, %37, %38, %39, %40, %41, %42, %43, %44, %45, %46, %47, %48, %49, %50, %51, %52, %53, %54, %55, %56, %57, %58, %59, %60, %61, %62, %63}, da, db, %67, 1, 1, 0, 1;\n}\n"
    : "+f"(d[0]), "+f"(d[1]), "+f"(d[2]), "+f"(d[3]), "+f"(d[4]), "+f"(d[5]), "+f"(d[6]), "+f"(d[7]), "+f"(d[8]), "+f"(d[9]), "+f"(d[10]), "+f"(d[11]), "+f"(d[12]), "+f"(d[13]), "+f"(d[14]), "+f"(d[15]), "+f"(d[16]), "+f"(d[17]), "+f"(d[18]), "+f"(d[19]), "+f"(d[20]), "+f"(d[21]), "+f"(d[22]), "+f"(d[23]), "+f"(d[24]), "+f"(d[25]), "+f"(d[26]), "+f"(d[27]), "+f"(d[28]), "+f"(d[29]), "+f"(d[30]), "+f"(d[31]), "+f"(d[32]), "+f"(d[33]), "+f"(d[34]), "+f"(d[35]), "+f"(d[36]), "+f"(d[37]), "+f"(d[38]), "+f"(d[39]), "+f"(d[40]), "+f"(d[41]), "+f"(d[42]), "+f"(d[43]), "+f"(d[44]), "+f"(d[45]), "+f"(d[46]), "+f"(d[47]), "+f"(d[48]), "+f"(d[49]), "+f"(d[50]), "+f"(d[51]), "+f"(d[52]), "+f"(d[53]), "+f"(d[54]), "+f"(d[55]), "+f"(d[56]), "+f"(d[57]), "+f"(d[58]), "+f"(d[59]), "+f"(d[60]), "+f"(d[61]), "+f"(d[62]), "+f"(d[63])
    : "r"(da), "r"(db), "r"(0x40000040u), "n"(SCALE_D));
}
template <int SCALE_D> __device__ __forceinline__ void wgmma_ss_n96(float (&d)[48], uint32_t da, uint32_t db) {
  asm volatile("{\n.reg .b64 da, db;\nmov.b64 da, {%48, %50};\nmov.b64 db, {%49, %50};\n"
    "wgmma.mma_async.sync.aligned.m64n96k16.f32.bf16.bf16 {%0, %1, %2, %3, %4, %5, %6, %7, %8, %9, %10, %11, %12, %13, %14, %15, %16, %17, %18, %19, %20, %21, %22, %23, %24, %25, %26, %27, %28, %29, %30, %31, %32, %33, %34, %35, %36, %37, %38, %39, %40, %41, %42, %43, %44, %45, %46, %47}, da, db, %51, 1, 1, 0, 1;\n}\n"
    : "+f"(d[0]), "+f"(d[1]), "+f"(d[2]), "+f"(d[3]), "+f"(d[4]), "+f"(d[5]), "+f"(d[6]), "+f"(d[7]), "+f"(d[8]), "+f"(d[9]), "+f"(d[10]), "+f"(d[11]), "+f"(d[12]), "+f"(d[13]), "+f"(d[14]), "+f"(d[15]), "+f"(d[16]), "+f"(d[17]), "+f"(d[18]), "+f"(d[19]), "+f"(d[20]), "+f"(d[21]), "+f"(d[22]), "+f"(d[23]), "+f"(d[24]), "+f"(d[25]), "+f"(d[26]), "+f"(d[27]), "+f"(d[28]), "+f"(d[29]), "+f"(d[30]), "+f"(d[31]), "+f"(d[32]), "+f"(d[33]), "+f"(d[34]), "+f"(d[35]), "+f"(d[36]), "+f"(d[37]), "+f"(d[38]), "+f"(d[39]), "+f"(d[40]), "+f"(d[41]), "+f"(d[42]), "+f"(d[43]), "+f"(d[44]), "+f"(d[45]), "+f"(d[46]), "+f"(d[47])
    : "r"(da), "r"(db), "r"(0x40000040u), "n"(SCALE_D));
}
template <int SCALE_D> __device__ __forceinline__ void wgmma_tt_n72(float (&d)[36], uint32_t da, uint32_t db) {
  asm volatile("{\n.reg .b64 da, db;\nmov.b64 da, {%36, %38};\nmov.b64 db, {%37, %38};\n"
    "wgmma.mma_async.sync.aligned.m64n72k16.f32.bf16.bf16 {%0, %1, %2, %3, %4, %5, %6, %7, %8, %9, %10, %11, %12, %13, %14, %15, %16, %17, %18, %19, %20, %21, %22, %23, %24, %25, %26, %27, %28, %29, %30, %31, %32, %33, %34, %35}, da, db, %39, 1, 1, 1, 1;\n}\n"
    : "+f"(d[0]), "+f"(d[1]), "+f"(d[2]), "+f"(d[3]), "+f"(d[4]), "+f"(d[5]), "+f"(d[6]), "+f"(d[7]), "+f"(d[8]), "+f"(d[9]), "+f"(d[10]), "+f"(d[11]), "+f"(d[12]), "+f"(d[13]), "+f"(d[14]), "+f"(d[15]), "+f"(d[16]), "+f"(d[17]), "+f"(d[18]), "+f"(d[19]), "+f"(d[20]), "+f"(d[21]), "+f"(d[22]), "+f"(d[23]), "+f"(d[24]), "+f"(d[25]), "+f"(d[26]), "+f"(d[27]), "+f"(d[28]), "+f"(d[29]), "+f"(d[30]), "+f"(d[31]), "+f"(d[32]), "+f"(d[33]), "+f"(d[34]), "+f"(d[35])
    : "r"(da), "r"(db), "r"(0x40000040u), "n"(SCALE_D));
}
template <int SCALE_D> __device__ __forceinline__ void wgmma_rs_n128(float (&d)[64], const uint4& a, uint32_t db) {
  asm volatile("{\n.reg .b64 db;\nmov.b64 db, {%68, %69};\n"
    "wgmma.mma_async.sync.aligned.m64n128k16.f32.bf16.bf16 {%0, %1, %2, %3, %4, %5, %6, %7, %8, %9, %10, %11, %12, %13, %14, %15, %16, %17, %18, %19, %20, %21, %22, %23, %24, %25, %26, %27, %28, %29, %30, %31, %32, %33, %34, %35, %36, %37, %38, %39, %40, %41, %42, %43, %44, %45, %46, %47, %48, %49, %50, %51, %52, %53, %54, %55, %56, %57, %58, %59, %60, %61, %62, %63}, {%64, %65, %66, %67}, db, %70, 1, 1, 1;\n}\n"
    : "+f"(d[0]), "+f"(d[1]), "+f"(d[2]), "+f"(d[3]), "+f"(d[4]), "+f"(d[5]), "+f"(d[6]), "+f"(d[7]), "+f"(d[8]), "+f"(d[9]), "+f"(d[10]), "+f"(d[11]), "+f"(d[12]), "+f"(d[13]), "+f"(d[14]), "+f"(d[15]), "+f"(d[16]), "+f"(d[17]), "+f"(d[18]), "+f"(d[19]), "+f"(d[20]), "+f"(d[21]), "+f"(d[22]), "+f"(d[23]), "+f"(d[24]), "+f"(d[25]), "+f"(d[26]), "+f"(d[27]), "+f"(d[28]), "+f"(d[29]), "+f"(d[30]), "+f"(d[31]), "+f"(d[32]), "+f"(d[33]), "+f"(d[34]), "+f"(d[35]), "+f"(d[36]), "+f"(d[37]), "+f"(d[38]), "+f"(d[39]), "+f"(d[40]), "+f"(d[41]), "+f"(d[42]), "+f"(d[43]), "+f"(d[44]), "+f"(d[45]), "+f"(d[46]), "+f"(d[47]), "+f"(d[48]), "+f"(d[49]), "+f"(d[50]), "+f"(d[51]), "+f"(d[52]), "+f"(d[53]), "+f"(d[54]), "+f"(d[55]), "+f"(d[56]), "+f"(d[57]), "+f"(d[58]), "+f"(d[59]), "+f"(d[60]), "+f"(d[61]), "+f"(d[62]), "+f"(d[63])
    : "r"(a.x), "r"(a.y), "r"(a.z), "r"(a.w), "r"(db), "r"(0x40000040u), "n"(SCALE_D));
}
template <int SCALE_D> __device__ __forceinline__ void wgmma_rs_n96(float (&d)[48], const uint4& a, uint32_t db) {
  asm volatile("{\n.reg .b64 db;\nmov.b64 db, {%52, %53};\n"
    "wgmma.mma_async.sync.aligned.m64n96k16.f32.bf16.bf16 {%0, %1, %2, %3, %4, %5, %6, %7, %8, %9, %10, %11, %12, %13, %14, %15, %16, %17, %18, %19, %20, %21, %22, %23, %24, %25, %26, %27, %28, %29, %30, %31, %32, %33, %34, %35, %36, %37, %38, %39, %40, %41, %42, %43, %44, %45, %46, %47}, {%48, %49, %50, %51}, db, %54, 1, 1, 1;\n}\n"
    : "+f"(d[0]), "+f"(d[1]), "+f"(d[2]), "+f"(d[3]), "+f"(d[4]), "+f"(d[5]), "+f"(d[6]), "+f"(d[7]), "+f"(d[8]), "+f"(d[9]), "+f"(d[10]), "+f"(d[11]), "+f"(d[12]), "+f"(d[13]), "+f"(d[14]), "+f"(d[15]), "+f"(d[16]), "+f"(d[17]), "+f"(d[18]), "+f"(d[19]), "+f"(d[20]), "+f"(d[21]), "+f"(d[22]), "+f"(d[23]), "+f"(d[24]), "+f"(d[25]), "+f"(d[26]), "+f"(d[27]), "+f"(d[28]), "+f"(d[29]), "+f"(d[30]), "+f"(d[31]), "+f"(d[32]), "+f"(d[33]), "+f"(d[34]), "+f"(d[35]), "+f"(d[36]), "+f"(d[37]), "+f"(d[38]), "+f"(d[39]), "+f"(d[40]), "+f"(d[41]), "+f"(d[42]), "+f"(d[43]), "+f"(d[44]), "+f"(d[45]), "+f"(d[46]), "+f"(d[47])
    : "r"(a.x), "r"(a.y), "r"(a.z), "r"(a.w), "r"(db), "r"(0x40000040u), "n"(SCALE_D));
}
template <int SCALE_D> __device__ __forceinline__ void wgmma_rs_n64(float (&d)[32], const uint4& a, uint32_t db) {
  asm volatile("{\n.reg .b64 db;\nmov.b64 db, {%36, %37};\n"
    "wgmma.mma_async.sync.aligned.m64n64k16.f32.bf16.bf16 {%0, %1, %2, %3, %4, %5, %6, %7, %8, %9, %10, %11, %12, %13, %14, %15, %16, %17, %18, %19, %20, %21, %22, %23, %24, %25, %26, %27, %28, %29, %30, %31}, {%32, %33, %34, %35}, db, %38, 1, 1, 1;\n}\n"
    : "+f"(d[0]), "+f"(d[1]), "+f"(d[2]), "+f"(d[3]), "+f"(d[4]), "+f"(d[5]), "+f"(d[6]), "+f"(d[7]), "+f"(d[8]), "+f"(d[9]), "+f"(d[10]), "+f"(d[11]), "+f"(d[12]), "+f"(d[13]), "+f"(d[14]), "+f"(d[15]), "+f"(d[16]), "+f"(d[17]), "+f"(d[18]), "+f"(d[19]), "+f"(d[20]), "+f"(d[21]), "+f"(d[22]), "+f"(d[23]), "+f"(d[24]), "+f"(d[25]), "+f"(d[26]), "+f"(d[27]), "+f"(d[28]), "+f"(d[29]), "+f"(d[30]), "+f"(d[31])
    : "r"(a.x), "r"(a.y), "r"(a.z), "r"(a.w), "r"(db), "r"(0x40000040u), "n"(SCALE_D));
}

constexpr float LOG2E = 1.4426950408889634f;
__device__ __forceinline__ float silu_f(float y) { return y * rcp(1.f + ex2(-y * LOG2E)); }

__device__ __forceinline__ void mish_tile(const float* c, float rs0, float rs1, float rl0, float rl1, uint4* dst) {
  float h[8], u[8], r[8];
#pragma unroll
  for (int i = 0; i < 8; i++) {
    const bool hi = (i >> 1) & 1;
    h[i] = c[i] * (hi ? rs1 : rs0);
    u[i] = ex2(fminf(c[i] * (hi ? rl1 : rl0), 28.853900817779268f));
  }
#pragma unroll
  for (int i = 0; i < 8; i++) { const float tt = u[i] + 2.f; r[i] = rcp(fmaf(u[i], tt, 2.f)); h[i] *= u[i] * tt; }
#pragma unroll
  for (int i = 0; i < 8; i++) h[i] *= r[i];
  stg_v4(dst, pack2(h[0], h[1]), pack2(h[2], h[3]), pack2(h[4], h[5]), pack2(h[6], h[7]));
}
__device__ __forceinline__ float phi_c(float c, float rs, float rl) {
  const float e = ex2(c * rl) + 1e-6f;
  const float p = fmaf(c, rs, 1.000001f);
  return c > 0.f ? p : e;
}
__device__ __forceinline__ uint4 phi_tile(const float* c, float rs0, float rs1, float rl0, float rl1) {
  uint4 r;
  r.x = pack2(phi_c(c[0], rs0, rl0), phi_c(c[1], rs0, rl0)); r.y = pack2(phi_c(c[2], rs1, rl1), phi_c(c[3], rs1, rl1));
  r.z = pack2(phi_c(c[4], rs0, rl0), phi_c(c[5], rs0, rl0)); r.w = pack2(phi_c(c[6], rs1, rl1), phi_c(c[7], rs1, rl1));
  return r;
}
template <int NB> __device__ __forceinline__ void init_bias(float* acc, uint32_t bias_addr, float ir0, float ir1) {
#pragma unroll
  for (int nb = 0; nb < NB; nb++) {
    const float2 b = lds_f32x2(bias_addr + 32 * nb);
    acc[4 * nb] = b.x * ir0; acc[4 * nb + 1] = b.y * ir0; acc[4 * nb + 2] = b.x * ir1; acc[4 * nb + 3] = b.y * ir1;
  }
}

__global__ void __launch_bounds__(384, 1)
fused_kernel(const __grid_constant__ CUtensorMap tm_x, const __grid_constant__ CUtensorMap tm_qkv,
             const __grid_constant__ CUtensorMap tm_w1, const __grid_constant__ CUtensorMap tm_w2a,
             const __grid_constant__ CUtensorMap tm_w2b, const __grid_constant__ CUtensorMap tm_wo,
             const __grid_constant__ CUtensorMap tm_out,
             const uint8_t* __restrict__ wqkv, const uint8_t* __restrict__ w1, const uint8_t* __restrict__ w2,
             const uint8_t* __restrict__ wo, const __nv_bfloat16* __restrict__ b1) {
  extern __shared__ __align__(1024) uint8_t smem_raw[];
  const uint32_t sb = smem_u32(smem_raw);
  const int tid = threadIdx.x, lane = tid & 31;
  const int warp = __shfl_sync(0xffffffffu, tid >> 5, 0);
  const int bid = blockIdx.x;
  const int G = bid >> 4, gi = bid & 15;
  const int khalf = G & 1;
  const int rb = (G >> 1) * 4 + (gi >> 2);
  const int nt = gi & 3;
  const int j = khalf + 2 * nt;
  const uint32_t bar0 = sb + OFF_BAR;
  PROF(0);

  if (warp >= 8) {
    asm volatile("setmaxnreg.dec.sync.aligned.u32 40;");
    if (warp == 8) {
      if (lane == 0) {
        if (sb & 1023u) asm volatile("trap;");
        for (int i = 0; i < NSLOT; i++) { mbar_init(bar0 + 8 * (BAR_FULL + i), 1); mbar_init(bar0 + 8 * (BAR_EMPTY + i), 8); }
        for (int i = BAR_X; i <= BAR_XT; i++) mbar_init(bar0 + 8 * i, 1);
        for (int i = BAR_PUB_A; i <= BAR_PUB_O; i++) mbar_init(bar0 + 8 * i, 8);
        for (int i = BAR_RDY_A; i <= BAR_RDY_KV; i++) mbar_init(bar0 + 8 * i, 1);
        asm volatile("fence.mbarrier_init.release.cluster;" ::: "memory");
        fence_async_smem();
        for (int i = 0; i < 4; i++) {
          mbar_expect_tx(bar0 + 8 * (BAR_X + i), 32768);
          tma2d(sb + OFF_D + (2 * i) * 16384, &tm_x, 128 * i, rb * 128, bar0 + 8 * (BAR_X + i));
          tma2d(sb + OFF_D + (2 * i + 1) * 16384, &tm_x, 128 * i + 64, rb * 128, bar0 + 8 * (BAR_X + i));
        }
      }
      __syncwarp();
      named_bar_sync(0, 384);
      if (lane == 0) {
        const int c_own = 128 * nt + 64 * khalf, c_par = 128 * nt + 64 * (1 - khalf);
#pragma unroll 1
        for (int st = 0; st < NSTAGES; st++) {
          const int slot = slot_of(st), use = use_of(st);
          const uint32_t full = bar0 + 8 * (BAR_FULL + slot);
          const uint32_t dst = sb + slot_off(slot);
          mbar_wait(bar0 + 8 * (BAR_EMPTY + slot), (use & 1) ^ (slot < 5 ? 1 : 0));
          if (st < 8) {
            mbar_expect_tx(full, 16384);
            const int k0 = 64 * st, c0 = 224 * j;
            tma2d(dst, &tm_w1, c0, k0, full);
            tma2d(dst + 8192, &tm_w1, c0 + 64, k0, full);
          } else if (st < 24) {
            mbar_expect_tx(full, 12288);
            const int k0 = 32 * (st - 8);
            tma2d(dst, &tm_qkv, 512 + 64 * j, k0, full);
            tma2d(dst + 4096, &tm_qkv, 1024 + 64 * j, k0, full);
            tma2d(dst + 8192, &tm_qkv, 64 * j, k0, full);
          } else if (st < 32) {
            mbar_expect_tx(full, 16384);
            const int k0 = 64 * (st - 24), c0 = 224 * j + 128;
            tma2d(dst, &tm_w1, c0, k0, full);
            tma2d(dst + 8192, &tm_w1, c0 + 64, k0, full);
          } else if (st < 40) {
            mbar_expect_tx(full, 16384);
            const int i = st - 32;
            const int k0 = 224 * (4 * khalf + (i >> 1)) + 64 * (i & 1);
            tma2d(dst, &tm_w2a, c_own, k0, full);
            tma2d(dst + 8192, &tm_w2a, c_par, k0, full);
          } else if (st < 48) {
            if (st == 40) {
              mbar_wait(bar0 + 8 * BAR_PUB_KV, 0);
              mbar_expect_tx(bar0 + 8 * BAR_XT, 16384);
              tma2d(sb + OFF_XT, &tm_x, c_own, rb * 128, bar0 + 8 * BAR_XT);
            }
            mbar_expect_tx(full, 12288);
            const int i = st - 40;
            const int k0 = 224 * (4 * khalf + (i >> 1)) + 128 + 48 * (i & 1);
            tma2d(dst, &tm_w2b, c_own, k0, full);
            tma2d(dst + 6144, &tm_w2b, c_par, k0, full);
          } else {
            mbar_expect_tx(full, 8192);
            tma2d(dst, &tm_wo, c_own, 64 * (st - 48), full);
          }
        }
      }
    } else {
      const int aw = warp - 9;
      unsigned dn; asm volatile("ld.relaxed.gpu.global.u32 %0, [%1];" : "=r"(dn) : "l"(&g_done) : "memory");
      named_bar_sync(0, 384);
      const unsigned ep1 = dn / NCTA + 1u;
      if (aw == 0) {
        for (int i = lane; i < 224; i += 32) sts_f32(sb + OFF_B1 + 4 * i, __bfloat162float(b1[224 * j + i]));
#pragma unroll 4
        for (int i = 0; i < 16; i++) sts_v4(sb + OFF_ONES + (i * 32 + lane) * 16, 0x3F803F80u, 0x3F803F80u, 0x3F803F80u, 0x3F803F80u);
        fence_async_smem();
        __syncwarp();
        if (lane == 0) {
          mbar_arrive(bar0 + 8 * BAR_BIAS);
          mbar_wait(bar0 + 8 * BAR_PUB_A, 0);  __threadfence(); red_inc(&g_cntA[(rb * 2 + (j >> 2)) * 8]);
          mbar_wait(bar0 + 8 * BAR_PUB_KV, 0); __threadfence(); red_inc(&g_cntKV[j * 8]);
          mbar_wait(bar0 + 8 * BAR_PUB_B, 0);  __threadfence(); red_inc(&g_cntB[(rb * 2 + (j >> 2)) * 8]);
          mbar_wait(bar0 + 8 * BAR_PUB_O, 0);  __threadfence(); red_inc(&g_cntO[rb * 8]);
        }
      } else if (aw == 1) {
        if (lane < 4) {
          const uint8_t* base = lane == 0 ? wqkv : lane == 1 ? w1 : lane == 2 ? w2 : wo;
          const uint32_t bytes = lane == 0 ? 12288u : lane == 3 ? 4096u : 14336u;
          asm volatile("cp.async.bulk.prefetch.L2.global [%0], %1;" ::"l"(base + (size_t)bid * bytes), "r"(bytes) : "memory");
        }
        __syncwarp();
        if (lane == 0) {
          poll_ge(&g_cntA[(rb * 2 + khalf) * 8], 4u * ep1); mbar_arrive(bar0 + 8 * BAR_RDY_A);
          PROF(1);
          poll_ge(&g_cntB[(rb * 2 + khalf) * 8], 4u * ep1); mbar_arrive(bar0 + 8 * BAR_RDY_B);
          PROF(2);
          poll_ge(&g_cntO[rb * 8], 8u * ep1);               mbar_arrive(bar0 + 8 * BAR_RDY_O);
          PROF(3);
        }
      } else {
        if (rb == 0) {
          float4* z = reinterpret_cast<float4*>(&g_kv[ep1 & 1][4 * j * 272]);
          for (int i = lane; i < 272; i += 32) z[i] = make_float4(0.f, 0.f, 0.f, 0.f);
        }
        const float* kvbuf = &g_kv[(ep1 & 1) ^ 1][4 * j * 272];
        mbar_wait(bar0 + 8 * BAR_PUB_KV, 0);
#pragma unroll 4
        for (int i = 0; i < 32; i++) sts_v4(sb + OFF_KVB + (i * 32 + lane) * 16, 0u, 0u, 0u, 0u);
        PROF(1);
        if (lane == 0) poll_ge(&g_cntKV[j * 8], 16u * ep1);
        __syncwarp();
        PROF(2);
        {
          const int d = lane >> 1, hf = lane & 1;
          const float* src = kvbuf + d * 16 + hf * 8;
          const uint32_t dst = sb + OFF_KVB + d * 128;
#pragma unroll
          for (int hp = 0; hp < 2; hp++) {
            uint4 v[2][2]; float zz[2];
#pragma unroll
            for (int q = 0; q < 2; q++) {
              const int hh = 2 * hp + q;
              v[q][0] = ldg_cg(src + hh * 272); v[q][1] = ldg_cg(src + hh * 272 + 4);
              asm volatile("ld.global.cg.f32 %0, [%1];" : "=f"(zz[q]) : "l"(kvbuf + hh * 272 + 256 + d) : "memory");
            }
#pragma unroll
            for (int q = 0; q < 2; q++) {
              const int hh = 2 * hp + q;
              sts_v4(dst + hh * 2048 + (((2 * hh + hf) ^ (d & 7)) << 4),
                     pack2(__uint_as_float(v[q][0].x), __uint_as_float(v[q][0].y)), pack2(__uint_as_float(v[q][0].z), __uint_as_float(v[q][0].w)),
                     pack2(__uint_as_float(v[q][1].x), __uint_as_float(v[q][1].y)), pack2(__uint_as_float(v[q][1].z), __uint_as_float(v[q][1].w)));
              const uint32_t z2 = pack2(zz[q], zz[q]);
              if (hf == 0) sts_v4(dst + 8192 + hh * 2048 + ((hh ^ (d & 7)) << 4), z2, z2, z2, z2);
            }
          }
        }
        fence_async_smem();
        __syncwarp();
        if (lane == 0) mbar_arrive(bar0 + 8 * BAR_RDY_KV);
        PROF(3);
      }
    }
  } else {
    asm volatile("setmaxnreg.inc.sync.aligned.u32 232;");
    const int wg = warp >> 2;
    const int g = lane >> 2, t = lane & 3;
    const int lr0 = warp * 16 + g;
    const int slab = rb * 8 + warp;
    unsigned dn; asm volatile("ld.relaxed.gpu.global.u32 %0, [%1];" : "=r"(dn) : "l"(&g_done) : "memory");
    const uint32_t a_lo = dlo(sb + OFF_D + wg * 8192, 16);
    const uint32_t sb_lo = sb >> 4;

#define B_LO(gs, off, lbo) (sb_lo + ((slot_off(slot_of(gs)) + (off)) >> 4) + (((lbo) >> 4) << 16))
#define STAGE_BEGIN(gs) do { mbar_wait(bar0 + 8 * (BAR_FULL + slot_of(gs)), use_of(gs) & 1); wg_fence(); } while (0)
#define RELEASE_SLOT(sl) do { if (lane == 0) mbar_arrive(bar0 + 8 * (BAR_EMPTY + (sl))); } while (0)
#define STAGE_END(prev) do { wg_commit(); wg_wait<1>(); if ((prev) >= 0 && (prev) < 46) RELEASE_SLOT(slot_of((prev) < 0 ? 0 : (prev))); } while (0)
#define WARP_ARRIVE(b) do { __syncwarp(); if (lane == 0) mbar_arrive(bar0 + 8 * (b)); } while (0)

    uint4* act_out = g_act + (size_t)(slab * 112 + 14 * j) * 32 + lane;
    const uint32_t bias_addr = sb + OFF_B1 + 8 * t;
    float rs0, rs1;
    float pool[160];
    float (&acca)[64] = reinterpret_cast<float (&)[64]>(pool[0]);
    float (&accq)[96] = reinterpret_cast<float (&)[96]>(pool[64]);
    float (&accb)[48] = reinterpret_cast<float (&)[48]>(pool[0]);
    float (&accy)[64] = reinterpret_cast<float (&)[64]>(pool[64]);
    float (&accs)[32] = reinterpret_cast<float (&)[32]>(pool[0]);
    float rl0, rl1, ir0, ir1;
    {
      uint4 q[16], p[16];
      const int par = g & 1;
      const uint32_t rowa = sb + OFF_D + lr0 * 128;
      const uint32_t u0 = (uint32_t)(((par * 4 + t) ^ g) << 4), u1 = u0 ^ 64u;
      named_bar_sync(0, 384);
      float sm[2][4], ga[2][4], gb[2][4];
#pragma unroll
      for (int a = 0; a < 2; a++) {
        sm[a][0] = sm[a][1] = sm[a][2] = sm[a][3] = 0.f;
        ga[a][0] = ga[a][1] = ga[a][2] = ga[a][3] = 0.f;
        gb[a][0] = gb[a][1] = gb[a][2] = gb[a][3] = 0.f;
      }
      const uint32_t ones = 0x3F803F80u;
#pragma unroll
      for (int c = 0; c < 8; c++) {
        if ((c & 1) == 0) mbar_wait(bar0 + 8 * (BAR_X + (c >> 1)), 0);
        q[2 * c] = lds_v4(rowa + c * 16384 + u0);     p[2 * c] = lds_v4(rowa + c * 16384 + 1024 + u0);
        q[2 * c + 1] = lds_v4(rowa + c * 16384 + u1); p[2 * c + 1] = lds_v4(rowa + c * 16384 + 1024 + u1);
#pragma unroll
        for (int h = 0; h < 2; h++) {
          const int i = 2 * c + h;
          mma16816(sm[0], q[i].x, p[i].x, q[i].y, p[i].y, ones, ones);
          mma16816(sm[1], q[i].z, p[i].z, q[i].w, p[i].w, ones, ones);
          mma16816(ga[0], q[i].x, p[i].x, q[i].y, p[i].y, q[i].x, q[i].y);
          mma16816(ga[1], q[i].z, p[i].z, q[i].w, p[i].w, q[i].z, q[i].w);
          mma16816(gb[0], q[i].x, p[i].x, q[i].y, p[i].y, p[i].x, p[i].y);
          mma16816(gb[1], q[i].z, p[i].z, q[i].w, p[i].w, p[i].z, p[i].w);
        }
      }
      const float m0 = (sm[0][0] + sm[1][0]) * (1.f / DM);
      const float m1 = (sm[0][2] + sm[1][2]) * (1.f / DM);
      const uint32_t mb0 = pack2(m0, m0), mb1 = pack2(m1, m1);
      PROF(12);
#pragma unroll
      for (int i = 0; i < 16; i++) {
        const uint32_t off = (uint32_t)(i >> 1) * 16384 + ((i & 1) ? u1 : u0);
        sts_v4(rowa + off, hsub2_bf16(q[i].x, mb0), hsub2_bf16(q[i].y, mb0), hsub2_bf16(q[i].z, mb0), hsub2_bf16(q[i].w, mb0));
        sts_v4(rowa + 1024 + off, hsub2_bf16(p[i].x, mb1), hsub2_bf16(p[i].y, mb1), hsub2_bf16(p[i].z, mb1), hsub2_bf16(p[i].w, mb1));
      }
      fence_async_smem();
      float d0 = par ? ga[0][1] + ga[1][1] : ga[0][0] + ga[1][0];
      float d1 = par ? gb[0][3] + gb[1][3] : gb[0][2] + gb[1][2];
      d0 = __shfl_sync(0xffffffffu, d0, (lane & ~3) | (g >> 1));
      d1 = __shfl_sync(0xffffffffu, d1, (lane & ~3) | (g >> 1));
      const float v0 = fmaxf(d0 * (1.f / DM) - m0 * m0, 0.f) + 1e-5f;
      const float v1 = fmaxf(d1 * (1.f / DM) - m1 * m1, 0.f) + 1e-5f;
      rs0 = rsqrtf(v0); rs1 = rsqrtf(v1);
      ir0 = v0 * rs0; ir1 = v1 * rs1;
      rl0 = rs0 * LOG2E; rl1 = rs1 * LOG2E;
      mbar_wait(bar0 + 8 * BAR_BIAS, 0);
      init_bias<16>(acca, bias_addr, ir0, ir1);
      named_bar_sync(1 + wg, 128);
      PROF(1);
    }
#pragma unroll
    for (int st = 0; st < 8; st++) {
      STAGE_BEGIN(st);
#pragma unroll
      for (int kk = 0; kk < 4; kk++) wgmma_ss_n128<1>(acca, a_lo + ((st * 16384 + kk * 32) >> 4), B_LO(st, kk * 2048, 8192));
      STAGE_END(st - 1);
      if (st == 0) zero_regs(accq);
    }
    PROF(2);
#pragma unroll
    for (int st = 0; st < 16; st++) {
      const int gs = 8 + st;
      STAGE_BEGIN(gs);
      const uint32_t as = a_lo + (((st >> 1) * 16384 + (st & 1) * 64) >> 4);
      wgmma_ss_n192<1>(accq, as, B_LO(gs, 0, 4096));
      wgmma_ss_n192<1>(accq, as + 2, B_LO(gs, 2048, 4096));
      STAGE_END(gs - 1);
      if (st == 0) fence_regs(acca);
      if (st < 8) mish_tile(acca + 8 * st, rs0, rs1, rl0, rl1, act_out + st * 32);
      if (st == 7) { WARP_ARRIVE(BAR_PUB_A); PROF(3); }
      if (st == 8) init_bias<12>(accb, bias_addr + 512, ir0, ir1);
    }
    PROF(4);
    const uint4* act_in = g_act + (size_t)(slab * 112 + 56 * khalf) * 32 + lane;
    const uint4* o_in = g_o + (size_t)(slab * 32) * 32 + lane;
    uint4 ab[4][4];
    auto load_a = [&](int rs) {
      if (rs < 8) {
        const int kt = 14 * (rs >> 1) + 4 * (rs & 1);
#pragma unroll
        for (int kk = 0; kk < 4; kk++) ab[rs & 3][kk] = ldg_cg(act_in + (kt + kk) * 32);
      } else if (rs < 16) {
        const int kt = 14 * ((rs - 8) >> 1) + 8 + 3 * (rs & 1);
#pragma unroll
        for (int kk = 0; kk < 3; kk++) ab[rs & 3][kk] = ldg_cg(act_in + (kt + kk) * 32);
      } else if (rs < 24) {
#pragma unroll
        for (int kk = 0; kk < 4; kk++) ab[rs & 3][kk] = ldg_cg(o_in + (4 * (rs - 16) + kk) * 32);
      }
    };
    auto keep_a = [&](int rs) {
#pragma unroll
      for (int kk = 0; kk < 4; kk++) if (!(rs >= 8 && rs < 16 && kk == 3)) fence_u4(ab[rs & 3][kk]);
    };
    uint4 pq[4];
    const unsigned ep1 = dn / NCTA + 1u;
    {
      const int m = lane >> 3, rr = lane & 7;
      const uint32_t srow = sb + OFF_D + (warp * 16 + (m & 1) * 8 + rr) * 128;
      const uint32_t ka = dlo(sb + OFF_PK + wg * 8192, 16);
      const uint32_t vb = dlo(sb + OFF_V + wg * 8192, OFF_ONES - (OFF_V + wg * 8192));
      float (&acck)[36] = reinterpret_cast<float (&)[36]>(pool[64]);
#pragma unroll
      for (int st = 0; st < 8; st++) {
        const int gs = 24 + st;
        STAGE_BEGIN(gs);
#pragma unroll
        for (int kk = 0; kk < 4; kk++) wgmma_ss_n96<1>(accb, a_lo + ((st * 16384 + kk * 32) >> 4), B_LO(gs, kk * 2048, 8192));
        if (st == 3) {
          wgmma_tt_n72<0>(acck, ka, vb);
#pragma unroll
          for (int kk = 1; kk < 4; kk++) wgmma_tt_n72<1>(acck, ka + kk * 128, vb + kk * 128);
        }
        STAGE_END(gs - 1);
        if (st >= 4) RELEASE_SLOT(5 + (st - 1) - 3);
        if (st == 0) {
          fence_regs(accq);
          pq[0] = phi_tile(accq + 64, rs0, rs1, rl0, rl1); pq[1] = phi_tile(accq + 72, rs0, rs1, rl0, rl1);
          pq[2] = phi_tile(accq + 80, rs0, rs1, rl0, rl1); pq[3] = phi_tile(accq + 88, rs0, rs1, rl0, rl1);
        } else if (st == 1) {
#pragma unroll
          for (int i = 0; i < 4; i++) {
            const uint4 r = phi_tile(accq + 8 * i, rs0, rs1, rl0, rl1);
            stmatrix_x4(srow + OFF_PK + (((2 * i + (m >> 1)) ^ rr) << 4), r.x, r.y, r.z, r.w);
          }
        } else if (st == 2) {
#pragma unroll
          for (int i = 0; i < 4; i++) {
            const float* c = accq + 32 + 8 * i;
            stmatrix_x4(srow + OFF_V + (((2 * i + (m >> 1)) ^ rr) << 4),
                        pack2(c[0] * rs0, c[1] * rs0), pack2(c[2] * rs1, c[3] * rs1), pack2(c[4] * rs0, c[5] * rs0), pack2(c[6] * rs1, c[7] * rs1));
          }
          fence_async_smem();
          named_bar_sync(1 + wg, 128);
        } else if (st == 4) {
          fence_regs(acck);
          const int wq = warp & 3;
          float* hb = &g_kv[(ep1 & 1) ^ 1][(4 * j + wq) * 272];
          float* a0p = hb + g * 16 + 2 * t;
#pragma unroll
          for (int w = 0; w < 4; w++) {
            if (wq == w) {
              red_add_v2(a0p, acck[8 * w], acck[8 * w + 1]); red_add_v2(a0p + 128, acck[8 * w + 2], acck[8 * w + 3]);
              red_add_v2(a0p + 8, acck[8 * w + 4], acck[8 * w + 5]); red_add_v2(a0p + 136, acck[8 * w + 6], acck[8 * w + 7]);
            }
          }
          if (t == 0) { red_add_f32(hb + 256 + g, acck[32]); red_add_f32(hb + 264 + g, acck[34]); }
          WARP_ARRIVE(BAR_PUB_KV);
        } else if (st == 5) {
          mbar_wait(bar0 + 8 * BAR_RDY_A, 0);
          load_a(0); load_a(1); load_a(2);
        }
      }
    }
    PROF(5);
#pragma unroll
    for (int st = 0; st < 8; st++) {
      const int gs = 32 + st;
      STAGE_BEGIN(gs);
#pragma unroll
      for (int kk = 0; kk < 4; kk++) {
        if (st == 0 && kk == 0) wgmma_rs_n128<0>(accy, ab[st & 3][kk], B_LO(gs, kk * 2048, 8192));
        else wgmma_rs_n128<1>(accy, ab[st & 3][kk], B_LO(gs, kk * 2048, 8192));
      }
      if (st == 7) {
        mbar_wait(bar0 + 8 * BAR_RDY_KV, 0);
        PROF(7);
        const uint32_t kb = dlo(sb + OFF_KVB, 8192);
        wgmma_rs_n96<0>(accb, pq[0], kb);
#pragma unroll
        for (int kk = 1; kk < 4; kk++) wgmma_rs_n96<1>(accb, pq[kk], kb + kk * 128);
      }
      STAGE_END(gs - 1);
      if (st == 0) { RELEASE_SLOT(9); fence_regs(accb); }
      else keep_a(st - 1);
      if (st == 5) mbar_wait(bar0 + 8 * BAR_RDY_B, 0);
      load_a(st + 3);
      if (st < 2) {
#pragma unroll
        for (int i = 3 * st; i < 3 * st + 3; i++)
          mish_tile(accb + 8 * i, rs0, rs1, rl0, rl1, act_out + (8 + i) * 32);
        if (st == 1) WARP_ARRIVE(BAR_PUB_B);
      }
      PROF(13 + st);
    }
    PROF(6);
#pragma unroll
    for (int st = 0; st < 8; st++) {
      const int gs = 40 + st, rs = 8 + st;
      STAGE_BEGIN(gs);
#pragma unroll
      for (int kk = 0; kk < 3; kk++) wgmma_rs_n128<1>(accy, ab[rs & 3][kk], B_LO(gs, kk * 2048, 6144));
      STAGE_END(gs - 1);
      keep_a(rs - 1);
      if (st == 0) {
        fence_regs(accb);
#pragma unroll
        for (int kk = 0; kk < 4; kk++) fence_u4(pq[kk]);
        uint4* o_out = g_o + (size_t)(slab * 32 + 4 * j) * 32 + lane;
#pragma unroll
        for (int hh = 0; hh < 4; hh++) {
          const float i0 = __fdividef(1.f, accb[32 + 4 * hh] + 1e-6f), i1 = __fdividef(1.f, accb[34 + 4 * hh] + 1e-6f);
          const float* n = accb + 8 * hh;
          stg_v4(o_out + hh * 32, pack2(n[0] * i0, n[1] * i0), pack2(n[2] * i1, n[3] * i1), pack2(n[4] * i0, n[5] * i0), pack2(n[6] * i1, n[7] * i1));
        }
        WARP_ARRIVE(BAR_PUB_O);
      }
      if (st == 5) mbar_wait(bar0 + 8 * BAR_RDY_O, 0);
      load_a(rs + 3);
    }
    PROF(8);
    const uint32_t tag = ep1 & 1u;
#pragma unroll
    for (int st = 0; st < 8; st++) {
      const int gs = 48 + st, rs = 16 + st;
      STAGE_BEGIN(gs);
#pragma unroll
      for (int kk = 0; kk < 4; kk++) {
        if (st == 0 && kk == 0) wgmma_rs_n64<0>(accs, ab[rs & 3][kk], B_LO(gs, kk * 2048, 8192));
        else wgmma_rs_n64<1>(accs, ab[rs & 3][kk], B_LO(gs, kk * 2048, 8192));
      }
      STAGE_END(gs - 1);
      keep_a(rs - 1);
      load_a(rs + 3);
      if (st == 0) {
        fence_regs(accy);
        float4* yp = g_yp + (size_t)((bid * 8 + warp) * 8) * 32 + lane;
#pragma unroll
        for (int q = 0; q < 8; q++) {
          const uint32_t v0 = (__float_as_uint(accy[32 + 4 * q]) & ~1u) | tag, v1 = (__float_as_uint(accy[33 + 4 * q]) & ~1u) | tag;
          const uint32_t v2 = (__float_as_uint(accy[34 + 4 * q]) & ~1u) | tag, v3 = (__float_as_uint(accy[35 + 4 * q]) & ~1u) | tag;
          asm volatile("st.relaxed.gpu.global.v4.u32 [%0], {%1,%2,%3,%4};" ::"l"(yp + q * 32), "r"(v0), "r"(v1), "r"(v2), "r"(v3) : "memory");
        }
      }
      PROF(21 + st);
    }
    PROF(9);
    {
      const float4* yp = g_yp + (size_t)(((bid ^ 16) * 8 + warp) * 8) * 32 + lane;
      uint4 pv[8];
      uint32_t it = 0;
      wg_wait<0>();
      keep_a(23);
      fence_regs(accs);
      while (true) {
        uint32_t bad = 0;
#pragma unroll
        for (int q = 0; q < 8; q++)
          asm volatile("ld.relaxed.gpu.global.v4.u32 {%0,%1,%2,%3}, [%4];" : "=r"(pv[q].x), "=r"(pv[q].y), "=r"(pv[q].z), "=r"(pv[q].w) : "l"(yp + q * 32) : "memory");
#pragma unroll
        for (int q = 0; q < 8; q++) bad |= (pv[q].x ^ tag) | (pv[q].y ^ tag) | (pv[q].z ^ tag) | (pv[q].w ^ tag);
        if (!__any_sync(0xffffffffu, bad & 1u)) break;
        if (++it > (1u << 20)) asm volatile("trap;");
      }
      PROF(10);
      mbar_wait(bar0 + 8 * BAR_XT, 0);
      const uint32_t xa = sb + OFF_XT + lr0 * 128 + 4 * t;
#pragma unroll
      for (int q = 0; q < 8; q++) {
        const uint32_t a0 = xa + ((q ^ g) << 4), a1 = a0 + 1024;
        const uint32_t x0 = lds_u32(a0), x1 = lds_u32(a1);
        const float y0 = accy[4 * q] + __uint_as_float(pv[q].x), y1 = accy[4 * q + 1] + __uint_as_float(pv[q].y);
        const float y2 = accy[4 * q + 2] + __uint_as_float(pv[q].z), y3 = accy[4 * q + 3] + __uint_as_float(pv[q].w);
        const float o0 = fmaf(accs[4 * q], silu_f(y0), bf_lo(x0)), o1 = fmaf(accs[4 * q + 1], silu_f(y1), bf_hi(x0));
        const float o2 = fmaf(accs[4 * q + 2], silu_f(y2), bf_lo(x1)), o3 = fmaf(accs[4 * q + 3], silu_f(y3), bf_hi(x1));
        sts_u32(a0, pack2(o0, o1));
        sts_u32(a1, pack2(o2, o3));
      }
      fence_async_smem();
      __syncwarp();
      if (lane == 0) {
        asm volatile("cp.async.bulk.tensor.2d.global.shared::cta.bulk_group [%0, {%2, %3}], [%1];"
                     ::"l"(&tm_out), "r"(sb + OFF_XT + warp * 2048), "r"(128 * nt + 64 * khalf), "r"(rb * 128 + warp * 16) : "memory");
        asm volatile("cp.async.bulk.commit_group;" ::: "memory");
        asm volatile("cp.async.bulk.wait_group.read 0;" ::: "memory");
      }
    }
    PROF(11);
    if (tid == 0) red_inc(&g_done);
  }
}

typedef CUresult (*EncodeFn)(CUtensorMap*, CUtensorMapDataType, cuuint32_t, void*, const cuuint64_t*, const cuuint64_t*,
                             const cuuint32_t*, const cuuint32_t*, CUtensorMapInterleave, CUtensorMapSwizzle,
                             CUtensorMapL2promotion, CUtensorMapFloatOOBfill);

void make_map(EncodeFn enc, CUtensorMap* tm, const void* ptr, int rows, int cols, int box_rows) {
  cuuint64_t gd[2] = {(cuuint64_t)cols, (cuuint64_t)rows};
  cuuint64_t gs[1] = {(cuuint64_t)cols * 2};
  cuuint32_t bd[2] = {64, (cuuint32_t)box_rows};
  cuuint32_t es[2] = {1, 1};
  enc(tm, CU_TENSOR_MAP_DATA_TYPE_BFLOAT16, 2, const_cast<void*>(ptr), gd, gs, bd, es, CU_TENSOR_MAP_INTERLEAVE_NONE,
      CU_TENSOR_MAP_SWIZZLE_128B, CU_TENSOR_MAP_L2_PROMOTION_L2_128B, CU_TENSOR_MAP_FLOAT_OOB_FILL_NONE);
}

}

extern "C" void kernel_launch(void* const* d_in, const int* in_sizes, int n_in, void* d_out, int out_size) {
  const __nv_bfloat16* x = (const __nv_bfloat16*)d_in[0];
  const void* wqkv = d_in[1];
  const void* wo = d_in[2];
  const void* w1 = d_in[4];
  const __nv_bfloat16* b1 = (const __nv_bfloat16*)d_in[5];
  const void* w2 = d_in[6];
  static EncodeFn enc = nullptr;
  if (!enc) {
    cudaDriverEntryPointQueryResult qr;
    void* fn = nullptr;
    cudaGetDriverEntryPoint("cuTensorMapEncodeTiled", &fn, cudaEnableDefault, &qr);
    enc = (EncodeFn)fn;
    cudaFuncSetAttribute(fused_kernel, cudaFuncAttributeMaxDynamicSharedMemorySize, SMEM_ALLOC);
  }
  CUtensorMap tx, tq, t1, t2a, t2b, to, tout;
  make_map(enc, &tx, x, 2048, DM, 128);
  make_map(enc, &tq, wqkv, DM, 3 * DM, 32);
  make_map(enc, &t1, w1, DM, FF, 64);
  make_map(enc, &t2a, w2, FF, DM, 64);
  make_map(enc, &t2b, w2, FF, DM, 48);
  make_map(enc, &to, wo, DM, DM, 64);
  make_map(enc, &tout, d_out, 2048, DM, 16);
  fused_kernel<<<NCTA, 384, SMEM_ALLOC>>>(tx, tq, t1, t2a, t2b, to, tout, (const uint8_t*)wqkv, (const uint8_t*)w1,
                                          (const uint8_t*)w2, (const uint8_t*)wo, b1);
}
```

```cpp
#include <cuda_runtime.h>
#include <cuda_bf16.h>
#include <cuda.h>
#include <stdint.h>

namespace {

constexpr int DM = 512, FF = 1792;
constexpr int NCTA = 128;
constexpr int NRING = 5;
constexpr int NSLOT = 10;
constexpr int SLOT_BYTES = 16384;
constexpr int OFF_D = 0;
constexpr int OFF_PK = 0, OFF_V = 16384;
constexpr int OFF_KVB = 0;
constexpr int OFF_XT = 16384;
constexpr int OFF_RING = 131072;
constexpr int OFF_MISC = OFF_RING + NRING * SLOT_BYTES;
constexpr int OFF_ONES = OFF_MISC;
constexpr int OFF_BAR = OFF_MISC + 8192;
constexpr int OFF_B1 = OFF_MISC + 8704;
constexpr int SMEM_ALLOC = OFF_MISC + 9728;

enum { BAR_FULL = 0, BAR_EMPTY = NSLOT, BAR_X = 2 * NSLOT, BAR_BIAS = BAR_X + 4, BAR_XT,
       BAR_PUB_A, BAR_PUB_KV, BAR_PUB_B, BAR_PUB_O,
       BAR_RDY_A, BAR_RDY_B, BAR_RDY_O, BAR_RDY_KV, BAR_COUNT };
static_assert(BAR_COUNT <= 40, "too many barriers");

constexpr int NSTAGES = 56;
__host__ __device__ constexpr int slot_of(int gs) {
  if (gs < 32) return gs % 5;
  const int p = (gs - 32) % 10;
  return p < 5 ? 5 + p : (p - 3) % 5;
}
__host__ __device__ constexpr int use_of(int gs) {
  if (gs < 32) return gs / 5;
  const int sl = slot_of(gs);
  return (gs - 32) / 10 + (sl < 5 ? (sl < 2 ? 7 : 6) : 0);
}
__host__ __device__ constexpr int slot_off(int sl) { return sl < 5 ? OFF_RING + sl * SLOT_BYTES : OFF_D + (sl - 2) * SLOT_BYTES; }

__device__ uint4 g_act[128 * 112 * 32];
__device__ uint4 g_o[128 * 32 * 32];
__device__ float4 g_yp[NCTA * 8 * 8 * 32];
__device__ float g_kv[2][32 * 272];
__device__ unsigned g_cntA[16 * 2 * 8];
__device__ unsigned g_cntB[16 * 2 * 8];
__device__ unsigned g_cntO[16 * 8];
__device__ unsigned g_cntKV[8 * 8];
__device__ unsigned g_done;

#define PROF(i)

__device__ __forceinline__ uint32_t smem_u32(const void* p) { return (uint32_t)__cvta_generic_to_shared(p); }
__device__ __forceinline__ void mbar_init(uint32_t bar, uint32_t cnt) { asm volatile("mbarrier.init.shared::cta.b64 [%0], %1;" ::"r"(bar), "r"(cnt)); }
__device__ __forceinline__ void mbar_expect_tx(uint32_t bar, uint32_t bytes) { asm volatile("mbarrier.arrive.expect_tx.shared::cta.b64 _, [%0], %1;" ::"r"(bar), "r"(bytes) : "memory"); }
__device__ __forceinline__ void mbar_arrive(uint32_t bar) { asm volatile("mbarrier.arrive.shared::cta.b64 _, [%0];" ::"r"(bar) : "memory"); }
__device__ __forceinline__ void mbar_wait(uint32_t bar, uint32_t parity) {
  asm volatile("{\n.reg .pred P1;\n.reg .u32 cnt;\n"
               "mbarrier.try_wait.parity.shared::cta.b64 P1, [%0], %1;\n@P1 bra DONE;\n"
               "mov.u32 cnt, 0;\n"
               "LAB_WAIT:\n"
               "mbarrier.try_wait.parity.shared::cta.b64 P1, [%0], %1;\n@P1 bra DONE;\n"
               "add.u32 cnt, cnt, 1;\nsetp.lt.u32 P1, cnt, 16777216;\n@P1 bra LAB_WAIT;\ntrap;\n"
               "DONE:\n}" ::"r"(bar), "r"(parity) : "memory");
}
__device__ __forceinline__ void tma2d(uint32_t dst, const CUtensorMap* tm, int c0, int c1, uint32_t bar) {
  asm volatile("cp.async.bulk.tensor.2d.shared::cluster.global.mbarrier::complete_tx::bytes [%0], [%1, {%3, %4}], [%2];" ::"r"(dst), "l"(tm), "r"(bar), "r"(c0), "r"(c1) : "memory");
}
__device__ __forceinline__ void wg_fence() { asm volatile("wgmma.fence.sync.aligned;" ::: "memory"); }
__device__ __forceinline__ void wg_commit() { asm volatile("wgmma.commit_group.sync.aligned;" ::: "memory"); }
template <int N> __device__ __forceinline__ void wg_wait() { asm volatile("wgmma.wait_group.sync.aligned %0;" ::"n"(N) : "memory"); }
template <int N> __device__ __forceinline__ void zero_regs(float (&d)[N]) {
#pragma unroll
  for (int i = 0; i < N; i++) d[i] = 0.f;
}
template <int N> __device__ __forceinline__ void fence_regs(float (&d)[N]) {
#pragma unroll
  for (int i = 0; i < N; i++) asm volatile("" : "+f"(d[i])::"memory");
}
__device__ __forceinline__ void fence_u4(uint4& v) { asm volatile("" : "+r"(v.x), "+r"(v.y), "+r"(v.z), "+r"(v.w)::"memory"); }
__device__ __forceinline__ void named_bar_sync(int id, int n) { asm volatile("bar.sync %0, %1;" ::"r"(id), "r"(n) : "memory"); }
__device__ __forceinline__ void fence_gpu() { asm volatile("fence.acq_rel.gpu;" ::: "memory"); }
__device__ __forceinline__ void fence_async_smem() { asm volatile("fence.proxy.async.shared::cta;" ::: "memory"); }
__device__ __forceinline__ constexpr uint32_t dlo(uint32_t addr, uint32_t lbo_bytes) { return ((addr & 0x3FFFFu) >> 4) | ((lbo_bytes >> 4) << 16); }
__device__ __forceinline__ void mma16816(float (&c)[4], uint32_t a0, uint32_t a1, uint32_t a2, uint32_t a3, uint32_t b0, uint32_t b1) {
  asm volatile("mma.sync.aligned.m16n8k16.row.col.f32.bf16.bf16.f32 {%0,%1,%2,%3}, {%4,%5,%6,%7}, {%8,%9}, {%0,%1,%2,%3};"
               : "+f"(c[0]), "+f"(c[1]), "+f"(c[2]), "+f"(c[3]) : "r"(a0), "r"(a1), "r"(a2), "r"(a3), "r"(b0), "r"(b1));
}
__device__ __forceinline__ void stmatrix_x4(uint32_t addr, uint32_t a, uint32_t b, uint32_t c, uint32_t d) {
  asm volatile("stmatrix.sync.aligned.m8n8.x4.shared.b16 [%0], {%1,%2,%3,%4};" ::"r"(addr), "r"(a), "r"(b), "r"(c), "r"(d) : "memory");
}
__device__ __forceinline__ uint32_t pack2(float lo, float hi) { uint32_t r; asm("cvt.rn.bf16x2.f32 %0, %1, %2;" : "=r"(r) : "f"(hi), "f"(lo)); return r; }
__device__ __forceinline__ float ex2(float x) { float r; asm("ex2.approx.ftz.f32 %0, %1;" : "=f"(r) : "f"(x)); return r; }
__device__ __forceinline__ float rcp(float x) { float r; asm("rcp.approx.ftz.f32 %0, %1;" : "=f"(r) : "f"(x)); return r; }
__device__ __forceinline__ float bf_lo(uint32_t v) { return __uint_as_float(v << 16); }
__device__ __forceinline__ float bf_hi(uint32_t v) { return __uint_as_float(v & 0xffff0000u); }
__device__ __forceinline__ uint32_t hsub2_bf16(uint32_t a, uint32_t b) {
  __nv_bfloat162 x = *reinterpret_cast<__nv_bfloat162*>(&a), y = *reinterpret_cast<__nv_bfloat162*>(&b);
  __nv_bfloat162 r = __hsub2(x, y);
  return *reinterpret_cast<uint32_t*>(&r);
}
__device__ __forceinline__ uint4 ldg_cg(const void* p) {
  uint4 v; asm volatile("ld.global.cg.v4.u32 {%0,%1,%2,%3}, [%4];" : "=r"(v.x), "=r"(v.y), "=r"(v.z), "=r"(v.w) : "l"(p) : "memory"); return v;
}
__device__ __forceinline__ void stg_v4(void* p, uint32_t a, uint32_t b, uint32_t c, uint32_t d) {
  asm volatile("st.global.v4.u32 [%0], {%1,%2,%3,%4};" ::"l"(p), "r"(a), "r"(b), "r"(c), "r"(d) : "memory");
}
__device__ __forceinline__ void sts_v4(uint32_t addr, uint32_t a, uint32_t b, uint32_t c, uint32_t d) {
  asm volatile("st.shared.v4.u32 [%0], {%1,%2,%3,%4};" ::"r"(addr), "r"(a), "r"(b), "r"(c), "r"(d) : "memory");
}
__device__ __forceinline__ void sts_f32(uint32_t addr, float v) { asm volatile("st.shared.f32 [%0], %1;" ::"r"(addr), "f"(v) : "memory"); }
__device__ __forceinline__ uint4 lds_v4(uint32_t addr) { uint4 v; asm volatile("ld.shared.v4.u32 {%0,%1,%2,%3}, [%4];" : "=r"(v.x), "=r"(v.y), "=r"(v.z), "=r"(v.w) : "r"(addr) : "memory"); return v; }
__device__ __forceinline__ uint32_t lds_u32(uint32_t addr) { uint32_t v; asm volatile("ld.shared.u32 %0, [%1];" : "=r"(v) : "r"(addr) : "memory"); return v; }
__device__ __forceinline__ void sts_u32(uint32_t addr, uint32_t v) { asm volatile("st.shared.u32 [%0], %1;" ::"r"(addr), "r"(v) : "memory"); }
__device__ __forceinline__ float2 lds_f32x2(uint32_t addr) { float2 v; asm volatile("ld.shared.v2.f32 {%0,%1}, [%2];" : "=f"(v.x), "=f"(v.y) : "r"(addr) : "memory"); return v; }
__device__ __forceinline__ void red_add_v2(float* p, float a, float b) { asm volatile("red.relaxed.gpu.global.add.v2.f32 [%0], {%1,%2};" ::"l"(p), "f"(a), "f"(b) : "memory"); }
__device__ __forceinline__ void red_add_f32(float* p, float a) { asm volatile("red.relaxed.gpu.global.add.f32 [%0], %1;" ::"l"(p), "f"(a) : "memory"); }
__device__ __forceinline__ void red_inc(unsigned* cnt) { asm volatile("red.relaxed.gpu.global.add.u32 [%0], 1;" ::"l"(cnt) : "memory"); }
__device__ __forceinline__ void poll_ge(const unsigned* cnt, unsigned target) {
  asm volatile("{\n.reg .pred P1;\n.reg .u32 cnt, v;\n.reg .s32 d;\n"
               "mov.u32 cnt, 0;\n"
               "LAB_POLL:\n"
               "ld.relaxed.gpu.global.u32 v, [%0];\nsub.s32 d, v, %1;\nsetp.ge.s32 P1, d, 0;\n@P1 bra DONE;\n"
               "add.u32 cnt, cnt, 1;\nsetp.lt.u32 P1, cnt, 4194304;\n@P1 bra LAB_POLL;\ntrap;\n"
               "DONE:\nfence.acq_rel.gpu;\n}" ::"l"(cnt), "r"(target) : "memory");
}

template <int SCALE_D> __device__ __forceinline__ void wgmma_ss_n192(float (&d)[96], uint32_t da, uint32_t db) {
  asm volatile("{\n.reg .b64 da, db;\nmov.b64 da, {%96, %98};\nmov.b64 db, {%97, %98};\n"
    "wgmma.mma_async.sync.aligned.m64n192k16.f32.bf16.bf16 {%0, %1, %2, %3, %4, %5, %6, %7, %8, %9, %10, %11, %12, %13, %14, %15, %16, %17, %18, %19, %20, %21, %22, %23, %24, %25, %26, %27, %28, %29, %30, %31, %32, %33, %34, %35, %36, %37, %38, %39, %40, %41, %42, %43, %44, %45, %46, %47, %48, %49, %50, %51, %52, %53, %54, %55, %56, %57, %58, %59, %60, %61, %62, %63, %64, %65, %66, %67, %68, %69, %70, %71, %72, %73, %74, %75, %76, %77, %78, %79, %80, %81, %82, %83, %84, %85, %86, %87, %88, %89, %90, %91, %92, %93, %94, %95}, da, db, %99, 1, 1, 0, 1;\n}\n"
    : "+f"(d[0]), "+f"(d[1]), "+f"(d[2]), "+f"(d[3]), "+f"(d[4]), "+f"(d[5]), "+f"(d[6]), "+f"(d[7]), "+f"(d[8]), "+f"(d[9]), "+f"(d[10]), "+f"(d[11]), "+f"(d[12]), "+f"(d[13]), "+f"(d[14]), "+f"(d[15]), "+f"(d[16]), "+f"(d[17]), "+f"(d[18]), "+f"(d[19]), "+f"(d[20]), "+f"(d[21]), "+f"(d[22]), "+f"(d[23]), "+f"(d[24]), "+f"(d[25]), "+f"(d[26]), "+f"(d[27]), "+f"(d[28]), "+f"(d[29]), "+f"(d[30]), "+f"(d[31]), "+f"(d[32]), "+f"(d[33]), "+f"(d[34]), "+f"(d[35]), "+f"(d[36]), "+f"(d[37]), "+f"(d[38]), "+f"(d[39]), "+f"(d[40]), "+f"(d[41]), "+f"(d[42]), "+f"(d[43]), "+f"(d[44]), "+f"(d[45]), "+f"(d[46]), "+f"(d[47]), "+f"(d[48]), "+f"(d[49]), "+f"(d[50]), "+f"(d[51]), "+f"(d[52]), "+f"(d[53]), "+f"(d[54]), "+f"(d[55]), "+f"(d[56]), "+f"(d[57]), "+f"(d[58]), "+f"(d[59]), "+f"(d[60]), "+f"(d[61]), "+f"(d[62]), "+f"(d[63]), "+f"(d[64]), "+f"(d[65]), "+f"(d[66]), "+f"(d[67]), "+f"(d[68]), "+f"(d[69]), "+f"(d[70]), "+f"(d[71]), "+f"(d[72]), "+f"(d[73]), "+f"(d[74]), "+f"(d[75]), "+f"(d[76]), "+f"(d[77]), "+f"(d[78]), "+f"(d[79]), "+f"(d[80]), "+f"(d[81]), "+f"(d[82]), "+f"(d[83]), "+f"(d[84]), "+f"(d[85]), "+f"(d[86]), "+f"(d[87]), "+f"(d[88]), "+f"(d[89]), "+f"(d[90]), "+f"(d[91]), "+f"(d[92]), "+f"(d[93]), "+f"(d[94]), "+f"(d[95])
    : "r"(da), "r"(db), "r"(0x40000040u), "n"(SCALE_D));
}
template <int SCALE_D> __device__ __forceinline__ void wgmma_ss_n128(float (&d)[64], uint32_t da, uint32_t db) {
  asm volatile("{\n.reg .b64 da, db;\nmov.b64 da, {%64, %66};\nmov.b64 db, {%65, %66};\n"
    "wgmma.mma_async.sync.aligned.m64n128k16.f32.bf16.bf16 {%0, %1, %2, %3, %4, %5, %6, %7, %8, %9, %10, %11, %12, %13, %14, %15, %16, %17, %18, %19, %20, %21, %22, %23, %24, %25, %26, %27, %28, %29, %30, %31, %32, %33, %34, %35, %36, %37, %38, %39, %40, %41, %42, %43, %44, %45, %46, %47, %48, %49, %50, %51, %52, %53, %54, %55, %56, %57, %58, %59, %60, %61, %62, %63}, da, db, %67, 1, 1, 0, 1;\n}\n"
    : "+f"(d[0]), "+f"(d[1]), "+f"(d[2]), "+f"(d[3]), "+f"(d[4]), "+f"(d[5]), "+f"(d[6]), "+f"(d[7]), "+f"(d[8]), "+f"(d[9]), "+f"(d[10]), "+f"(d[11]), "+f"(d[12]), "+f"(d[13]), "+f"(d[14]), "+f"(d[15]), "+f"(d[16]), "+f"(d[17]), "+f"(d[18]), "+f"(d[19]), "+f"(d[20]), "+f"(d[21]), "+f"(d[22]), "+f"(d[23]), "+f"(d[24]), "+f"(d[25]), "+f"(d[26]), "+f"(d[27]), "+f"(d[28]), "+f"(d[29]), "+f"(d[30]), "+f"(d[31]), "+f"(d[32]), "+f"(d[33]), "+f"(d[34]), "+f"(d[35]), "+f"(d[36]), "+f"(d[37]), "+f"(d[38]), "+f"(d[39]), "+f"(d[40]), "+f"(d[41]), "+f"(d[42]), "+f"(d[43]), "+f"(d[44]), "+f"(d[45]), "+f"(d[46]), "+f"(d[47]), "+f"(d[48]), "+f"(d[49]), "+f"(d[50]), "+f"(d[51]), "+f"(d[52]), "+f"(d[53]), "+f"(d[54]), "+f"(d[55]), "+f"(d[56]), "+f"(d[57]), "+f"(d[58]), "+f"(d[59]), "+f"(d[60]), "+f"(d[61]), "+f"(d[62]), "+f"(d[63])
    : "r"(da), "r"(db), "r"(0x40000040u), "n"(SCALE_D));
}
template <int SCALE_D> __device__ __forceinline__ void wgmma_ss_n96(float (&d)[48], uint32_t da, uint32_t db) {
  asm volatile("{\n.reg .b64 da, db;\nmov.b64 da, {%48, %50};\nmov.b64 db, {%49, %50};\n"
    "wgmma.mma_async.sync.aligned.m64n96k16.f32.bf16.bf16 {%0, %1, %2, %3, %4, %5, %6, %7, %8, %9, %10, %11, %12, %13, %14, %15, %16, %17, %18, %19, %20, %21, %22, %23, %24, %25, %26, %27, %28, %29, %30, %31, %32, %33, %34, %35, %36, %37, %38, %39, %40, %41, %42, %43, %44, %45, %46, %47}, da, db, %51, 1, 1, 0, 1;\n}\n"
    : "+f"(d[0]), "+f"(d[1]), "+f"(d[2]), "+f"(d[3]), "+f"(d[4]), "+f"(d[5]), "+f"(d[6]), "+f"(d[7]), "+f"(d[8]), "+f"(d[9]), "+f"(d[10]), "+f"(d[11]), "+f"(d[12]), "+f"(d[13]), "+f"(d[14]), "+f"(d[15]), "+f"(d[16]), "+f"(d[17]), "+f"(d[18]), "+f"(d[19]), "+f"(d[20]), "+f"(d[21]), "+f"(d[22]), "+f"(d[23]), "+f"(d[24]), "+f"(d[25]), "+f"(d[26]), "+f"(d[27]), "+f"(d[28]), "+f"(d[29]), "+f"(d[30]), "+f"(d[31]), "+f"(d[32]), "+f"(d[33]), "+f"(d[34]), "+f"(d[35]), "+f"(d[36]), "+f"(d[37]), "+f"(d[38]), "+f"(d[39]), "+f"(d[40]), "+f"(d[41]), "+f"(d[42]), "+f"(d[43]), "+f"(d[44]), "+f"(d[45]), "+f"(d[46]), "+f"(d[47])
    : "r"(da), "r"(db), "r"(0x40000040u), "n"(SCALE_D));
}
template <int SCALE_D> __device__ __forceinline__ void wgmma_tt_n72(float (&d)[36], uint32_t da, uint32_t db) {
  asm volatile("{\n.reg .b64 da, db;\nmov.b64 da, {%36, %38};\nmov.b64 db, {%37, %38};\n"
    "wgmma.mma_async.sync.aligned.m64n72k16.f32.bf16.bf16 {%0, %1, %2, %3, %4, %5, %6, %7, %8, %9, %10, %11, %12, %13, %14, %15, %16, %17, %18, %19, %20, %21, %22, %23, %24, %25, %26, %27, %28, %29, %30, %31, %32, %33, %34, %35}, da, db, %39, 1, 1, 1, 1;\n}\n"
    : "+f"(d[0]), "+f"(d[1]), "+f"(d[2]), "+f"(d[3]), "+f"(d[4]), "+f"(d[5]), "+f"(d[6]), "+f"(d[7]), "+f"(d[8]), "+f"(d[9]), "+f"(d[10]), "+f"(d[11]), "+f"(d[12]), "+f"(d[13]), "+f"(d[14]), "+f"(d[15]), "+f"(d[16]), "+f"(d[17]), "+f"(d[18]), "+f"(d[19]), "+f"(d[20]), "+f"(d[21]), "+f"(d[22]), "+f"(d[23]), "+f"(d[24]), "+f"(d[25]), "+f"(d[26]), "+f"(d[27]), "+f"(d[28]), "+f"(d[29]), "+f"(d[30]), "+f"(d[31]), "+f"(d[32]), "+f"(d[33]), "+f"(d[34]), "+f"(d[35])
    : "r"(da), "r"(db), "r"(0x40000040u), "n"(SCALE_D));
}
template <int SCALE_D> __device__ __forceinline__ void wgmma_rs_n128(float (&d)[64], const uint4& a, uint32_t db) {
  asm volatile("{\n.reg .b64 db;\nmov.b64 db, {%68, %69};\n"
    "wgmma.mma_async.sync.aligned.m64n128k16.f32.bf16.bf16 {%0, %1, %2, %3, %4, %5, %6, %7, %8, %9, %10, %11, %12, %13, %14, %15, %16, %17, %18, %19, %20, %21, %22, %23, %24, %25, %26, %27, %28, %29, %30, %31, %32, %33, %34, %35, %36, %37, %38, %39, %40, %41, %42, %43, %44, %45, %46, %47, %48, %49, %50, %51, %52, %53, %54, %55, %56, %57, %58, %59, %60, %61, %62, %63}, {%64, %65, %66, %67}, db, %70, 1, 1, 1;\n}\n"
    : "+f"(d[0]), "+f"(d[1]), "+f"(d[2]), "+f"(d[3]), "+f"(d[4]), "+f"(d[5]), "+f"(d[6]), "+f"(d[7]), "+f"(d[8]), "+f"(d[9]), "+f"(d[10]), "+f"(d[11]), "+f"(d[12]), "+f"(d[13]), "+f"(d[14]), "+f"(d[15]), "+f"(d[16]), "+f"(d[17]), "+f"(d[18]), "+f"(d[19]), "+f"(d[20]), "+f"(d[21]), "+f"(d[22]), "+f"(d[23]), "+f"(d[24]), "+f"(d[25]), "+f"(d[26]), "+f"(d[27]), "+f"(d[28]), "+f"(d[29]), "+f"(d[30]), "+f"(d[31]), "+f"(d[32]), "+f"(d[33]), "+f"(d[34]), "+f"(d[35]), "+f"(d[36]), "+f"(d[37]), "+f"(d[38]), "+f"(d[39]), "+f"(d[40]), "+f"(d[41]), "+f"(d[42]), "+f"(d[43]), "+f"(d[44]), "+f"(d[45]), "+f"(d[46]), "+f"(d[47]), "+f"(d[48]), "+f"(d[49]), "+f"(d[50]), "+f"(d[51]), "+f"(d[52]), "+f"(d[53]), "+f"(d[54]), "+f"(d[55]), "+f"(d[56]), "+f"(d[57]), "+f"(d[58]), "+f"(d[59]), "+f"(d[60]), "+f"(d[61]), "+f"(d[62]), "+f"(d[63])
    : "r"(a.x), "r"(a.y), "r"(a.z), "r"(a.w), "r"(db), "r"(0x40000040u), "n"(SCALE_D));
}
template <int SCALE_D> __device__ __forceinline__ void wgmma_rs_n96(float (&d)[48], const uint4& a, uint32_t db) {
  asm volatile("{\n.reg .b64 db;\nmov.b64 db, {%52, %53};\n"
    "wgmma.mma_async.sync.aligned.m64n96k16.f32.bf16.bf16 {%0, %1, %2, %3, %4, %5, %6, %7, %8, %9, %10, %11, %12, %13, %14, %15, %16, %17, %18, %19, %20, %21, %22, %23, %24, %25, %26, %27, %28, %29, %30, %31, %32, %33, %34, %35, %36, %37, %38, %39, %40, %41, %42, %43, %44, %45, %46, %47}, {%48, %49, %50, %51}, db, %54, 1, 1, 1;\n}\n"
    : "+f"(d[0]), "+f"(d[1]), "+f"(d[2]), "+f"(d[3]), "+f"(d[4]), "+f"(d[5]), "+f"(d[6]), "+f"(d[7]), "+f"(d[8]), "+f"(d[9]), "+f"(d[10]), "+f"(d[11]), "+f"(d[12]), "+f"(d[13]), "+f"(d[14]), "+f"(d[15]), "+f"(d[16]), "+f"(d[17]), "+f"(d[18]), "+f"(d[19]), "+f"(d[20]), "+f"(d[21]), "+f"(d[22]), "+f"(d[23]), "+f"(d[24]), "+f"(d[25]), "+f"(d[26]), "+f"(d[27]), "+f"(d[28]), "+f"(d[29]), "+f"(d[30]), "+f"(d[31]), "+f"(d[32]), "+f"(d[33]), "+f"(d[34]), "+f"(d[35]), "+f"(d[36]), "+f"(d[37]), "+f"(d[38]), "+f"(d[39]), "+f"(d[40]), "+f"(d[41]), "+f"(d[42]), "+f"(d[43]), "+f"(d[44]), "+f"(d[45]), "+f"(d[46]), "+f"(d[47])
    : "r"(a.x), "r"(a.y), "r"(a.z), "r"(a.w), "r"(db), "r"(0x40000040u), "n"(SCALE_D));
}
template <int SCALE_D> __device__ __forceinline__ void wgmma_rs_n64(float (&d)[32], const uint4& a, uint32_t db) {
  asm volatile("{\n.reg .b64 db;\nmov.b64 db, {%36, %37};\n"
    "wgmma.mma_async.sync.aligned.m64n64k16.f32.bf16.bf16 {%0, %1, %2, %3, %4, %5, %6, %7, %8, %9, %10, %11, %12, %13, %14, %15, %16, %17, %18, %19, %20, %21, %22, %23, %24, %25, %26, %27, %28, %29, %30, %31}, {%32, %33, %34, %35}, db, %38, 1, 1, 1;\n}\n"
    : "+f"(d[0]), "+f"(d[1]), "+f"(d[2]), "+f"(d[3]), "+f"(d[4]), "+f"(d[5]), "+f"(d[6]), "+f"(d[7]), "+f"(d[8]), "+f"(d[9]), "+f"(d[10]), "+f"(d[11]), "+f"(d[12]), "+f"(d[13]), "+f"(d[14]), "+f"(d[15]), "+f"(d[16]), "+f"(d[17]), "+f"(d[18]), "+f"(d[19]), "+f"(d[20]), "+f"(d[21]), "+f"(d[22]), "+f"(d[23]), "+f"(d[24]), "+f"(d[25]), "+f"(d[26]), "+f"(d[27]), "+f"(d[28]), "+f"(d[29]), "+f"(d[30]), "+f"(d[31])
    : "r"(a.x), "r"(a.y), "r"(a.z), "r"(a.w), "r"(db), "r"(0x40000040u), "n"(SCALE_D));
}

constexpr float LOG2E = 1.4426950408889634f;
__device__ __forceinline__ float silu_f(float y) { return y * rcp(1.f + ex2(-y * LOG2E)); }

__device__ __forceinline__ void mish_tile(const float* c, float rs0, float rs1, float rl0, float rl1, uint4* dst) {
  float h[8], u[8], r[8];
#pragma unroll
  for (int i = 0; i < 8; i++) {
    const bool hi = (i >> 1) & 1;
    h[i] = c[i] * (hi ? rs1 : rs0);
    u[i] = ex2(fminf(c[i] * (hi ? rl1 : rl0), 28.853900817779268f));
  }
#pragma unroll
  for (int i = 0; i < 8; i++) { const float tt = u[i] + 2.f; r[i] = rcp(fmaf(u[i], tt, 2.f)); h[i] *= u[i] * tt; }
#pragma unroll
  for (int i = 0; i < 8; i++) h[i] *= r[i];
  stg_v4(dst, pack2(h[0], h[1]), pack2(h[2], h[3]), pack2(h[4], h[5]), pack2(h[6], h[7]));
}
__device__ __forceinline__ float phi_c(float c, float rs, float rl) {
  const float e = ex2(c * rl) + 1e-6f;
  const float p = fmaf(c, rs, 1.000001f);
  return c > 0.f ? p : e;
}
__device__ __forceinline__ uint4 phi_tile(const float* c, float rs0, float rs1, float rl0, float rl1) {
  uint4 r;
  r.x = pack2(phi_c(c[0], rs0, rl0), phi_c(c[1], rs0, rl0)); r.y = pack2(phi_c(c[2], rs1, rl1), phi_c(c[3], rs1, rl1));
  r.z = pack2(phi_c(c[4], rs0, rl0), phi_c(c[5], rs0, rl0)); r.w = pack2(phi_c(c[6], rs1, rl1), phi_c(c[7], rs1, rl1));
  return r;
}
template <int NB> __device__ __forceinline__ void init_bias(float* acc, uint32_t bias_addr, float ir0, float ir1) {
#pragma unroll
  for (int nb = 0; nb < NB; nb++) {
    const float2 b = lds_f32x2(bias_addr + 32 * nb);
    acc[4 * nb] = b.x * ir0; acc[4 * nb + 1] = b.y * ir0; acc[4 * nb + 2] = b.x * ir1; acc[4 * nb + 3] = b.y * ir1;
  }
}

__global__ void __launch_bounds__(384, 1)
fused_kernel(const __grid_constant__ CUtensorMap tm_x, const __grid_constant__ CUtensorMap tm_qkv,
             const __grid_constant__ CUtensorMap tm_w1, const __grid_constant__ CUtensorMap tm_w2a,
             const __grid_constant__ CUtensorMap tm_w2b, const __grid_constant__ CUtensorMap tm_wo,
             const __grid_constant__ CUtensorMap tm_out,
             const uint8_t* __restrict__ wqkv, const uint8_t* __restrict__ w1, const uint8_t* __restrict__ w2,
             const uint8_t* __restrict__ wo, const __nv_bfloat16* __restrict__ b1) {
  extern __shared__ __align__(1024) uint8_t smem_raw[];
  const uint32_t sb = smem_u32(smem_raw);
  const int tid = threadIdx.x, lane = tid & 31;
  const int warp = __shfl_sync(0xffffffffu, tid >> 5, 0);
  const int bid = blockIdx.x;
  const int G = bid >> 4, gi = bid & 15;
  const int khalf = G & 1;
  const int rb = (G >> 1) * 4 + (gi >> 2);
  const int nt = gi & 3;
  const int j = khalf + 2 * nt;
  const uint32_t bar0 = sb + OFF_BAR;
  PROF(0);

  if (warp >= 8) {
    asm volatile("setmaxnreg.dec.sync.aligned.u32 40;");
    if (warp == 8) {
      if (lane == 0) {
        if (sb & 1023u) asm volatile("trap;");
        for (int i = 0; i < NSLOT; i++) { mbar_init(bar0 + 8 * (BAR_FULL + i), 1); mbar_init(bar0 + 8 * (BAR_EMPTY + i), 8); }
        for (int i = BAR_X; i <= BAR_XT; i++) mbar_init(bar0 + 8 * i, 1);
        for (int i = BAR_PUB_A; i <= BAR_PUB_O; i++) mbar_init(bar0 + 8 * i, 8);
        for (int i = BAR_RDY_A; i <= BAR_RDY_KV; i++) mbar_init(bar0 + 8 * i, 1);
        asm volatile("fence.mbarrier_init.release.cluster;" ::: "memory");
        fence_async_smem();
        for (int i = 0; i < 4; i++) {
          mbar_expect_tx(bar0 + 8 * (BAR_X + i), 32768);
          tma2d(sb + OFF_D + (2 * i) * 16384, &tm_x, 128 * i, rb * 128, bar0 + 8 * (BAR_X + i));
          tma2d(sb + OFF_D + (2 * i + 1) * 16384, &tm_x, 128 * i + 64, rb * 128, bar0 + 8 * (BAR_X + i));
        }
      }
      __syncwarp();
      named_bar_sync(0, 384);
      if (lane == 0) {
        const int c_own = 128 * nt + 64 * khalf, c_par = 128 * nt + 64 * (1 - khalf);
#pragma unroll 1
        for (int st = 0; st < NSTAGES; st++) {
          const int slot = slot_of(st), use = use_of(st);
          const uint32_t full = bar0 + 8 * (BAR_FULL + slot);
          const uint32_t dst = sb + slot_off(slot);
          mbar_wait(bar0 + 8 * (BAR_EMPTY + slot), (use & 1) ^ (slot < 5 ? 1 : 0));
          if (st < 8) {
            mbar_expect_tx(full, 16384);
            const int k0 = 64 * st, c0 = 224 * j;
            tma2d(dst, &tm_w1, c0, k0, full);
            tma2d(dst + 8192, &tm_w1, c0 + 64, k0, full);
          } else if (st < 24) {
            mbar_expect_tx(full, 12288);
            const int k0 = 32 * (st - 8);
            tma2d(dst, &tm_qkv, 512 + 64 * j, k0, full);
            tma2d(dst + 4096, &tm_qkv, 1024 + 64 * j, k0, full);
            tma2d(dst + 8192, &tm_qkv, 64 * j, k0, full);
          } else if (st < 32) {
            mbar_expect_tx(full, 16384);
            const int k0 = 64 * (st - 24), c0 = 224 * j + 128;
            tma2d(dst, &tm_w1, c0, k0, full);
            tma2d(dst + 8192, &tm_w1, c0 + 64, k0, full);
          } else if (st < 40) {
            mbar_expect_tx(full, 16384);
            const int i = st - 32;
            const int k0 = 224 * (4 * khalf + (i >> 1)) + 64 * (i & 1);
            tma2d(dst, &tm_w2a, c_own, k0, full);
            tma2d(dst + 8192, &tm_w2a, c_par, k0, full);
          } else if (st < 48) {
            if (st == 40) {
              mbar_wait(bar0 + 8 * BAR_PUB_KV, 0);
              mbar_expect_tx(bar0 + 8 * BAR_XT, 16384);
              tma2d(sb + OFF_XT, &tm_x, c_own, rb * 128, bar0 + 8 * BAR_XT);
            }
            mbar_expect_tx(full, 12288);
            const int i = st - 40;
            const int k0 = 224 * (4 * khalf + (i >> 1)) + 128 + 48 * (i & 1);
            tma2d(dst, &tm_w2b, c_own, k0, full);
            tma2d(dst + 6144, &tm_w2b, c_par, k0, full);
          } else {
            mbar_expect_tx(full, 8192);
            tma2d(dst, &tm_wo, c_own, 64 * (st - 48), full);
          }
        }
      }
    } else {
      const int aw = warp - 9;
      unsigned dn; asm volatile("ld.relaxed.gpu.global.u32 %0, [%1];" : "=r"(dn) : "l"(&g_done) : "memory");
      named_bar_sync(0, 384);
      const unsigned ep1 = dn / NCTA + 1u;
      if (aw == 0) {
        for (int i = lane; i < 224; i += 32) sts_f32(sb + OFF_B1 + 4 * i, __bfloat162float(b1[224 * j + i]));
#pragma unroll 4
        for (int i = 0; i < 16; i++) sts_v4(sb + OFF_ONES + (i * 32 + lane) * 16, 0x3F803F80u, 0x3F803F80u, 0x3F803F80u, 0x3F803F80u);
        fence_async_smem();
        __syncwarp();
        if (lane == 0) {
          mbar_arrive(bar0 + 8 * BAR_BIAS);
          mbar_wait(bar0 + 8 * BAR_PUB_A, 0);  fence_gpu(); red_inc(&g_cntA[(rb * 2 + (j >> 2)) * 8]);
          mbar_wait(bar0 + 8 * BAR_PUB_KV, 0); fence_gpu(); red_inc(&g_cntKV[j * 8]);
          mbar_wait(bar0 + 8 * BAR_PUB_B, 0);  fence_gpu(); red_inc(&g_cntB[(rb * 2 + (j >> 2)) * 8]);
          mbar_wait(bar0 + 8 * BAR_PUB_O, 0);  fence_gpu(); red_inc(&g_cntO[rb * 8]);
        }
      } else if (aw == 1) {
        if (lane < 4) {
          const uint8_t* base = lane == 0 ? wqkv : lane == 1 ? w1 : lane == 2 ? w2 : wo;
          const uint32_t bytes = lane == 0 ? 12288u : lane == 3 ? 4096u : 14336u;
          asm volatile("cp.async.bulk.prefetch.L2.global [%0], %1;" ::"l"(base + (size_t)bid * bytes), "r"(bytes) : "memory");
        }
        __syncwarp();
        if (lane == 0) {
          poll_ge(&g_cntA[(rb * 2 + khalf) * 8], 4u * ep1); mbar_arrive(bar0 + 8 * BAR_RDY_A);
          PROF(1);
          poll_ge(&g_cntB[(rb * 2 + khalf) * 8], 4u * ep1); mbar_arrive(bar0 + 8 * BAR_RDY_B);
          PROF(2);
          poll_ge(&g_cntO[rb * 8], 8u * ep1);               mbar_arrive(bar0 + 8 * BAR_RDY_O);
          PROF(3);
        }
      } else {
        if (rb == 0) {
          float4* z = reinterpret_cast<float4*>(&g_kv[ep1 & 1][4 * j * 272]);
          for (int i = lane; i < 272; i += 32) z[i] = make_float4(0.f, 0.f, 0.f, 0.f);
        }
        const float* kvbuf = &g_kv[(ep1 & 1) ^ 1][4 * j * 272];
        mbar_wait(bar0 + 8 * BAR_PUB_KV, 0);
        PROF(1);
        if (lane == 0) poll_ge(&g_cntKV[j * 8], 16u * ep1);
        __syncwarp();
        PROF(2);
        {
          const int d = lane >> 1, hf = lane & 1;
          const float* src = kvbuf + d * 16 + hf * 8;
          const uint32_t dst = sb + OFF_KVB + d * 128;
#pragma unroll
          for (int hp = 0; hp < 2; hp++) {
            uint4 v[2][2]; float zz[2];
#pragma unroll
            for (int q = 0; q < 2; q++) {
              const int hh = 2 * hp + q;
              v[q][0] = ldg_cg(src + hh * 272); v[q][1] = ldg_cg(src + hh * 272 + 4);
              asm volatile("ld.global.cg.f32 %0, [%1];" : "=f"(zz[q]) : "l"(kvbuf + hh * 272 + 256 + d) : "memory");
            }
#pragma unroll
            for (int q = 0; q < 2; q++) {
              const int hh = 2 * hp + q;
              sts_v4(dst + hh * 2048 + (((2 * hh + hf) ^ (d & 7)) << 4),
                     pack2(__uint_as_float(v[q][0].x), __uint_as_float(v[q][0].y)), pack2(__uint_as_float(v[q][0].z), __uint_as_float(v[q][0].w)),
                     pack2(__uint_as_float(v[q][1].x), __uint_as_float(v[q][1].y)), pack2(__uint_as_float(v[q][1].z), __uint_as_float(v[q][1].w)));
              const uint32_t z2 = pack2(zz[q], zz[q]);
              if (hf == 0) sts_v4(dst + 8192 + hh * 2048 + ((hh ^ (d & 7)) << 4), z2, z2, z2, z2);
            }
          }
        }
        fence_async_smem();
        __syncwarp();
        if (lane == 0) mbar_arrive(bar0 + 8 * BAR_RDY_KV);
        PROF(3);
      }
    }
  } else {
    asm volatile("setmaxnreg.inc.sync.aligned.u32 232;");
    const int wg = warp >> 2;
    const int g = lane >> 2, t = lane & 3;
    const int lr0 = warp * 16 + g;
    const int slab = rb * 8 + warp;
    unsigned dn; asm volatile("ld.relaxed.gpu.global.u32 %0, [%1];" : "=r"(dn) : "l"(&g_done) : "memory");
    const uint32_t a_lo = dlo(sb + OFF_D + wg * 8192, 16);
    const uint32_t sb_lo = sb >> 4;

#define B_LO(gs, off, lbo) (sb_lo + ((slot_off(slot_of(gs)) + (off)) >> 4) + (((lbo) >> 4) << 16))
#define STAGE_BEGIN(gs) do { mbar_wait(bar0 + 8 * (BAR_FULL + slot_of(gs)), use_of(gs) & 1); wg_fence(); } while (0)
#define RELEASE_SLOT(sl) do { if (lane == 0) mbar_arrive(bar0 + 8 * (BAR_EMPTY + (sl))); } while (0)
#define STAGE_END(prev) do { wg_commit(); wg_wait<1>(); if ((prev) >= 0 && (prev) < 46) RELEASE_SLOT(slot_of((prev) < 0 ? 0 : (prev))); } while (0)
#define WARP_ARRIVE(b) do { __syncwarp(); if (lane == 0) mbar_arrive(bar0 + 8 * (b)); } while (0)

    uint4* act_out = g_act + (size_t)(slab * 112 + 14 * j) * 32 + lane;
    const uint32_t bias_addr = sb + OFF_B1 + 8 * t;
    float rs0, rs1;
    float pool[160];
    float (&acca)[64] = reinterpret_cast<float (&)[64]>(pool[0]);
    float (&accq)[96] = reinterpret_cast<float (&)[96]>(pool[64]);
    float (&accb)[48] = reinterpret_cast<float (&)[48]>(pool[0]);
    float (&accy)[64] = reinterpret_cast<float (&)[64]>(pool[64]);
    float (&accs)[32] = reinterpret_cast<float (&)[32]>(pool[0]);
    float rl0, rl1, ir0, ir1;
    {
      uint4 q[16], p[16];
      const int par = g & 1;
      const uint32_t rowa = sb + OFF_D + lr0 * 128;
      const uint32_t u0 = (uint32_t)(((par * 4 + t) ^ g) << 4), u1 = u0 ^ 64u;
      named_bar_sync(0, 384);
      float sm[2][4], ga[2][4], gb[2][4];
#pragma unroll
      for (int a = 0; a < 2; a++) {
        sm[a][0] = sm[a][1] = sm[a][2] = sm[a][3] = 0.f;
        ga[a][0] = ga[a][1] = ga[a][2] = ga[a][3] = 0.f;
        gb[a][0] = gb[a][1] = gb[a][2] = gb[a][3] = 0.f;
      }
      const uint32_t ones = 0x3F803F80u;
#pragma unroll
      for (int c = 0; c < 8; c++) {
        if ((c & 1) == 0) mbar_wait(bar0 + 8 * (BAR_X + (c >> 1)), 0);
        q[2 * c] = lds_v4(rowa + c * 16384 + u0);     p[2 * c] = lds_v4(rowa + c * 16384 + 1024 + u0);
        q[2 * c + 1] = lds_v4(rowa + c * 16384 + u1); p[2 * c + 1] = lds_v4(rowa + c * 16384 + 1024 + u1);
#pragma unroll
        for (int h = 0; h < 2; h++) {
          const int i = 2 * c + h;
          mma16816(sm[0], q[i].x, p[i].x, q[i].y, p[i].y, ones, ones);
          mma16816(sm[1], q[i].z, p[i].z, q[i].w, p[i].w, ones, ones);
          mma16816(ga[0], q[i].x, p[i].x, q[i].y, p[i].y, q[i].x, q[i].y);
          mma16816(ga[1], q[i].z, p[i].z, q[i].w, p[i].w, q[i].z, q[i].w);
          mma16816(gb[0], q[i].x, p[i].x, q[i].y, p[i].y, p[i].x, p[i].y);
          mma16816(gb[1], q[i].z, p[i].z, q[i].w, p[i].w, p[i].z, p[i].w);
        }
      }
      const float m0 = (sm[0][0] + sm[1][0]) * (1.f / DM);
      const float m1 = (sm[0][2] + sm[1][2]) * (1.f / DM);
      const uint32_t mb0 = pack2(m0, m0), mb1 = pack2(m1, m1);
      PROF(12);
#pragma unroll
      for (int i = 0; i < 16; i++) {
        const uint32_t off = (uint32_t)(i >> 1) * 16384 + ((i & 1) ? u1 : u0);
        sts_v4(rowa + off, hsub2_bf16(q[i].x, mb0), hsub2_bf16(q[i].y, mb0), hsub2_bf16(q[i].z, mb0), hsub2_bf16(q[i].w, mb0));
        sts_v4(rowa + 1024 + off, hsub2_bf16(p[i].x, mb1), hsub2_bf16(p[i].y, mb1), hsub2_bf16(p[i].z, mb1), hsub2_bf16(p[i].w, mb1));
      }
      fence_async_smem();
      float d0 = par ? ga[0][1] + ga[1][1] : ga[0][0] + ga[1][0];
      float d1 = par ? gb[0][3] + gb[1][3] : gb[0][2] + gb[1][2];
      d0 = __shfl_sync(0xffffffffu, d0, (lane & ~3) | (g >> 1));
      d1 = __shfl_sync(0xffffffffu, d1, (lane & ~3) | (g >> 1));
      const float v0 = fmaxf(d0 * (1.f / DM) - m0 * m0, 0.f) + 1e-5f;
      const float v1 = fmaxf(d1 * (1.f / DM) - m1 * m1, 0.f) + 1e-5f;
      rs0 = rsqrtf(v0); rs1 = rsqrtf(v1);
      ir0 = v0 * rs0; ir1 = v1 * rs1;
      rl0 = rs0 * LOG2E; rl1 = rs1 * LOG2E;
      mbar_wait(bar0 + 8 * BAR_BIAS, 0);
      init_bias<16>(acca, bias_addr, ir0, ir1);
      named_bar_sync(1 + wg, 128);
      PROF(1);
    }
#pragma unroll
    for (int st = 0; st < 8; st++) {
      STAGE_BEGIN(st);
#pragma unroll
      for (int kk = 0; kk < 4; kk++) wgmma_ss_n128<1>(acca, a_lo + ((st * 16384 + kk * 32) >> 4), B_LO(st, kk * 2048, 8192));
      STAGE_END(st - 1);
      if (st == 0) zero_regs(accq);
    }
    PROF(2);
#pragma unroll
    for (int st = 0; st < 16; st++) {
      const int gs = 8 + st;
      STAGE_BEGIN(gs);
      const uint32_t as = a_lo + (((st >> 1) * 16384 + (st & 1) * 64) >> 4);
      wgmma_ss_n192<1>(accq, as, B_LO(gs, 0, 4096));
      wgmma_ss_n192<1>(accq, as + 2, B_LO(gs, 2048, 4096));
      STAGE_END(gs - 1);
      if (st == 0) fence_regs(acca);
      if (st < 8) mish_tile(acca + 8 * st, rs0, rs1, rl0, rl1, act_out + st * 32);
      if (st == 7) { WARP_ARRIVE(BAR_PUB_A); PROF(3); }
      if (st == 8) init_bias<12>(accb, bias_addr + 512, ir0, ir1);
    }
    PROF(4);
    const uint4* act_in = g_act + (size_t)(slab * 112 + 56 * khalf) * 32 + lane;
    const uint4* o_in = g_o + (size_t)(slab * 32) * 32 + lane;
    uint4 ab[4][4];
    auto load_a = [&](int rs) {
      if (rs < 8) {
        const int kt = 14 * (rs >> 1) + 4 * (rs & 1);
#pragma unroll
        for (int kk = 0; kk < 4; kk++) ab[rs & 3][kk] = ldg_cg(act_in + (kt + kk) * 32);
      } else if (rs < 16) {
        const int kt = 14 * ((rs - 8) >> 1) + 8 + 3 * (rs & 1);
#pragma unroll
        for (int kk = 0; kk < 3; kk++) ab[rs & 3][kk] = ldg_cg(act_in + (kt + kk) * 32);
      } else if (rs < 24) {
#pragma unroll
        for (int kk = 0; kk < 4; kk++) ab[rs & 3][kk] = ldg_cg(o_in + (4 * (rs - 16) + kk) * 32);
      }
    };
    auto keep_a = [&](int rs) {
#pragma unroll
      for (int kk = 0; kk < 4; kk++) if (!(rs >= 8 && rs < 16 && kk == 3)) fence_u4(ab[rs & 3][kk]);
    };
    uint4 pq[4];
    const unsigned ep1 = dn / NCTA + 1u;
    {
      const int m = lane >> 3, rr = lane & 7;
      const uint32_t srow = sb + OFF_D + (warp * 16 + (m & 1) * 8 + rr) * 128;
      const uint32_t ka = dlo(sb + OFF_PK + wg * 8192, 16);
      const uint32_t vb = dlo(sb + OFF_V + wg * 8192, OFF_ONES - (OFF_V + wg * 8192));
      float (&acck)[36] = reinterpret_cast<float (&)[36]>(pool[64]);
#pragma unroll
      for (int st = 0; st < 8; st++) {
        const int gs = 24 + st;
        STAGE_BEGIN(gs);
#pragma unroll
        for (int kk = 0; kk < 4; kk++) wgmma_ss_n96<1>(accb, a_lo + ((st * 16384 + kk * 32) >> 4), B_LO(gs, kk * 2048, 8192));
        if (st == 3) {
          wgmma_tt_n72<0>(acck, ka, vb);
#pragma unroll
          for (int kk = 1; kk < 4; kk++) wgmma_tt_n72<1>(acck, ka + kk * 128, vb + kk * 128);
        }
        STAGE_END(gs - 1);
        if (st >= 4) RELEASE_SLOT(5 + (st - 1) - 3);
        if (st == 0) {
          fence_regs(accq);
          pq[0] = phi_tile(accq + 64, rs0, rs1, rl0, rl1); pq[1] = phi_tile(accq + 72, rs0, rs1, rl0, rl1);
          pq[2] = phi_tile(accq + 80, rs0, rs1, rl0, rl1); pq[3] = phi_tile(accq + 88, rs0, rs1, rl0, rl1);
        } else if (st == 1) {
#pragma unroll
          for (int i = 0; i < 4; i++) {
            const uint4 r = phi_tile(accq + 8 * i, rs0, rs1, rl0, rl1);
            stmatrix_x4(srow + OFF_PK + (((2 * i + (m >> 1)) ^ rr) << 4), r.x, r.y, r.z, r.w);
          }
        } else if (st == 2) {
#pragma unroll
          for (int i = 0; i < 4; i++) {
            const float* c = accq + 32 + 8 * i;
            stmatrix_x4(srow + OFF_V + (((2 * i + (m >> 1)) ^ rr) << 4),
                        pack2(c[0] * rs0, c[1] * rs0), pack2(c[2] * rs1, c[3] * rs1), pack2(c[4] * rs0, c[5] * rs0), pack2(c[6] * rs1, c[7] * rs1));
          }
          fence_async_smem();
          named_bar_sync(1 + wg, 128);
        } else if (st == 4) {
          fence_regs(acck);
          const int wq = warp & 3;
          float* hb = &g_kv[(ep1 & 1) ^ 1][(4 * j + wq) * 272];
          float* a0p = hb + g * 16 + 2 * t;
#pragma unroll
          for (int w = 0; w < 4; w++) {
            if (wq == w) {
              red_add_v2(a0p, acck[8 * w], acck[8 * w + 1]); red_add_v2(a0p + 128, acck[8 * w + 2], acck[8 * w + 3]);
              red_add_v2(a0p + 8, acck[8 * w + 4], acck[8 * w + 5]); red_add_v2(a0p + 136, acck[8 * w + 6], acck[8 * w + 7]);
            }
          }
          if (t == 0) { red_add_f32(hb + 256 + g, acck[32]); red_add_f32(hb + 264 + g, acck[34]); }
#pragma unroll
          for (int i = 0; i < 4; i++) sts_v4(sb + OFF_KVB + warp * 2048 + i * 512 + lane * 16, 0u, 0u, 0u, 0u);
          WARP_ARRIVE(BAR_PUB_KV);
        } else if (st == 5) {
          mbar_wait(bar0 + 8 * BAR_RDY_A, 0);
          load_a(0); load_a(1); load_a(2);
        }
        PROF(21 + st);
      }
    }
    PROF(5);
#pragma unroll
    for (int st = 0; st < 8; st++) {
      const int gs = 32 + st;
      STAGE_BEGIN(gs);
#pragma unroll
      for (int kk = 0; kk < 4; kk++) {
        if (st == 0 && kk == 0) wgmma_rs_n128<0>(accy, ab[st & 3][kk], B_LO(gs, kk * 2048, 8192));
        else wgmma_rs_n128<1>(accy, ab[st & 3][kk], B_LO(gs, kk * 2048, 8192));
      }
      if (st == 4) {
        mbar_wait(bar0 + 8 * BAR_RDY_KV, 0);
        PROF(7);
        const uint32_t kb = dlo(sb + OFF_KVB, 8192);
        wgmma_rs_n96<0>(accb, pq[0], kb);
#pragma unroll
        for (int kk = 1; kk < 4; kk++) wgmma_rs_n96<1>(accb, pq[kk], kb + kk * 128);
      }
      STAGE_END(gs - 1);
      if (st == 0) { RELEASE_SLOT(9); fence_regs(accb); }
      else keep_a(st - 1);
      if (st == 5) {
        fence_regs(accb);
#pragma unroll
        for (int kk = 0; kk < 4; kk++) fence_u4(pq[kk]);
        uint4* o_out = g_o + (size_t)(slab * 32 + 4 * j) * 32 + lane;
#pragma unroll
        for (int hh = 0; hh < 4; hh++) {
          const float i0 = __fdividef(1.f, accb[32 + 4 * hh] + 1e-6f), i1 = __fdividef(1.f, accb[34 + 4 * hh] + 1e-6f);
          const float* n = accb + 8 * hh;
          stg_v4(o_out + hh * 32, pack2(n[0] * i0, n[1] * i0), pack2(n[2] * i1, n[3] * i1), pack2(n[4] * i0, n[5] * i0), pack2(n[6] * i1, n[7] * i1));
        }
        WARP_ARRIVE(BAR_PUB_O);
      }
      if (st == 5) mbar_wait(bar0 + 8 * BAR_RDY_B, 0);
      load_a(st + 3);
      if (st < 2) {
#pragma unroll
        for (int i = 3 * st; i < 3 * st + 3; i++)
          mish_tile(accb + 8 * i, rs0, rs1, rl0, rl1, act_out + (8 + i) * 32);
        if (st == 1) WARP_ARRIVE(BAR_PUB_B);
      }
      PROF(13 + st);
    }
    PROF(6);
#pragma unroll
    for (int st = 0; st < 8; st++) {
      const int gs = 40 + st, rs = 8 + st;
      STAGE_BEGIN(gs);
#pragma unroll
      for (int kk = 0; kk < 3; kk++) wgmma_rs_n128<1>(accy, ab[rs & 3][kk], B_LO(gs, kk * 2048, 6144));
      STAGE_END(gs - 1);
      keep_a(rs - 1);
      if (st == 5) mbar_wait(bar0 + 8 * BAR_RDY_O, 0);
      load_a(rs + 3);
    }
    PROF(8);
    const uint32_t tag = ep1 & 1u;
#pragma unroll
    for (int st = 0; st < 8; st++) {
      const int gs = 48 + st, rs = 16 + st;
      STAGE_BEGIN(gs);
#pragma unroll
      for (int kk = 0; kk < 4; kk++) {
        if (st == 0 && kk == 0) wgmma_rs_n64<0>(accs, ab[rs & 3][kk], B_LO(gs, kk * 2048, 8192));
        else wgmma_rs_n64<1>(accs, ab[rs & 3][kk], B_LO(gs, kk * 2048, 8192));
      }
      STAGE_END(gs - 1);
      keep_a(rs - 1);
      load_a(rs + 3);
      if (st == 0) {
        fence_regs(accy);
        float4* yp = g_yp + (size_t)((bid * 8 + warp) * 8) * 32 + lane;
#pragma unroll
        for (int q = 0; q < 8; q++) {
          const uint32_t v0 = (__float_as_uint(accy[32 + 4 * q]) & ~1u) | tag, v1 = (__float_as_uint(accy[33 + 4 * q]) & ~1u) | tag;
          const uint32_t v2 = (__float_as_uint(accy[34 + 4 * q]) & ~1u) | tag, v3 = (__float_as_uint(accy[35 + 4 * q]) & ~1u) | tag;
          asm volatile("st.relaxed.gpu.global.v4.u32 [%0], {%1,%2,%3,%4};" ::"l"(yp + q * 32), "r"(v0), "r"(v1), "r"(v2), "r"(v3) : "memory");
        }
      }
    }
    PROF(9);
    {
      const float4* yp = g_yp + (size_t)(((bid ^ 16) * 8 + warp) * 8) * 32 + lane;
      uint4 pv[8];
      uint32_t it = 0;
      wg_wait<0>();
      keep_a(23);
      fence_regs(accs);
      while (true) {
        uint32_t bad = 0;
#pragma unroll
        for (int q = 0; q < 8; q++)
          asm volatile("ld.relaxed.gpu.global.v4.u32 {%0,%1,%2,%3}, [%4];" : "=r"(pv[q].x), "=r"(pv[q].y), "=r"(pv[q].z), "=r"(pv[q].w) : "l"(yp + q * 32) : "memory");
#pragma unroll
        for (int q = 0; q < 8; q++) bad |= (pv[q].x ^ tag) | (pv[q].y ^ tag) | (pv[q].z ^ tag) | (pv[q].w ^ tag);
        if (!__any_sync(0xffffffffu, bad & 1u)) break;
        if (++it > (1u << 20)) asm volatile("trap;");
      }
      PROF(10);
      mbar_wait(bar0 + 8 * BAR_XT, 0);
      const uint32_t xa = sb + OFF_XT + lr0 * 128 + 4 * t;
#pragma unroll
      for (int q = 0; q < 8; q++) {
        const uint32_t a0 = xa + ((q ^ g) << 4), a1 = a0 + 1024;
        const uint32_t x0 = lds_u32(a0), x1 = lds_u32(a1);
        const float y0 = accy[4 * q] + __uint_as_float(pv[q].x), y1 = accy[4 * q + 1] + __uint_as_float(pv[q].y);
        const float y2 = accy[4 * q + 2] + __uint_as_float(pv[q].z), y3 = accy[4 * q + 3] + __uint_as_float(pv[q].w);
        const float o0 = fmaf(accs[4 * q], silu_f(y0), bf_lo(x0)), o1 = fmaf(accs[4 * q + 1], silu_f(y1), bf_hi(x0));
        const float o2 = fmaf(accs[4 * q + 2], silu_f(y2), bf_lo(x1)), o3 = fmaf(accs[4 * q + 3], silu_f(y3), bf_hi(x1));
        sts_u32(a0, pack2(o0, o1));
        sts_u32(a1, pack2(o2, o3));
      }
      fence_async_smem();
      __syncwarp();
      if (lane == 0) {
        asm volatile("cp.async.bulk.tensor.2d.global.shared::cta.bulk_group [%0, {%2, %3}], [%1];"
                     ::"l"(&tm_out), "r"(sb + OFF_XT + warp * 2048), "r"(128 * nt + 64 * khalf), "r"(rb * 128 + warp * 16) : "memory");
        asm volatile("cp.async.bulk.commit_group;" ::: "memory");
        asm volatile("cp.async.bulk.wait_group.read 0;" ::: "memory");
      }
    }
    PROF(11);
    if (tid == 0) red_inc(&g_done);
  }
}

typedef CUresult (*EncodeFn)(CUtensorMap*, CUtensorMapDataType, cuuint32_t, void*, const cuuint64_t*, const cuuint64_t*,
                             const cuuint32_t*, const cuuint32_t*, CUtensorMapInterleave, CUtensorMapSwizzle,
                             CUtensorMapL2promotion, CUtensorMapFloatOOBfill);

void make_map(EncodeFn enc, CUtensorMap* tm, const void* ptr, int rows, int cols, int box_rows) {
  cuuint64_t gd[2] = {(cuuint64_t)cols, (cuuint64_t)rows};
  cuuint64_t gs[1] = {(cuuint64_t)cols * 2};
  cuuint32_t bd[2] = {64, (cuuint32_t)box_rows};
  cuuint32_t es[2] = {1, 1};
  enc(tm, CU_TENSOR_MAP_DATA_TYPE_BFLOAT16, 2, const_cast<void*>(ptr), gd, gs, bd, es, CU_TENSOR_MAP_INTERLEAVE_NONE,
      CU_TENSOR_MAP_SWIZZLE_128B, CU_TENSOR_MAP_L2_PROMOTION_L2_128B, CU_TENSOR_MAP_FLOAT_OOB_FILL_NONE);
}

}

extern "C" void kernel_launch(void* const* d_in, const int* in_sizes, int n_in, void* d_out, int out_size) {
  const __nv_bfloat16* x = (const __nv_bfloat16*)d_in[0];
  const void* wqkv = d_in[1];
  const void* wo = d_in[2];
  const void* w1 = d_in[4];
  const __nv_bfloat16* b1 = (const __nv_bfloat16*)d_in[5];
  const void* w2 = d_in[6];
  static EncodeFn enc = nullptr;
  if (!enc) {
    cudaDriverEntryPointQueryResult qr;
    void* fn = nullptr;
    cudaGetDriverEntryPoint("cuTensorMapEncodeTiled", &fn, cudaEnableDefault, &qr);
    enc = (EncodeFn)fn;
    cudaFuncSetAttribute(fused_kernel, cudaFuncAttributeMaxDynamicSharedMemorySize, SMEM_ALLOC);
  }
  CUtensorMap tx, tq, t1, t2a, t2b, to, tout;
  make_map(enc, &tx, x, 2048, DM, 128);
  make_map(enc, &tq, wqkv, DM, 3 * DM, 32);
  make_map(enc, &t1, w1, DM, FF, 64);
  make_map(enc, &t2a, w2, FF, DM, 64);
  make_map(enc, &t2b, w2, FF, DM, 48);
  make_map(enc, &to, wo, DM, DM, 64);
  make_map(enc, &tout, d_out, 2048, DM, 16);
  fused_kernel<<<NCTA, 384, SMEM_ALLOC>>>(tx, tq, t1, t2a, t2b, to, tout, (const uint8_t*)wqkv, (const uint8_t*)w1,
                                          (const uint8_t*)w2, (const uint8_t*)wo, b1);
}
```

```cpp
#include <cuda_runtime.h>
#include <cuda_bf16.h>
#include <cuda.h>
#include <stdint.h>

namespace {

constexpr int DM = 512, FF = 1792;
constexpr int NCTA = 128;
constexpr int NRING = 5;
constexpr int NSLOT = 10;
constexpr int SLOT_BYTES = 16384;
constexpr int OFF_D = 0;
constexpr int OFF_PK = 0, OFF_V = 16384;
constexpr int OFF_KVB = 0;
constexpr int OFF_XT = 16384;
constexpr int OFF_RING = 131072;
constexpr int OFF_MISC = OFF_RING + NRING * SLOT_BYTES;
constexpr int OFF_ONES = OFF_MISC;
constexpr int OFF_BAR = OFF_MISC + 8192;
constexpr int OFF_B1 = OFF_MISC + 8704;
constexpr int SMEM_ALLOC = OFF_MISC + 9728;

enum { BAR_FULL = 0, BAR_EMPTY = NSLOT, BAR_X = 2 * NSLOT, BAR_BIAS = BAR_X + 4, BAR_XT,
       BAR_PUB_KV, BAR_RDY_KV, BAR_COUNT };
static_assert(BAR_COUNT <= 40, "too many barriers");

constexpr int NSTAGES = 56;
__host__ __device__ constexpr int slot_of(int gs) {
  if (gs < 32) return gs % 5;
  const int p = (gs - 32) % 10;
  return p < 5 ? 5 + p : (p - 3) % 5;
}
__host__ __device__ constexpr int use_of(int gs) {
  if (gs < 32) return gs / 5;
  const int sl = slot_of(gs);
  return (gs - 32) / 10 + (sl < 5 ? (sl < 2 ? 7 : 6) : 0);
}
__host__ __device__ constexpr int slot_off(int sl) { return sl < 5 ? OFF_RING + sl * SLOT_BYTES : OFF_D + (sl - 2) * SLOT_BYTES; }

__device__ uint4 g_act[128 * 112 * 32];
__device__ uint4 g_o[128 * 32 * 32];
__device__ float4 g_yp[NCTA * 8 * 8 * 32];
__device__ float g_kv[2][32 * 272];
__device__ unsigned g_cntKV[8 * 8];
__device__ unsigned g_done;

#define PROF(i)

__device__ __forceinline__ uint32_t smem_u32(const void* p) { return (uint32_t)__cvta_generic_to_shared(p); }
__device__ __forceinline__ void mbar_init(uint32_t bar, uint32_t cnt) { asm volatile("mbarrier.init.shared::cta.b64 [%0], %1;" ::"r"(bar), "r"(cnt)); }
__device__ __forceinline__ void mbar_expect_tx(uint32_t bar, uint32_t bytes) { asm volatile("mbarrier.arrive.expect_tx.shared::cta.b64 _, [%0], %1;" ::"r"(bar), "r"(bytes) : "memory"); }
__device__ __forceinline__ void mbar_arrive(uint32_t bar) { asm volatile("mbarrier.arrive.shared::cta.b64 _, [%0];" ::"r"(bar) : "memory"); }
__device__ __forceinline__ void mbar_wait(uint32_t bar, uint32_t parity) {
  asm volatile("{\n.reg .pred P1;\n.reg .u32 cnt;\n"
               "mbarrier.try_wait.parity.shared::cta.b64 P1, [%0], %1;\n@P1 bra DONE;\n"
               "mov.u32 cnt, 0;\n"
               "LAB_WAIT:\n"
               "mbarrier.try_wait.parity.shared::cta.b64 P1, [%0], %1;\n@P1 bra DONE;\n"
               "add.u32 cnt, cnt, 1;\nsetp.lt.u32 P1, cnt, 16777216;\n@P1 bra LAB_WAIT;\ntrap;\n"
               "DONE:\n}" ::"r"(bar), "r"(parity) : "memory");
}
__device__ __forceinline__ void tma2d(uint32_t dst, const CUtensorMap* tm, int c0, int c1, uint32_t bar) {
  asm volatile("cp.async.bulk.tensor.2d.shared::cluster.global.mbarrier::complete_tx::bytes [%0], [%1, {%3, %4}], [%2];" ::"r"(dst), "l"(tm), "r"(bar), "r"(c0), "r"(c1) : "memory");
}
__device__ __forceinline__ void wg_fence() { asm volatile("wgmma.fence.sync.aligned;" ::: "memory"); }
__device__ __forceinline__ void wg_commit() { asm volatile("wgmma.commit_group.sync.aligned;" ::: "memory"); }
template <int N> __device__ __forceinline__ void wg_wait() { asm volatile("wgmma.wait_group.sync.aligned %0;" ::"n"(N) : "memory"); }
template <int N> __device__ __forceinline__ void zero_regs(float (&d)[N]) {
#pragma unroll
  for (int i = 0; i < N; i++) d[i] = 0.f;
}
template <int N> __device__ __forceinline__ void fence_regs(float (&d)[N]) {
#pragma unroll
  for (int i = 0; i < N; i++) asm volatile("" : "+f"(d[i])::"memory");
}
__device__ __forceinline__ void fence_u4(uint4& v) { asm volatile("" : "+r"(v.x), "+r"(v.y), "+r"(v.z), "+r"(v.w)::"memory"); }
__device__ __forceinline__ void named_bar_sync(int id, int n) { asm volatile("bar.sync %0, %1;" ::"r"(id), "r"(n) : "memory"); }
__device__ __forceinline__ void fence_gpu() { asm volatile("fence.acq_rel.gpu;" ::: "memory"); }
__device__ __forceinline__ void fence_async_smem() { asm volatile("fence.proxy.async.shared::cta;" ::: "memory"); }
__device__ __forceinline__ constexpr uint32_t dlo(uint32_t addr, uint32_t lbo_bytes) { return ((addr & 0x3FFFFu) >> 4) | ((lbo_bytes >> 4) << 16); }
__device__ __forceinline__ void mma16816(float (&c)[4], uint32_t a0, uint32_t a1, uint32_t a2, uint32_t a3, uint32_t b0, uint32_t b1) {
  asm volatile("mma.sync.aligned.m16n8k16.row.col.f32.bf16.bf16.f32 {%0,%1,%2,%3}, {%4,%5,%6,%7}, {%8,%9}, {%0,%1,%2,%3};"
               : "+f"(c[0]), "+f"(c[1]), "+f"(c[2]), "+f"(c[3]) : "r"(a0), "r"(a1), "r"(a2), "r"(a3), "r"(b0), "r"(b1));
}
__device__ __forceinline__ void stmatrix_x4(uint32_t addr, uint32_t a, uint32_t b, uint32_t c, uint32_t d) {
  asm volatile("stmatrix.sync.aligned.m8n8.x4.shared.b16 [%0], {%1,%2,%3,%4};" ::"r"(addr), "r"(a), "r"(b), "r"(c), "r"(d) : "memory");
}
__device__ __forceinline__ uint32_t pack2(float lo, float hi) { uint32_t r; asm("cvt.rn.bf16x2.f32 %0, %1, %2;" : "=r"(r) : "f"(hi), "f"(lo)); return r; }
__device__ __forceinline__ float ex2(float x) { float r; asm("ex2.approx.ftz.f32 %0, %1;" : "=f"(r) : "f"(x)); return r; }
__device__ __forceinline__ float rcp(float x) { float r; asm("rcp.approx.ftz.f32 %0, %1;" : "=f"(r) : "f"(x)); return r; }
__device__ __forceinline__ float bf_lo(uint32_t v) { return __uint_as_float(v << 16); }
__device__ __forceinline__ float bf_hi(uint32_t v) { return __uint_as_float(v & 0xffff0000u); }
__device__ __forceinline__ uint32_t hsub2_bf16(uint32_t a, uint32_t b) {
  __nv_bfloat162 x = *reinterpret_cast<__nv_bfloat162*>(&a), y = *reinterpret_cast<__nv_bfloat162*>(&b);
  __nv_bfloat162 r = __hsub2(x, y);
  return *reinterpret_cast<uint32_t*>(&r);
}
__device__ __forceinline__ uint4 ldg_cg(const void* p) {
  uint4 v; asm volatile("ld.global.cg.v4.u32 {%0,%1,%2,%3}, [%4];" : "=r"(v.x), "=r"(v.y), "=r"(v.z), "=r"(v.w) : "l"(p) : "memory"); return v;
}
__device__ __forceinline__ void stg_frag(void* p, uint32_t a, uint32_t b, uint32_t c, uint32_t d, uint32_t tag) {
  asm volatile("st.relaxed.gpu.global.v4.u32 [%0], {%1,%2,%3,%4};" ::"l"(p), "r"((a & ~1u) | tag), "r"(b), "r"(c), "r"(d) : "memory");
}
__device__ __forceinline__ uint4 ldg_frag(const void* p) {
  uint4 v; asm volatile("ld.relaxed.gpu.global.v4.u32 {%0,%1,%2,%3}, [%4];" : "=r"(v.x), "=r"(v.y), "=r"(v.z), "=r"(v.w) : "l"(p) : "memory"); return v;
}
__device__ __forceinline__ void validate_frag(uint4& v, const void* p, uint32_t tag) {
  asm volatile("{\n.reg .pred P1;\n.reg .u32 cnt, tb;\n"
               "and.b32 tb, %0, 1;\nsetp.eq.u32 P1, tb, %5;\n@P1 bra DONE;\n"
               "mov.u32 cnt, 0;\n"
               "LAB_RETRY:\n"
               "ld.relaxed.gpu.global.v4.u32 {%0,%1,%2,%3}, [%4];\n"
               "and.b32 tb, %0, 1;\nsetp.eq.u32 P1, tb, %5;\n@P1 bra DONE;\n"
               "add.u32 cnt, cnt, 1;\nsetp.lt.u32 P1, cnt, 4194304;\n@P1 bra LAB_RETRY;\ntrap;\n"
               "DONE:\n}" : "+r"(v.x), "+r"(v.y), "+r"(v.z), "+r"(v.w) : "l"(p), "r"(tag) : "memory");
}
__device__ __forceinline__ void sts_v4(uint32_t addr, uint32_t a, uint32_t b, uint32_t c, uint32_t d) {
  asm volatile("st.shared.v4.u32 [%0], {%1,%2,%3,%4};" ::"r"(addr), "r"(a), "r"(b), "r"(c), "r"(d) : "memory");
}
__device__ __forceinline__ void sts_f32(uint32_t addr, float v) { asm volatile("st.shared.f32 [%0], %1;" ::"r"(addr), "f"(v) : "memory"); }
__device__ __forceinline__ uint4 lds_v4(uint32_t addr) { uint4 v; asm volatile("ld.shared.v4.u32 {%0,%1,%2,%3}, [%4];" : "=r"(v.x), "=r"(v.y), "=r"(v.z), "=r"(v.w) : "r"(addr) : "memory"); return v; }
__device__ __forceinline__ uint32_t lds_u32(uint32_t addr) { uint32_t v; asm volatile("ld.shared.u32 %0, [%1];" : "=r"(v) : "r"(addr) : "memory"); return v; }
__device__ __forceinline__ void sts_u32(uint32_t addr, uint32_t v) { asm volatile("st.shared.u32 [%0], %1;" ::"r"(addr), "r"(v) : "memory"); }
__device__ __forceinline__ float2 lds_f32x2(uint32_t addr) { float2 v; asm volatile("ld.shared.v2.f32 {%0,%1}, [%2];" : "=f"(v.x), "=f"(v.y) : "r"(addr) : "memory"); return v; }
__device__ __forceinline__ void red_add_v2(float* p, float a, float b) { asm volatile("red.relaxed.gpu.global.add.v2.f32 [%0], {%1,%2};" ::"l"(p), "f"(a), "f"(b) : "memory"); }
__device__ __forceinline__ void red_add_f32(float* p, float a) { asm volatile("red.relaxed.gpu.global.add.f32 [%0], %1;" ::"l"(p), "f"(a) : "memory"); }
__device__ __forceinline__ void red_inc(unsigned* cnt) { asm volatile("red.relaxed.gpu.global.add.u32 [%0], 1;" ::"l"(cnt) : "memory"); }
__device__ __forceinline__ void poll_ge(const unsigned* cnt, unsigned target) {
  asm volatile("{\n.reg .pred P1;\n.reg .u32 cnt, v;\n.reg .s32 d;\n"
               "mov.u32 cnt, 0;\n"
               "LAB_POLL:\n"
               "ld.relaxed.gpu.global.u32 v, [%0];\nsub.s32 d, v, %1;\nsetp.ge.s32 P1, d, 0;\n@P1 bra DONE;\n"
               "add.u32 cnt, cnt, 1;\nsetp.lt.u32 P1, cnt, 4194304;\n@P1 bra LAB_POLL;\ntrap;\n"
               "DONE:\nld.acquire.gpu.global.u32 v, [%0];\n}" ::"l"(cnt), "r"(target) : "memory");
}

template <int SCALE_D> __device__ __forceinline__ void wgmma_ss_n192(float (&d)[96], uint32_t da, uint32_t db) {
  asm volatile("{\n.reg .b64 da, db;\nmov.b64 da, {%96, %98};\nmov.b64 db, {%97, %98};\n"
    "wgmma.mma_async.sync.aligned.m64n192k16.f32.bf16.bf16 {%0, %1, %2, %3, %4, %5, %6, %7, %8, %9, %10, %11, %12, %13, %14, %15, %16, %17, %18, %19, %20, %21, %22, %23, %24, %25, %26, %27, %28, %29, %30, %31, %32, %33, %34, %35, %36, %37, %38, %39, %40, %41, %42, %43, %44, %45, %46, %47, %48, %49, %50, %51, %52, %53, %54, %55, %56, %57, %58, %59, %60, %61, %62, %63, %64, %65, %66, %67, %68, %69, %70, %71, %72, %73, %74, %75, %76, %77, %78, %79, %80, %81, %82, %83, %84, %85, %86, %87, %88, %89, %90, %91, %92, %93, %94, %95}, da, db, %99, 1, 1, 0, 1;\n}\n"
    : "+f"(d[0]), "+f"(d[1]), "+f"(d[2]), "+f"(d[3]), "+f"(d[4]), "+f"(d[5]), "+f"(d[6]), "+f"(d[7]), "+f"(d[8]), "+f"(d[9]), "+f"(d[10]), "+f"(d[11]), "+f"(d[12]), "+f"(d[13]), "+f"(d[14]), "+f"(d[15]), "+f"(d[16]), "+f"(d[17]), "+f"(d[18]), "+f"(d[19]), "+f"(d[20]), "+f"(d[21]), "+f"(d[22]), "+f"(d[23]), "+f"(d[24]), "+f"(d[25]), "+f"(d[26]), "+f"(d[27]), "+f"(d[28]), "+f"(d[29]), "+f"(d[30]), "+f"(d[31]), "+f"(d[32]), "+f"(d[33]), "+f"(d[34]), "+f"(d[35]), "+f"(d[36]), "+f"(d[37]), "+f"(d[38]), "+f"(d[39]), "+f"(d[40]), "+f"(d[41]), "+f"(d[42]), "+f"(d[43]), "+f"(d[44]), "+f"(d[45]), "+f"(d[46]), "+f"(d[47]), "+f"(d[48]), "+f"(d[49]), "+f"(d[50]), "+f"(d[51]), "+f"(d[52]), "+f"(d[53]), "+f"(d[54]), "+f"(d[55]), "+f"(d[56]), "+f"(d[57]), "+f"(d[58]), "+f"(d[59]), "+f"(d[60]), "+f"(d[61]), "+f"(d[62]), "+f"(d[63]), "+f"(d[64]), "+f"(d[65]), "+f"(d[66]), "+f"(d[67]), "+f"(d[68]), "+f"(d[69]), "+f"(d[70]), "+f"(d[71]), "+f"(d[72]), "+f"(d[73]), "+f"(d[74]), "+f"(d[75]), "+f"(d[76]), "+f"(d[77]), "+f"(d[78]), "+f"(d[79]), "+f"(d[80]), "+f"(d[81]), "+f"(d[82]), "+f"(d[83]), "+f"(d[84]), "+f"(d[85]), "+f"(d[86]), "+f"(d[87]), "+f"(d[88]), "+f"(d[89]), "+f"(d[90]), "+f"(d[91]), "+f"(d[92]), "+f"(d[93]), "+f"(d[94]), "+f"(d[95])
    : "r"(da), "r"(db), "r"(0x40000040u), "n"(SCALE_D));
}
template <int SCALE_D> __device__ __forceinline__ void wgmma_ss_n128(float (&d)[64], uint32_t da, uint32_t db) {
  asm volatile("{\n.reg .b64 da, db;\nmov.b64 da, {%64, %66};\nmov.b64 db, {%65, %66};\n"
    "wgmma.mma_async.sync.aligned.m64n128k16.f32.bf16.bf16 {%0, %1, %2, %3, %4, %5, %6, %7, %8, %9, %10, %11, %12, %13, %14, %15, %16, %17, %18, %19, %20, %21, %22, %23, %24, %25, %26, %27, %28, %29, %30, %31, %32, %33, %34, %35, %36, %37, %38, %39, %40, %41, %42, %43, %44, %45, %46, %47, %48, %49, %50, %51, %52, %53, %54, %55, %56, %57, %58, %59, %60, %61, %62, %63}, da, db, %67, 1, 1, 0, 1;\n}\n"
    : "+f"(d[0]), "+f"(d[1]), "+f"(d[2]), "+f"(d[3]), "+f"(d[4]), "+f"(d[5]), "+f"(d[6]), "+f"(d[7]), "+f"(d[8]), "+f"(d[9]), "+f"(d[10]), "+f"(d[11]), "+f"(d[12]), "+f"(d[13]), "+f"(d[14]), "+f"(d[15]), "+f"(d[16]), "+f"(d[17]), "+f"(d[18]), "+f"(d[19]), "+f"(d[20]), "+f"(d[21]), "+f"(d[22]), "+f"(d[23]), "+f"(d[24]), "+f"(d[25]), "+f"(d[26]), "+f"(d[27]), "+f"(d[28]), "+f"(d[29]), "+f"(d[30]), "+f"(d[31]), "+f"(d[32]), "+f"(d[33]), "+f"(d[34]), "+f"(d[35]), "+f"(d[36]), "+f"(d[37]), "+f"(d[38]), "+f"(d[39]), "+f"(d[40]), "+f"(d[41]), "+f"(d[42]), "+f"(d[43]), "+f"(d[44]), "+f"(d[45]), "+f"(d[46]), "+f"(d[47]), "+f"(d[48]), "+f"(d[49]), "+f"(d[50]), "+f"(d[51]), "+f"(d[52]), "+f"(d[53]), "+f"(d[54]), "+f"(d[55]), "+f"(d[56]), "+f"(d[57]), "+f"(d[58]), "+f"(d[59]), "+f"(d[60]), "+f"(d[61]), "+f"(d[62]), "+f"(d[63])
    : "r"(da), "r"(db), "r"(0x40000040u), "n"(SCALE_D));
}
template <int SCALE_D> __device__ __forceinline__ void wgmma_ss_n96(float (&d)[48], uint32_t da, uint32_t db) {
  asm volatile("{\n.reg .b64 da, db;\nmov.b64 da, {%48, %50};\nmov.b64 db, {%49, %50};\n"
    "wgmma.mma_async.sync.aligned.m64n96k16.f32.bf16.bf16 {%0, %1, %2, %3, %4, %5, %6, %7, %8, %9, %10, %11, %12, %13, %14, %15, %16, %17, %18, %19, %20, %21, %22, %23, %24, %25, %26, %27, %28, %29, %30, %31, %32, %33, %34, %35, %36, %37, %38, %39, %40, %41, %42, %43, %44, %45, %46, %47}, da, db, %51, 1, 1, 0, 1;\n}\n"
    : "+f"(d[0]), "+f"(d[1]), "+f"(d[2]), "+f"(d[3]), "+f"(d[4]), "+f"(d[5]), "+f"(d[6]), "+f"(d[7]), "+f"(d[8]), "+f"(d[9]), "+f"(d[10]), "+f"(d[11]), "+f"(d[12]), "+f"(d[13]), "+f"(d[14]), "+f"(d[15]), "+f"(d[16]), "+f"(d[17]), "+f"(d[18]), "+f"(d[19]), "+f"(d[20]), "+f"(d[21]), "+f"(d[22]), "+f"(d[23]), "+f"(d[24]), "+f"(d[25]), "+f"(d[26]), "+f"(d[27]), "+f"(d[28]), "+f"(d[29]), "+f"(d[30]), "+f"(d[31]), "+f"(d[32]), "+f"(d[33]), "+f"(d[34]), "+f"(d[35]), "+f"(d[36]), "+f"(d[37]), "+f"(d[38]), "+f"(d[39]), "+f"(d[40]), "+f"(d[41]), "+f"(d[42]), "+f"(d[43]), "+f"(d[44]), "+f"(d[45]), "+f"(d[46]), "+f"(d[47])
    : "r"(da), "r"(db), "r"(0x40000040u), "n"(SCALE_D));
}
template <int SCALE_D> __device__ __forceinline__ void wgmma_tt_n72(float (&d)[36], uint32_t da, uint32_t db) {
  asm volatile("{\n.reg .b64 da, db;\nmov.b64 da, {%36, %38};\nmov.b64 db, {%37, %38};\n"
    "wgmma.mma_async.sync.aligned.m64n72k16.f32.bf16.bf16 {%0, %1, %2, %3, %4, %5, %6, %7, %8, %9, %10, %11, %12, %13, %14, %15, %16, %17, %18, %19, %20, %21, %22, %23, %24, %25, %26, %27, %28, %29, %30, %31, %32, %33, %34, %35}, da, db, %39, 1, 1, 1, 1;\n}\n"
    : "+f"(d[0]), "+f"(d[1]), "+f"(d[2]), "+f"(d[3]), "+f"(d[4]), "+f"(d[5]), "+f"(d[6]), "+f"(d[7]), "+f"(d[8]), "+f"(d[9]), "+f"(d[10]), "+f"(d[11]), "+f"(d[12]), "+f"(d[13]), "+f"(d[14]), "+f"(d[15]), "+f"(d[16]), "+f"(d[17]), "+f"(d[18]), "+f"(d[19]), "+f"(d[20]), "+f"(d[21]), "+f"(d[22]), "+f"(d[23]), "+f"(d[24]), "+f"(d[25]), "+f"(d[26]), "+f"(d[27]), "+f"(d[28]), "+f"(d[29]), "+f"(d[30]), "+f"(d[31]), "+f"(d[32]), "+f"(d[33]), "+f"(d[34]), "+f"(d[35])
    : "r"(da), "r"(db), "r"(0x40000040u), "n"(SCALE_D));
}
template <int SCALE_D> __device__ __forceinline__ void wgmma_rs_n128(float (&d)[64], const uint4& a, uint32_t db) {
  asm volatile("{\n.reg .b64 db;\nmov.b64 db, {%68, %69};\n"
    "wgmma.mma_async.sync.aligned.m64n128k16.f32.bf16.bf16 {%0, %1, %2, %3, %4, %5, %6, %7, %8, %9, %10, %11, %12, %13, %14, %15, %16, %17, %18, %19, %20, %21, %22, %23, %24, %25, %26, %27, %28, %29, %30, %31, %32, %33, %34, %35, %36, %37, %38, %39, %40, %41, %42, %43, %44, %45, %46, %47, %48, %49, %50, %51, %52, %53, %54, %55, %56, %57, %58, %59, %60, %61, %62, %63}, {%64, %65, %66, %67}, db, %70, 1, 1, 1;\n}\n"
    : "+f"(d[0]), "+f"(d[1]), "+f"(d[2]), "+f"(d[3]), "+f"(d[4]), "+f"(d[5]), "+f"(d[6]), "+f"(d[7]), "+f"(d[8]), "+f"(d[9]), "+f"(d[10]), "+f"(d[11]), "+f"(d[12]), "+f"(d[13]), "+f"(d[14]), "+f"(d[15]), "+f"(d[16]), "+f"(d[17]), "+f"(d[18]), "+f"(d[19]), "+f"(d[20]), "+f"(d[21]), "+f"(d[22]), "+f"(d[23]), "+f"(d[24]), "+f"(d[25]), "+f"(d[26]), "+f"(d[27]), "+f"(d[28]), "+f"(d[29]), "+f"(d[30]), "+f"(d[31]), "+f"(d[32]), "+f"(d[33]), "+f"(d[34]), "+f"(d[35]), "+f"(d[36]), "+f"(d[37]), "+f"(d[38]), "+f"(d[39]), "+f"(d[40]), "+f"(d[41]), "+f"(d[42]), "+f"(d[43]), "+f"(d[44]), "+f"(d[45]), "+f"(d[46]), "+f"(d[47]), "+f"(d[48]), "+f"(d[49]), "+f"(d[50]), "+f"(d[51]), "+f"(d[52]), "+f"(d[53]), "+f"(d[54]), "+f"(d[55]), "+f"(d[56]), "+f"(d[57]), "+f"(d[58]), "+f"(d[59]), "+f"(d[60]), "+f"(d[61]), "+f"(d[62]), "+f"(d[63])
    : "r"(a.x), "r"(a.y), "r"(a.z), "r"(a.w), "r"(db), "r"(0x40000040u), "n"(SCALE_D));
}
template <int SCALE_D> __device__ __forceinline__ void wgmma_rs_n96(float (&d)[48], const uint4& a, uint32_t db) {
  asm volatile("{\n.reg .b64 db;\nmov.b64 db, {%52, %53};\n"
    "wgmma.mma_async.sync.aligned.m64n96k16.f32.bf16.bf16 {%0, %1, %2, %3, %4, %5, %6, %7, %8, %9, %10, %11, %12, %13, %14, %15, %16, %17, %18, %19, %20, %21, %22, %23, %24, %25, %26, %27, %28, %29, %30, %31, %32, %33, %34, %35, %36, %37, %38, %39, %40, %41, %42, %43, %44, %45, %46, %47}, {%48, %49, %50, %51}, db, %54, 1, 1, 1;\n}\n"
    : "+f"(d[0]), "+f"(d[1]), "+f"(d[2]), "+f"(d[3]), "+f"(d[4]), "+f"(d[5]), "+f"(d[6]), "+f"(d[7]), "+f"(d[8]), "+f"(d[9]), "+f"(d[10]), "+f"(d[11]), "+f"(d[12]), "+f"(d[13]), "+f"(d[14]), "+f"(d[15]), "+f"(d[16]), "+f"(d[17]), "+f"(d[18]), "+f"(d[19]), "+f"(d[20]), "+f"(d[21]), "+f"(d[22]), "+f"(d[23]), "+f"(d[24]), "+f"(d[25]), "+f"(d[26]), "+f"(d[27]), "+f"(d[28]), "+f"(d[29]), "+f"(d[30]), "+f"(d[31]), "+f"(d[32]), "+f"(d[33]), "+f"(d[34]), "+f"(d[35]), "+f"(d[36]), "+f"(d[37]), "+f"(d[38]), "+f"(d[39]), "+f"(d[40]), "+f"(d[41]), "+f"(d[42]), "+f"(d[43]), "+f"(d[44]), "+f"(d[45]), "+f"(d[46]), "+f"(d[47])
    : "r"(a.x), "r"(a.y), "r"(a.z), "r"(a.w), "r"(db), "r"(0x40000040u), "n"(SCALE_D));
}
template <int SCALE_D> __device__ __forceinline__ void wgmma_rs_n64(float (&d)[32], const uint4& a, uint32_t db) {
  asm volatile("{\n.reg .b64 db;\nmov.b64 db, {%36, %37};\n"
    "wgmma.mma_async.sync.aligned.m64n64k16.f32.bf16.bf16 {%0, %1, %2, %3, %4, %5, %6, %7, %8, %9, %10, %11, %12, %13, %14, %15, %16, %17, %18, %19, %20, %21, %22, %23, %24, %25, %26, %27, %28, %29, %30, %31}, {%32, %33, %34, %35}, db, %38, 1, 1, 1;\n}\n"
    : "+f"(d[0]), "+f"(d[1]), "+f"(d[2]), "+f"(d[3]), "+f"(d[4]), "+f"(d[5]), "+f"(d[6]), "+f"(d[7]), "+f"(d[8]), "+f"(d[9]), "+f"(d[10]), "+f"(d[11]), "+f"(d[12]), "+f"(d[13]), "+f"(d[14]), "+f"(d[15]), "+f"(d[16]), "+f"(d[17]), "+f"(d[18]), "+f"(d[19]), "+f"(d[20]), "+f"(d[21]), "+f"(d[22]), "+f"(d[23]), "+f"(d[24]), "+f"(d[25]), "+f"(d[26]), "+f"(d[27]), "+f"(d[28]), "+f"(d[29]), "+f"(d[30]), "+f"(d[31])
    : "r"(a.x), "r"(a.y), "r"(a.z), "r"(a.w), "r"(db), "r"(0x40000040u), "n"(SCALE_D));
}

constexpr float LOG2E = 1.4426950408889634f;
__device__ __forceinline__ float silu_f(float y) { return y * rcp(1.f + ex2(-y * LOG2E)); }

__device__ __forceinline__ void mish_tile(const float* c, float rs0, float rs1, float rl0, float rl1, uint4* dst, uint32_t tag) {
  float h[8], u[8], r[8];
#pragma unroll
  for (int i = 0; i < 8; i++) {
    const bool hi = (i >> 1) & 1;
    h[i] = c[i] * (hi ? rs1 : rs0);
    u[i] = ex2(fminf(c[i] * (hi ? rl1 : rl0), 28.853900817779268f));
  }
#pragma unroll
  for (int i = 0; i < 8; i++) { const float tt = u[i] + 2.f; r[i] = rcp(fmaf(u[i], tt, 2.f)); h[i] *= u[i] * tt; }
#pragma unroll
  for (int i = 0; i < 8; i++) h[i] *= r[i];
  stg_frag(dst, pack2(h[0], h[1]), pack2(h[2], h[3]), pack2(h[4], h[5]), pack2(h[6], h[7]), tag);
}
__device__ __forceinline__ float phi_c(float c, float rs, float rl) {
  const float e = ex2(c * rl) + 1e-6f;
  const float p = fmaf(c, rs, 1.000001f);
  return c > 0.f ? p : e;
}
__device__ __forceinline__ uint4 phi_tile(const float* c, float rs0, float rs1, float rl0, float rl1) {
  uint4 r;
  r.x = pack2(phi_c(c[0], rs0, rl0), phi_c(c[1], rs0, rl0)); r.y = pack2(phi_c(c[2], rs1, rl1), phi_c(c[3], rs1, rl1));
  r.z = pack2(phi_c(c[4], rs0, rl0), phi_c(c[5], rs0, rl0)); r.w = pack2(phi_c(c[6], rs1, rl1), phi_c(c[7], rs1, rl1));
  return r;
}
template <int NB> __device__ __forceinline__ void init_bias(float* acc, uint32_t bias_addr, float ir0, float ir1) {
#pragma unroll
  for (int nb = 0; nb < NB; nb++) {
    const float2 b = lds_f32x2(bias_addr + 32 * nb);
    acc[4 * nb] = b.x * ir0; acc[4 * nb + 1] = b.y * ir0; acc[4 * nb + 2] = b.x * ir1; acc[4 * nb + 3] = b.y * ir1;
  }
}

__global__ void __launch_bounds__(384, 1)
fused_kernel(const __grid_constant__ CUtensorMap tm_x, const __grid_constant__ CUtensorMap tm_qkv,
             const __grid_constant__ CUtensorMap tm_w1, const __grid_constant__ CUtensorMap tm_w2a,
             const __grid_constant__ CUtensorMap tm_w2b, const __grid_constant__ CUtensorMap tm_wo,
             const __grid_constant__ CUtensorMap tm_out,
             const uint8_t* __restrict__ wqkv, const uint8_t* __restrict__ w1, const uint8_t* __restrict__ w2,
             const uint8_t* __restrict__ wo, const __nv_bfloat16* __restrict__ b1) {
  extern __shared__ __align__(1024) uint8_t smem_raw[];
  const uint32_t sb = smem_u32(smem_raw);
  const int tid = threadIdx.x, lane = tid & 31;
  const int warp = __shfl_sync(0xffffffffu, tid >> 5, 0);
  const int bid = blockIdx.x;
  const int G = bid >> 4, gi = bid & 15;
  const int khalf = G & 1;
  const int rb = (G >> 1) * 4 + (gi >> 2);
  const int nt = gi & 3;
  const int j = khalf + 2 * nt;
  const uint32_t bar0 = sb + OFF_BAR;
  PROF(0);

  if (warp >= 8) {
    asm volatile("setmaxnreg.dec.sync.aligned.u32 40;");
    if (warp == 8) {
      if (lane == 0) {
        if (sb & 1023u) asm volatile("trap;");
        for (int i = 0; i < NSLOT; i++) { mbar_init(bar0 + 8 * (BAR_FULL + i), 1); mbar_init(bar0 + 8 * (BAR_EMPTY + i), 8); }
        for (int i = BAR_X; i <= BAR_XT; i++) mbar_init(bar0 + 8 * i, 1);
        mbar_init(bar0 + 8 * BAR_PUB_KV, 8);
        mbar_init(bar0 + 8 * BAR_RDY_KV, 2);
        asm volatile("fence.mbarrier_init.release.cluster;" ::: "memory");
        fence_async_smem();
        for (int i = 0; i < 4; i++) {
          mbar_expect_tx(bar0 + 8 * (BAR_X + i), 32768);
          tma2d(sb + OFF_D + (2 * i) * 16384, &tm_x, 128 * i, rb * 128, bar0 + 8 * (BAR_X + i));
          tma2d(sb + OFF_D + (2 * i + 1) * 16384, &tm_x, 128 * i + 64, rb * 128, bar0 + 8 * (BAR_X + i));
        }
      }
      __syncwarp();
      named_bar_sync(0, 384);
      if (lane == 0) {
        const int c_own = 128 * nt + 64 * khalf, c_par = 128 * nt + 64 * (1 - khalf);
#pragma unroll 1
        for (int st = 0; st < NSTAGES; st++) {
          const int slot = slot_of(st), use = use_of(st);
          const uint32_t full = bar0 + 8 * (BAR_FULL + slot);
          const uint32_t dst = sb + slot_off(slot);
          mbar_wait(bar0 + 8 * (BAR_EMPTY + slot), (use & 1) ^ (slot < 5 ? 1 : 0));
          if (st < 8) {
            mbar_expect_tx(full, 16384);
            const int k0 = 64 * st, c0 = 224 * j;
            tma2d(dst, &tm_w1, c0, k0, full);
            tma2d(dst + 8192, &tm_w1, c0 + 64, k0, full);
          } else if (st < 24) {
            mbar_expect_tx(full, 12288);
            const int k0 = 32 * (st - 8);
            tma2d(dst, &tm_qkv, 512 + 64 * j, k0, full);
            tma2d(dst + 4096, &tm_qkv, 1024 + 64 * j, k0, full);
            tma2d(dst + 8192, &tm_qkv, 64 * j, k0, full);
          } else if (st < 32) {
            mbar_expect_tx(full, 16384);
            const int k0 = 64 * (st - 24), c0 = 224 * j + 128;
            tma2d(dst, &tm_w1, c0, k0, full);
            tma2d(dst + 8192, &tm_w1, c0 + 64, k0, full);
          } else if (st < 40) {
            mbar_expect_tx(full, 16384);
            const int i = st - 32;
            const int k0 = 224 * (4 * khalf + (i >> 1)) + 64 * (i & 1);
            tma2d(dst, &tm_w2a, c_own, k0, full);
            tma2d(dst + 8192, &tm_w2a, c_par, k0, full);
          } else if (st < 48) {
            if (st == 40) {
              mbar_wait(bar0 + 8 * BAR_PUB_KV, 0);
              mbar_expect_tx(bar0 + 8 * BAR_XT, 16384);
              tma2d(sb + OFF_XT, &tm_x, c_own, rb * 128, bar0 + 8 * BAR_XT);
            }
            mbar_expect_tx(full, 12288);
            const int i = st - 40;
            const int k0 = 224 * (4 * khalf + (i >> 1)) + 128 + 48 * (i & 1);
            tma2d(dst, &tm_w2b, c_own, k0, full);
            tma2d(dst + 6144, &tm_w2b, c_par, k0, full);
          } else {
            mbar_expect_tx(full, 8192);
            tma2d(dst, &tm_wo, c_own, 64 * (st - 48), full);
          }
        }
      }
    } else {
      const int aw = warp - 9;
      unsigned dn; asm volatile("ld.relaxed.gpu.global.u32 %0, [%1];" : "=r"(dn) : "l"(&g_done) : "memory");
      named_bar_sync(0, 384);
      const unsigned ep1 = dn / NCTA + 1u;
      if (aw == 0) {
        for (int i = lane; i < 224; i += 32) sts_f32(sb + OFF_B1 + 4 * i, __bfloat162float(b1[224 * j + i]));
#pragma unroll 4
        for (int i = 0; i < 16; i++) sts_v4(sb + OFF_ONES + (i * 32 + lane) * 16, 0x3F803F80u, 0x3F803F80u, 0x3F803F80u, 0x3F803F80u);
        fence_async_smem();
        __syncwarp();
        if (lane == 0) {
          mbar_arrive(bar0 + 8 * BAR_BIAS);
          mbar_wait(bar0 + 8 * BAR_PUB_KV, 0); PROF(3); fence_gpu(); red_inc(&g_cntKV[j * 8]); PROF(4);
        }
      } else {
        const int h0 = 2 * (aw - 1);
        if (aw == 1 && lane < 4) {
          const uint8_t* base = lane == 0 ? wqkv : lane == 1 ? w1 : lane == 2 ? w2 : wo;
          const uint32_t bytes = lane == 0 ? 12288u : lane == 3 ? 4096u : 14336u;
          asm volatile("cp.async.bulk.prefetch.L2.global [%0], %1;" ::"l"(base + (size_t)bid * bytes), "r"(bytes) : "memory");
        }
        if (rb == 0) {
          float4* z = reinterpret_cast<float4*>(&g_kv[ep1 & 1][(4 * j + h0) * 272]);
          for (int i = lane; i < 136; i += 32) z[i] = make_float4(0.f, 0.f, 0.f, 0.f);
        }
        const float* kvbuf = &g_kv[(ep1 & 1) ^ 1][(4 * j + h0) * 272];
        mbar_wait(bar0 + 8 * BAR_PUB_KV, 0);
        PROF(1);
        if (lane == 0) poll_ge(&g_cntKV[j * 8], 16u * ep1);
        __syncwarp();
        PROF(2);
        {
          const int d = lane >> 1, hf = lane & 1;
          const float* src = kvbuf + d * 16 + hf * 8;
          const uint32_t dst = sb + OFF_KVB + d * 128 + h0 * 2048;
          uint4 v[2][2]; float zz[2];
#pragma unroll
          for (int q = 0; q < 2; q++) {
            v[q][0] = ldg_cg(src + q * 272); v[q][1] = ldg_cg(src + q * 272 + 4);
            asm volatile("ld.global.cg.f32 %0, [%1];" : "=f"(zz[q]) : "l"(kvbuf + q * 272 + 256 + d) : "memory");
          }
#pragma unroll
          for (int q = 0; q < 2; q++) {
            const int hh = h0 + q;
            sts_v4(dst + q * 2048 + (((2 * hh + hf) ^ (d & 7)) << 4),
                   pack2(__uint_as_float(v[q][0].x), __uint_as_float(v[q][0].y)), pack2(__uint_as_float(v[q][0].z), __uint_as_float(v[q][0].w)),
                   pack2(__uint_as_float(v[q][1].x), __uint_as_float(v[q][1].y)), pack2(__uint_as_float(v[q][1].z), __uint_as_float(v[q][1].w)));
            const uint32_t z2 = pack2(zz[q], zz[q]);
            if (hf == 0) sts_v4(dst + 8192 + q * 2048 + ((hh ^ (d & 7)) << 4), z2, z2, z2, z2);
          }
        }
        fence_async_smem();
        __syncwarp();
        if (lane == 0) mbar_arrive(bar0 + 8 * BAR_RDY_KV);
        PROF(3);
      }
    }
  } else {
    asm volatile("setmaxnreg.inc.sync.aligned.u32 232;");
    const int wg = warp >> 2;
    const int g = lane >> 2, t = lane & 3;
    const int lr0 = warp * 16 + g;
    const int slab = rb * 8 + warp;
    unsigned dn; asm volatile("ld.relaxed.gpu.global.u32 %0, [%1];" : "=r"(dn) : "l"(&g_done) : "memory");
    const uint32_t a_lo = dlo(sb + OFF_D + wg * 8192, 16);
    const uint32_t sb_lo = sb >> 4;

#define B_LO(gs, off, lbo) (sb_lo + ((slot_off(slot_of(gs)) + (off)) >> 4) + (((lbo) >> 4) << 16))
#define STAGE_BEGIN(gs) do { mbar_wait(bar0 + 8 * (BAR_FULL + slot_of(gs)), use_of(gs) & 1); wg_fence(); } while (0)
#define RELEASE_SLOT(sl) do { if (lane == 0) mbar_arrive(bar0 + 8 * (BAR_EMPTY + (sl))); } while (0)
#define STAGE_END(prev) do { wg_commit(); wg_wait<1>(); if ((prev) >= 0 && (prev) < 46) RELEASE_SLOT(slot_of((prev) < 0 ? 0 : (prev))); } while (0)
#define WARP_ARRIVE(b) do { __syncwarp(); if (lane == 0) mbar_arrive(bar0 + 8 * (b)); } while (0)

    uint4* act_out = g_act + (size_t)(slab * 112 + 14 * j) * 32 + lane;
    const uint32_t bias_addr = sb + OFF_B1 + 8 * t;
    float rs0, rs1;
    float pool[160];
    float (&acca)[64] = reinterpret_cast<float (&)[64]>(pool[0]);
    float (&accq)[96] = reinterpret_cast<float (&)[96]>(pool[64]);
    float (&accb)[48] = reinterpret_cast<float (&)[48]>(pool[0]);
    float (&accy)[64] = reinterpret_cast<float (&)[64]>(pool[64]);
    float (&accs)[32] = reinterpret_cast<float (&)[32]>(pool[0]);
    float rl0, rl1, ir0, ir1;
    const unsigned ep1 = dn / NCTA + 1u;
    const uint32_t tag = ep1 & 1u;
    {
      uint4 q[16], p[16];
      const int par = g & 1;
      const uint32_t rowa = sb + OFF_D + lr0 * 128;
      const uint32_t u0 = (uint32_t)(((par * 4 + t) ^ g) << 4), u1 = u0 ^ 64u;
      named_bar_sync(0, 384);
      float sm[2][4], ga[2][4], gb[2][4];
#pragma unroll
      for (int a = 0; a < 2; a++) {
        sm[a][0] = sm[a][1] = sm[a][2] = sm[a][3] = 0.f;
        ga[a][0] = ga[a][1] = ga[a][2] = ga[a][3] = 0.f;
        gb[a][0] = gb[a][1] = gb[a][2] = gb[a][3] = 0.f;
      }
      const uint32_t ones = 0x3F803F80u;
#pragma unroll
      for (int c = 0; c < 8; c++) {
        if ((c & 1) == 0) mbar_wait(bar0 + 8 * (BAR_X + (c >> 1)), 0);
        q[2 * c] = lds_v4(rowa + c * 16384 + u0);     p[2 * c] = lds_v4(rowa + c * 16384 + 1024 + u0);
        q[2 * c + 1] = lds_v4(rowa + c * 16384 + u1); p[2 * c + 1] = lds_v4(rowa + c * 16384 + 1024 + u1);
#pragma unroll
        for (int h = 0; h < 2; h++) {
          const int i = 2 * c + h;
          mma16816(sm[0], q[i].x, p[i].x, q[i].y, p[i].y, ones, ones);
          mma16816(sm[1], q[i].z, p[i].z, q[i].w, p[i].w, ones, ones);
          mma16816(ga[0], q[i].x, p[i].x, q[i].y, p[i].y, q[i].x, q[i].y);
          mma16816(ga[1], q[i].z, p[i].z, q[i].w, p[i].w, q[i].z, q[i].w);
          mma16816(gb[0], q[i].x, p[i].x, q[i].y, p[i].y, p[i].x, p[i].y);
          mma16816(gb[1], q[i].z, p[i].z, q[i].w, p[i].w, p[i].z, p[i].w);
        }
      }
      const float m0 = (sm[0][0] + sm[1][0]) * (1.f / DM);
      const float m1 = (sm[0][2] + sm[1][2]) * (1.f / DM);
      const uint32_t mb0 = pack2(m0, m0), mb1 = pack2(m1, m1);
      PROF(12);
#pragma unroll
      for (int i = 0; i < 16; i++) {
        const uint32_t off = (uint32_t)(i >> 1) * 16384 + ((i & 1) ? u1 : u0);
        sts_v4(rowa + off, hsub2_bf16(q[i].x, mb0), hsub2_bf16(q[i].y, mb0), hsub2_bf16(q[i].z, mb0), hsub2_bf16(q[i].w, mb0));
        sts_v4(rowa + 1024 + off, hsub2_bf16(p[i].x, mb1), hsub2_bf16(p[i].y, mb1), hsub2_bf16(p[i].z, mb1), hsub2_bf16(p[i].w, mb1));
      }
      fence_async_smem();
      float d0 = par ? ga[0][1] + ga[1][1] : ga[0][0] + ga[1][0];
      float d1 = par ? gb[0][3] + gb[1][3] : gb[0][2] + gb[1][2];
      d0 = __shfl_sync(0xffffffffu, d0, (lane & ~3) | (g >> 1));
      d1 = __shfl_sync(0xffffffffu, d1, (lane & ~3) | (g >> 1));
      const float v0 = fmaxf(d0 * (1.f / DM) - m0 * m0, 0.f) + 1e-5f;
      const float v1 = fmaxf(d1 * (1.f / DM) - m1 * m1, 0.f) + 1e-5f;
      rs0 = rsqrtf(v0); rs1 = rsqrtf(v1);
      ir0 = v0 * rs0; ir1 = v1 * rs1;
      rl0 = rs0 * LOG2E; rl1 = rs1 * LOG2E;
      mbar_wait(bar0 + 8 * BAR_BIAS, 0);
      init_bias<16>(acca, bias_addr, ir0, ir1);
      named_bar_sync(1 + wg, 128);
      PROF(1);
    }
#pragma unroll
    for (int st = 0; st < 8; st++) {
      STAGE_BEGIN(st);
#pragma unroll
      for (int kk = 0; kk < 4; kk++) wgmma_ss_n128<1>(acca, a_lo + ((st * 16384 + kk * 32) >> 4), B_LO(st, kk * 2048, 8192));
      STAGE_END(st - 1);
      if (st == 0) zero_regs(accq);
    }
    PROF(2);
#pragma unroll
    for (int st = 0; st < 16; st++) {
      const int gs = 8 + st;
      STAGE_BEGIN(gs);
      const uint32_t as = a_lo + (((st >> 1) * 16384 + (st & 1) * 64) >> 4);
      wgmma_ss_n192<1>(accq, as, B_LO(gs, 0, 4096));
      wgmma_ss_n192<1>(accq, as + 2, B_LO(gs, 2048, 4096));
      STAGE_END(gs - 1);
      if (st == 0) fence_regs(acca);
      if (st < 8) mish_tile(acca + 8 * st, rs0, rs1, rl0, rl1, act_out + st * 32, tag);
      if (st == 7) PROF(3);
      if (st == 8) init_bias<12>(accb, bias_addr + 512, ir0, ir1);
    }
    PROF(4);
    const uint4* act_in = g_act + (size_t)(slab * 112 + 56 * khalf) * 32 + lane;
    const uint4* o_in = g_o + (size_t)(slab * 32) * 32 + lane;
    uint4 ab[4][4];
    auto a_ptr = [&](int rs, int kk) -> const uint4* {
      if (rs < 8) return act_in + (14 * (rs >> 1) + 4 * (rs & 1) + kk) * 32;
      if (rs < 16) return act_in + (14 * ((rs - 8) >> 1) + 8 + 3 * (rs & 1) + kk) * 32;
      return o_in + (4 * (rs - 16) + kk) * 32;
    };
    auto load_a = [&](int rs) {
      if (rs < 24) {
#pragma unroll
        for (int kk = 0; kk < 4; kk++) if (!(rs >= 8 && rs < 16 && kk == 3)) ab[rs & 3][kk] = ldg_frag(a_ptr(rs, kk));
      }
    };
    auto check_a = [&](int rs) {
#pragma unroll
      for (int kk = 0; kk < 4; kk++) if (!(rs >= 8 && rs < 16 && kk == 3)) validate_frag(ab[rs & 3][kk], a_ptr(rs, kk), tag);
    };
    auto keep_a = [&](int rs) {
#pragma unroll
      for (int kk = 0; kk < 4; kk++) if (!(rs >= 8 && rs < 16 && kk == 3)) fence_u4(ab[rs & 3][kk]);
    };
    uint4 pq[4];
    {
      const int m = lane >> 3, rr = lane & 7;
      const uint32_t srow = sb + OFF_D + (warp * 16 + (m & 1) * 8 + rr) * 128;
      const uint32_t ka = dlo(sb + OFF_PK + wg * 8192, 16);
      const uint32_t vb = dlo(sb + OFF_V + wg * 8192, OFF_ONES - (OFF_V + wg * 8192));
      float (&acck)[36] = reinterpret_cast<float (&)[36]>(pool[64]);
#pragma unroll
      for (int st = 0; st < 8; st++) {
        const int gs = 24 + st;
        STAGE_BEGIN(gs);
#pragma unroll
        for (int kk = 0; kk < 4; kk++) wgmma_ss_n96<1>(accb, a_lo + ((st * 16384 + kk * 32) >> 4), B_LO(gs, kk * 2048, 8192));
        if (st == 3) {
          wgmma_tt_n72<0>(acck, ka, vb);
#pragma unroll
          for (int kk = 1; kk < 4; kk++) wgmma_tt_n72<1>(acck, ka + kk * 128, vb + kk * 128);
        }
        STAGE_END(gs - 1);
        if (st >= 4) RELEASE_SLOT(5 + (st - 1) - 3);
        if (st == 0) {
          fence_regs(accq);
          pq[0] = phi_tile(accq + 64, rs0, rs1, rl0, rl1); pq[1] = phi_tile(accq + 72, rs0, rs1, rl0, rl1);
          pq[2] = phi_tile(accq + 80, rs0, rs1, rl0, rl1); pq[3] = phi_tile(accq + 88, rs0, rs1, rl0, rl1);
        } else if (st == 1) {
#pragma unroll
          for (int i = 0; i < 4; i++) {
            const uint4 r = phi_tile(accq + 8 * i, rs0, rs1, rl0, rl1);
            stmatrix_x4(srow + OFF_PK + (((2 * i + (m >> 1)) ^ rr) << 4), r.x, r.y, r.z, r.w);
          }
        } else if (st == 2) {
#pragma unroll
          for (int i = 0; i < 4; i++) {
            const float* c = accq + 32 + 8 * i;
            stmatrix_x4(srow + OFF_V + (((2 * i + (m >> 1)) ^ rr) << 4),
                        pack2(c[0] * rs0, c[1] * rs0), pack2(c[2] * rs1, c[3] * rs1), pack2(c[4] * rs0, c[5] * rs0), pack2(c[6] * rs1, c[7] * rs1));
          }
          fence_async_smem();
          named_bar_sync(1 + wg, 128);
        } else if (st == 4) {
          fence_regs(acck);
          const int wq = warp & 3;
          float* hb = &g_kv[(ep1 & 1) ^ 1][(4 * j + wq) * 272];
          float* a0p = hb + g * 16 + 2 * t;
#pragma unroll
          for (int w = 0; w < 4; w++) {
            if (wq == w) {
              red_add_v2(a0p, acck[8 * w], acck[8 * w + 1]); red_add_v2(a0p + 128, acck[8 * w + 2], acck[8 * w + 3]);
              red_add_v2(a0p + 8, acck[8 * w + 4], acck[8 * w + 5]); red_add_v2(a0p + 136, acck[8 * w + 6], acck[8 * w + 7]);
            }
          }
          if (t == 0) { red_add_f32(hb + 256 + g, acck[32]); red_add_f32(hb + 264 + g, acck[34]); }
#pragma unroll
          for (int i = 0; i < 4; i++) sts_v4(sb + OFF_KVB + warp * 2048 + i * 512 + lane * 16, 0u, 0u, 0u, 0u);
          WARP_ARRIVE(BAR_PUB_KV);
        } else if (st == 5) {
          load_a(0); load_a(1); load_a(2);
        }
        PROF(21 + st);
      }
    }
    PROF(5);
#pragma unroll
    for (int st = 0; st < 8; st++) {
      const int gs = 32 + st;
      check_a(st);
      STAGE_BEGIN(gs);
#pragma unroll
      for (int kk = 0; kk < 4; kk++) {
        if (st == 0 && kk == 0) wgmma_rs_n128<0>(accy, ab[st & 3][kk], B_LO(gs, kk * 2048, 8192));
        else wgmma_rs_n128<1>(accy, ab[st & 3][kk], B_LO(gs, kk * 2048, 8192));
      }
      if (st == 4) {
        mbar_wait(bar0 + 8 * BAR_RDY_KV, 0);
        PROF(7);
        const uint32_t kb = dlo(sb + OFF_KVB, 8192);
        wgmma_rs_n96<0>(accb, pq[0], kb);
#pragma unroll
        for (int kk = 1; kk < 4; kk++) wgmma_rs_n96<1>(accb, pq[kk], kb + kk * 128);
      }
      STAGE_END(gs - 1);
      if (st == 0) { RELEASE_SLOT(9); fence_regs(accb); }
      else keep_a(st - 1);
      if (st == 5) {
        fence_regs(accb);
#pragma unroll
        for (int kk = 0; kk < 4; kk++) fence_u4(pq[kk]);
        uint4* o_out = g_o + (size_t)(slab * 32 + 4 * j) * 32 + lane;
#pragma unroll
        for (int hh = 0; hh < 4; hh++) {
          const float i0 = __fdividef(1.f, accb[32 + 4 * hh] + 1e-6f), i1 = __fdividef(1.f, accb[34 + 4 * hh] + 1e-6f);
          const float* n = accb + 8 * hh;
          stg_frag(o_out + hh * 32, pack2(n[0] * i0, n[1] * i0), pack2(n[2] * i1, n[3] * i1), pack2(n[4] * i0, n[5] * i0), pack2(n[6] * i1, n[7] * i1), tag);
        }
      }
      load_a(st + 3);
      if (st < 2) {
#pragma unroll
        for (int i = 3 * st; i < 3 * st + 3; i++)
          mish_tile(accb + 8 * i, rs0, rs1, rl0, rl1, act_out + (8 + i) * 32, tag);
      }
      PROF(13 + st);
    }
    PROF(6);
#pragma unroll
    for (int st = 0; st < 8; st++) {
      const int gs = 40 + st, rs = 8 + st;
      check_a(rs);
      STAGE_BEGIN(gs);
#pragma unroll
      for (int kk = 0; kk < 3; kk++) wgmma_rs_n128<1>(accy, ab[rs & 3][kk], B_LO(gs, kk * 2048, 6144));
      STAGE_END(gs - 1);
      keep_a(rs - 1);
      load_a(rs + 3);
    }
    PROF(8);
#pragma unroll
    for (int st = 0; st < 8; st++) {
      const int gs = 48 + st, rs = 16 + st;
      check_a(rs);
      STAGE_BEGIN(gs);
#pragma unroll
      for (int kk = 0; kk < 4; kk++) {
        if (st == 0 && kk == 0) wgmma_rs_n64<0>(accs, ab[rs & 3][kk], B_LO(gs, kk * 2048, 8192));
        else wgmma_rs_n64<1>(accs, ab[rs & 3][kk], B_LO(gs, kk * 2048, 8192));
      }
      STAGE_END(gs - 1);
      keep_a(rs - 1);
      load_a(rs + 3);
      if (st == 0) {
        fence_regs(accy);
        float4* yp = g_yp + (size_t)((bid * 8 + warp) * 8) * 32 + lane;
#pragma unroll
        for (int q = 0; q < 8; q++) {
          const uint32_t v0 = (__float_as_uint(accy[32 + 4 * q]) & ~1u) | tag, v1 = (__float_as_uint(accy[33 + 4 * q]) & ~1u) | tag;
          const uint32_t v2 = (__float_as_uint(accy[34 + 4 * q]) & ~1u) | tag, v3 = (__float_as_uint(accy[35 + 4 * q]) & ~1u) | tag;
          asm volatile("st.relaxed.gpu.global.v4.u32 [%0], {%1,%2,%3,%4};" ::"l"(yp + q * 32), "r"(v0), "r"(v1), "r"(v2), "r"(v3) : "memory");
        }
      }
    }
    PROF(9);
    {
      const float4* yp = g_yp + (size_t)(((bid ^ 16) * 8 + warp) * 8) * 32 + lane;
      uint4 pv[8];
      uint32_t it = 0;
      wg_wait<0>();
      keep_a(23);
      fence_regs(accs);
      while (true) {
        uint32_t bad = 0;
#pragma unroll
        for (int q = 0; q < 8; q++)
          asm volatile("ld.relaxed.gpu.global.v4.u32 {%0,%1,%2,%3}, [%4];" : "=r"(pv[q].x), "=r"(pv[q].y), "=r"(pv[q].z), "=r"(pv[q].w) : "l"(yp + q * 32) : "memory");
#pragma unroll
        for (int q = 0; q < 8; q++) bad |= (pv[q].x ^ tag) | (pv[q].y ^ tag) | (pv[q].z ^ tag) | (pv[q].w ^ tag);
        if (!__any_sync(0xffffffffu, bad & 1u)) break;
        if (++it > (1u << 20)) asm volatile("trap;");
      }
      PROF(10);
      mbar_wait(bar0 + 8 * BAR_XT, 0);
      const uint32_t xa = sb + OFF_XT + lr0 * 128 + 4 * t;
#pragma unroll
      for (int q = 0; q < 8; q++) {
        const uint32_t a0 = xa + ((q ^ g) << 4), a1 = a0 + 1024;
        const uint32_t x0 = lds_u32(a0), x1 = lds_u32(a1);
        const float y0 = accy[4 * q] + __uint_as_float(pv[q].x), y1 = accy[4 * q + 1] + __uint_as_float(pv[q].y);
        const float y2 = accy[4 * q + 2] + __uint_as_float(pv[q].z), y3 = accy[4 * q + 3] + __uint_as_float(pv[q].w);
        const float o0 = fmaf(accs[4 * q], silu_f(y0), bf_lo(x0)), o1 = fmaf(accs[4 * q + 1], silu_f(y1), bf_hi(x0));
        const float o2 = fmaf(accs[4 * q + 2], silu_f(y2), bf_lo(x1)), o3 = fmaf(accs[4 * q + 3], silu_f(y3), bf_hi(x1));
        sts_u32(a0, pack2(o0, o1));
        sts_u32(a1, pack2(o2, o3));
      }
      fence_async_smem();
      __syncwarp();
      if (lane == 0) {
        asm volatile("cp.async.bulk.tensor.2d.global.shared::cta.bulk_group [%0, {%2, %3}], [%1];"
                     ::"l"(&tm_out), "r"(sb + OFF_XT + warp * 2048), "r"(128 * nt + 64 * khalf), "r"(rb * 128 + warp * 16) : "memory");
        asm volatile("cp.async.bulk.commit_group;" ::: "memory");
        asm volatile("cp.async.bulk.wait_group.read 0;" ::: "memory");
      }
    }
    PROF(11);
    if (tid == 0) red_inc(&g_done);
  }
}

typedef CUresult (*EncodeFn)(CUtensorMap*, CUtensorMapDataType, cuuint32_t, void*, const cuuint64_t*, const cuuint64_t*,
                             const cuuint32_t*, const cuuint32_t*, CUtensorMapInterleave, CUtensorMapSwizzle,
                             CUtensorMapL2promotion, CUtensorMapFloatOOBfill);

void make_map(EncodeFn enc, CUtensorMap* tm, const void* ptr, int rows, int cols, int box_rows) {
  cuuint64_t gd[2] = {(cuuint64_t)cols, (cuuint64_t)rows};
  cuuint64_t gs[1] = {(cuuint64_t)cols * 2};
  cuuint32_t bd[2] = {64, (cuuint32_t)box_rows};
  cuuint32_t es[2] = {1, 1};
  enc(tm, CU_TENSOR_MAP_DATA_TYPE_BFLOAT16, 2, const_cast<void*>(ptr), gd, gs, bd, es, CU_TENSOR_MAP_INTERLEAVE_NONE,
      CU_TENSOR_MAP_SWIZZLE_128B, CU_TENSOR_MAP_L2_PROMOTION_L2_128B, CU_TENSOR_MAP_FLOAT_OOB_FILL_NONE);
}

}

extern "C" void kernel_launch(void* const* d_in, const int* in_sizes, int n_in, void* d_out, int out_size) {
  const __nv_bfloat16* x = (const __nv_bfloat16*)d_in[0];
  const void* wqkv = d_in[1];
  const void* wo = d_in[2];
  const void* w1 = d_in[4];
  const __nv_bfloat16* b1 = (const __nv_bfloat16*)d_in[5];
  const void* w2 = d_in[6];
  static EncodeFn enc = nullptr;
  if (!enc) {
    cudaDriverEntryPointQueryResult qr;
    void* fn = nullptr;
    cudaGetDriverEntryPoint("cuTensorMapEncodeTiled", &fn, cudaEnableDefault, &qr);
    enc = (EncodeFn)fn;
    cudaFuncSetAttribute(fused_kernel, cudaFuncAttributeMaxDynamicSharedMemorySize, SMEM_ALLOC);
  }
  CUtensorMap tx, tq, t1, t2a, t2b, to, tout;
  make_map(enc, &tx, x, 2048, DM, 128);
  make_map(enc, &tq, wqkv, DM, 3 * DM, 32);
  make_map(enc, &t1, w1, DM, FF, 64);
  make_map(enc, &t2a, w2, FF, DM, 64);
  make_map(enc, &t2b, w2, FF, DM, 48);
  make_map(enc, &to, wo, DM, DM, 64);
  make_map(enc, &tout, d_out, 2048, DM, 16);
  fused_kernel<<<NCTA, 384, SMEM_ALLOC>>>(tx, tq, t1, t2a, t2b, to, tout, (const uint8_t*)wqkv, (const uint8_t*)w1,
                                          (const uint8_t*)w2, (const uint8_t*)wo, b1);
}
```

```cpp
#include <cuda_runtime.h>
#include <cuda_bf16.h>
#include <cuda.h>
#include <stdint.h>

namespace {

constexpr int DM = 512, FF = 1792;
constexpr int NCTA = 128;
constexpr int NRING = 5;
constexpr int NSLOT = 10;
constexpr int SLOT_BYTES = 16384;
constexpr int OFF_D = 0;
constexpr int OFF_PK = 0, OFF_V = 16384;
constexpr int OFF_KVB = 0;
constexpr int OFF_XT = 16384;
constexpr int OFF_RING = 131072;
constexpr int OFF_MISC = OFF_RING + NRING * SLOT_BYTES;
constexpr int OFF_ONES = OFF_MISC;
constexpr int OFF_BAR = OFF_MISC + 8192;
constexpr int OFF_B1 = OFF_MISC + 8704;
constexpr int SMEM_ALLOC = OFF_MISC + 9728;

enum { BAR_FULL = 0, BAR_EMPTY = NSLOT, BAR_X = 2 * NSLOT, BAR_BIAS = BAR_X + 4, BAR_XT,
       BAR_PUB_KV, BAR_RDY_KV, BAR_COUNT };
static_assert(BAR_COUNT <= 40, "too many barriers");

constexpr int NSTAGES = 56;
__host__ __device__ constexpr int slot_of(int gs) {
  if (gs < 32) return gs % 5;
  const int p = (gs - 32) % 10;
  return p < 5 ? 5 + p : (p - 3) % 5;
}
__host__ __device__ constexpr int use_of(int gs) {
  if (gs < 32) return gs / 5;
  const int sl = slot_of(gs);
  return (gs - 32) / 10 + (sl < 5 ? (sl < 2 ? 7 : 6) : 0);
}
__host__ __device__ constexpr int slot_off(int sl) { return sl < 5 ? OFF_RING + sl * SLOT_BYTES : OFF_D + (sl - 2) * SLOT_BYTES; }

__device__ uint4 g_act[128 * 112 * 32];
__device__ uint4 g_o[128 * 32 * 32];
__device__ float4 g_yp[NCTA * 8 * 8 * 32];
__device__ float g_kv[2][32 * 272];
__device__ unsigned g_cntKV[8 * 8];
__device__ unsigned g_done;

#define PROF(i)

__device__ __forceinline__ uint32_t smem_u32(const void* p) { return (uint32_t)__cvta_generic_to_shared(p); }
__device__ __forceinline__ void mbar_init(uint32_t bar, uint32_t cnt) { asm volatile("mbarrier.init.shared::cta.b64 [%0], %1;" ::"r"(bar), "r"(cnt)); }
__device__ __forceinline__ void mbar_expect_tx(uint32_t bar, uint32_t bytes) { asm volatile("mbarrier.arrive.expect_tx.shared::cta.b64 _, [%0], %1;" ::"r"(bar), "r"(bytes) : "memory"); }
__device__ __forceinline__ void mbar_arrive(uint32_t bar) { asm volatile("mbarrier.arrive.shared::cta.b64 _, [%0];" ::"r"(bar) : "memory"); }
__device__ __forceinline__ void mbar_wait(uint32_t bar, uint32_t parity) {
  asm volatile("{\n.reg .pred P1;\n.reg .u32 cnt;\n"
               "mbarrier.try_wait.parity.shared::cta.b64 P1, [%0], %1;\n@P1 bra DONE;\n"
               "mov.u32 cnt, 0;\n"
               "LAB_WAIT:\n"
               "mbarrier.try_wait.parity.shared::cta.b64 P1, [%0], %1;\n@P1 bra DONE;\n"
               "add.u32 cnt, cnt, 1;\nsetp.lt.u32 P1, cnt, 16777216;\n@P1 bra LAB_WAIT;\ntrap;\n"
               "DONE:\n}" ::"r"(bar), "r"(parity) : "memory");
}
__device__ __forceinline__ void tma2d(uint32_t dst, const CUtensorMap* tm, int c0, int c1, uint32_t bar) {
  asm volatile("cp.async.bulk.tensor.2d.shared::cluster.global.mbarrier::complete_tx::bytes [%0], [%1, {%3, %4}], [%2];" ::"r"(dst), "l"(tm), "r"(bar), "r"(c0), "r"(c1) : "memory");
}
__device__ __forceinline__ void tma2d_mc(uint32_t dst, const CUtensorMap* tm, int c0, int c1, uint32_t bar) {
  asm volatile("cp.async.bulk.tensor.2d.shared::cluster.global.mbarrier::complete_tx::bytes.multicast::cluster [%0], [%1, {%3, %4}], [%2], %5;"
               ::"r"(dst), "l"(tm), "r"(bar), "r"(c0), "r"(c1), "h"((uint16_t)3) : "memory");
}
__device__ __forceinline__ void mbar_arrive_remote(uint32_t bar_cluster_addr) {
  asm volatile("mbarrier.arrive.shared::cluster.b64 _, [%0];" ::"r"(bar_cluster_addr) : "memory");
}
__device__ __forceinline__ uint32_t mapa(uint32_t addr, uint32_t rank) { uint32_t r; asm volatile("mapa.shared::cluster.u32 %0, %1, %2;" : "=r"(r) : "r"(addr), "r"(rank)); return r; }
__device__ __forceinline__ void cluster_arrive() { asm volatile("barrier.cluster.arrive.relaxed.aligned;" ::: "memory"); }
__device__ __forceinline__ void cluster_wait() { asm volatile("barrier.cluster.wait.acquire.aligned;" ::: "memory"); }
__device__ __forceinline__ void wg_fence() { asm volatile("wgmma.fence.sync.aligned;" ::: "memory"); }
__device__ __forceinline__ void wg_commit() { asm volatile("wgmma.commit_group.sync.aligned;" ::: "memory"); }
template <int N> __device__ __forceinline__ void wg_wait() { asm volatile("wgmma.wait_group.sync.aligned %0;" ::"n"(N) : "memory"); }
template <int N> __device__ __forceinline__ void zero_regs(float (&d)[N]) {
#pragma unroll
  for (int i = 0; i < N; i++) d[i] = 0.f;
}
template <int N> __device__ __forceinline__ void fence_regs(float (&d)[N]) {
#pragma unroll
  for (int i = 0; i < N; i++) asm volatile("" : "+f"(d[i])::"memory");
}
__device__ __forceinline__ void fence_u4(uint4& v) { asm volatile("" : "+r"(v.x), "+r"(v.y), "+r"(v.z), "+r"(v.w)::"memory"); }
__device__ __forceinline__ void named_bar_sync(int id, int n) { asm volatile("bar.sync %0, %1;" ::"r"(id), "r"(n) : "memory"); }
__device__ __forceinline__ void fence_gpu() { asm volatile("fence.acq_rel.gpu;" ::: "memory"); }
__device__ __forceinline__ void fence_async_smem() { asm volatile("fence.proxy.async.shared::cta;" ::: "memory"); }
__device__ __forceinline__ constexpr uint32_t dlo(uint32_t addr, uint32_t lbo_bytes) { return ((addr & 0x3FFFFu) >> 4) | ((lbo_bytes >> 4) << 16); }
__device__ __forceinline__ void mma16816(float (&c)[4], uint32_t a0, uint32_t a1, uint32_t a2, uint32_t a3, uint32_t b0, uint32_t b1) {
  asm volatile("mma.sync.aligned.m16n8k16.row.col.f32.bf16.bf16.f32 {%0,%1,%2,%3}, {%4,%5,%6,%7}, {%8,%9}, {%0,%1,%2,%3};"
               : "+f"(c[0]), "+f"(c[1]), "+f"(c[2]), "+f"(c[3]) : "r"(a0), "r"(a1), "r"(a2), "r"(a3), "r"(b0), "r"(b1));
}
__device__ __forceinline__ void stmatrix_x4(uint32_t addr, uint32_t a, uint32_t b, uint32_t c, uint32_t d) {
  asm volatile("stmatrix.sync.aligned.m8n8.x4.shared.b16 [%0], {%1,%2,%3,%4};" ::"r"(addr), "r"(a), "r"(b), "r"(c), "r"(d) : "memory");
}
__device__ __forceinline__ uint32_t pack2(float lo, float hi) { uint32_t r; asm("cvt.rn.bf16x2.f32 %0, %1, %2;" : "=r"(r) : "f"(hi), "f"(lo)); return r; }
__device__ __forceinline__ float ex2(float x) { float r; asm("ex2.approx.ftz.f32 %0, %1;" : "=f"(r) : "f"(x)); return r; }
__device__ __forceinline__ float rcp(float x) { float r; asm("rcp.approx.ftz.f32 %0, %1;" : "=f"(r) : "f"(x)); return r; }
__device__ __forceinline__ float bf_lo(uint32_t v) { return __uint_as_float(v << 16); }
__device__ __forceinline__ float bf_hi(uint32_t v) { return __uint_as_float(v & 0xffff0000u); }
__device__ __forceinline__ uint32_t hsub2_bf16(uint32_t a, uint32_t b) {
  __nv_bfloat162 x = *reinterpret_cast<__nv_bfloat162*>(&a), y = *reinterpret_cast<__nv_bfloat162*>(&b);
  __nv_bfloat162 r = __hsub2(x, y);
  return *reinterpret_cast<uint32_t*>(&r);
}
__device__ __forceinline__ uint4 ldg_cg(const void* p) {
  uint4 v; asm volatile("ld.global.cg.v4.u32 {%0,%1,%2,%3}, [%4];" : "=r"(v.x), "=r"(v.y), "=r"(v.z), "=r"(v.w) : "l"(p) : "memory"); return v;
}
__device__ __forceinline__ void stg_frag(void* p, uint32_t a, uint32_t b, uint32_t c, uint32_t d, uint32_t tag) {
  asm volatile("st.relaxed.gpu.global.v4.u32 [%0], {%1,%2,%3,%4};" ::"l"(p), "r"((a & ~1u) | tag), "r"(b), "r"(c), "r"(d) : "memory");
}
__device__ __forceinline__ uint4 ldg_frag(const void* p) {
  uint4 v; asm volatile("ld.relaxed.gpu.global.v4.u32 {%0,%1,%2,%3}, [%4];" : "=r"(v.x), "=r"(v.y), "=r"(v.z), "=r"(v.w) : "l"(p) : "memory"); return v;
}
__device__ __forceinline__ void validate4(uint4 (&v)[4], const void* p, uint32_t tag4) {
  asm volatile("{\n.reg .pred P1;\n.reg .u32 cnt, tb, it;\n"
               "mov.u32 it, 0;\n"
               "LAB_CHECK:\n"
               "lop3.b32 tb, %0, %4, %8, 0x80;\nand.b32 tb, tb, %12;\n"
               "lop3.b32 cnt, %0, %4, %8, 0xFE;\nor.b32 cnt, cnt, %12;\n"
               "xor.b32 tb, tb, %17;\nxor.b32 cnt, cnt, %17;\nor.b32 tb, tb, cnt;\nand.b32 tb, tb, 1;\n"
               "setp.eq.u32 P1, tb, 0;\n@P1 bra DONE;\n"
               "ld.relaxed.gpu.global.v4.u32 {%0,%1,%2,%3}, [%16];\n"
               "ld.relaxed.gpu.global.v4.u32 {%4,%5,%6,%7}, [%16+512];\n"
               "ld.relaxed.gpu.global.v4.u32 {%8,%9,%10,%11}, [%16+1024];\n"
               "ld.relaxed.gpu.global.v4.u32 {%12,%13,%14,%15}, [%16+1536];\n"
               "add.u32 it, it, 1;\nsetp.lt.u32 P1, it, 4194304;\n@P1 bra LAB_CHECK;\ntrap;\n"
               "DONE:\n}"
               : "+r"(v[0].x), "+r"(v[0].y), "+r"(v[0].z), "+r"(v[0].w), "+r"(v[1].x), "+r"(v[1].y), "+r"(v[1].z), "+r"(v[1].w),
                 "+r"(v[2].x), "+r"(v[2].y), "+r"(v[2].z), "+r"(v[2].w), "+r"(v[3].x), "+r"(v[3].y), "+r"(v[3].z), "+r"(v[3].w)
               : "l"(p), "r"(tag4) : "memory");
}
__device__ __forceinline__ void validate3(uint4 (&v)[4], const void* p, uint32_t tag4) {
  asm volatile("{\n.reg .pred P1;\n.reg .u32 cnt, tb, it;\n"
               "mov.u32 it, 0;\n"
               "LAB_CHECK:\n"
               "lop3.b32 tb, %0, %4, %8, 0x80;\n"
               "lop3.b32 cnt, %0, %4, %8, 0xFE;\n"
               "xor.b32 tb, tb, %13;\nxor.b32 cnt, cnt, %13;\nor.b32 tb, tb, cnt;\nand.b32 tb, tb, 1;\n"
               "setp.eq.u32 P1, tb, 0;\n@P1 bra DONE;\n"
               "ld.relaxed.gpu.global.v4.u32 {%0,%1,%2,%3}, [%12];\n"
               "ld.relaxed.gpu.global.v4.u32 {%4,%5,%6,%7}, [%12+512];\n"
               "ld.relaxed.gpu.global.v4.u32 {%8,%9,%10,%11}, [%12+1024];\n"
               "add.u32 it, it, 1;\nsetp.lt.u32 P1, it, 4194304;\n@P1 bra LAB_CHECK;\ntrap;\n"
               "DONE:\n}"
               : "+r"(v[0].x), "+r"(v[0].y), "+r"(v[0].z), "+r"(v[0].w), "+r"(v[1].x), "+r"(v[1].y), "+r"(v[1].z), "+r"(v[1].w),
                 "+r"(v[2].x), "+r"(v[2].y), "+r"(v[2].z), "+r"(v[2].w)
               : "l"(p), "r"(tag4) : "memory");
}
__device__ __forceinline__ void sts_v4(uint32_t addr, uint32_t a, uint32_t b, uint32_t c, uint32_t d) {
  asm volatile("st.shared.v4.u32 [%0], {%1,%2,%3,%4};" ::"r"(addr), "r"(a), "r"(b), "r"(c), "r"(d) : "memory");
}
__device__ __forceinline__ void sts_f32(uint32_t addr, float v) { asm volatile("st.shared.f32 [%0], %1;" ::"r"(addr), "f"(v) : "memory"); }
__device__ __forceinline__ uint4 lds_v4(uint32_t addr) { uint4 v; asm volatile("ld.shared.v4.u32 {%0,%1,%2,%3}, [%4];" : "=r"(v.x), "=r"(v.y), "=r"(v.z), "=r"(v.w) : "r"(addr) : "memory"); return v; }
__device__ __forceinline__ uint32_t lds_u32(uint32_t addr) { uint32_t v; asm volatile("ld.shared.u32 %0, [%1];" : "=r"(v) : "r"(addr) : "memory"); return v; }
__device__ __forceinline__ void sts_u32(uint32_t addr, uint32_t v) { asm volatile("st.shared.u32 [%0], %1;" ::"r"(addr), "r"(v) : "memory"); }
__device__ __forceinline__ float2 lds_f32x2(uint32_t addr) { float2 v; asm volatile("ld.shared.v2.f32 {%0,%1}, [%2];" : "=f"(v.x), "=f"(v.y) : "r"(addr) : "memory"); return v; }
__device__ __forceinline__ void red_add_v2(float* p, float a, float b) { asm volatile("red.relaxed.gpu.global.add.v2.f32 [%0], {%1,%2};" ::"l"(p), "f"(a), "f"(b) : "memory"); }
__device__ __forceinline__ void red_add_f32(float* p, float a) { asm volatile("red.relaxed.gpu.global.add.f32 [%0], %1;" ::"l"(p), "f"(a) : "memory"); }
__device__ __forceinline__ void red_inc(unsigned* cnt) { asm volatile("red.relaxed.gpu.global.add.u32 [%0], 1;" ::"l"(cnt) : "memory"); }
__device__ __forceinline__ void poll_ge(const unsigned* cnt, unsigned target) {
  asm volatile("{\n.reg .pred P1;\n.reg .u32 cnt, v;\n.reg .s32 d;\n"
               "mov.u32 cnt, 0;\n"
               "LAB_POLL:\n"
               "ld.relaxed.gpu.global.u32 v, [%0];\nsub.s32 d, v, %1;\nsetp.ge.s32 P1, d, 0;\n@P1 bra DONE;\n"
               "add.u32 cnt, cnt, 1;\nsetp.lt.u32 P1, cnt, 4194304;\n@P1 bra LAB_POLL;\ntrap;\n"
               "DONE:\nld.acquire.gpu.global.u32 v, [%0];\n}" ::"l"(cnt), "r"(target) : "memory");
}

template <int SCALE_D> __device__ __forceinline__ void wgmma_ss_n192(float (&d)[96], uint32_t da, uint32_t db) {
  asm volatile("{\n.reg .b64 da, db;\nmov.b64 da, {%96, %98};\nmov.b64 db, {%97, %98};\n"
    "wgmma.mma_async.sync.aligned.m64n192k16.f32.bf16.bf16 {%0, %1, %2, %3, %4, %5, %6, %7, %8, %9, %10, %11, %12, %13, %14, %15, %16, %17, %18, %19, %20, %21, %22, %23, %24, %25, %26, %27, %28, %29, %30, %31, %32, %33, %34, %35, %36, %37, %38, %39, %40, %41, %42, %43, %44, %45, %46, %47, %48, %49, %50, %51, %52, %53, %54, %55, %56, %57, %58, %59, %60, %61, %62, %63, %64, %65, %66, %67, %68, %69, %70, %71, %72, %73, %74, %75, %76, %77, %78, %79, %80, %81, %82, %83, %84, %85, %86, %87, %88, %89, %90, %91, %92, %93, %94, %95}, da, db, %99, 1, 1, 0, 1;\n}\n"
    : "+f"(d[0]), "+f"(d[1]), "+f"(d[2]), "+f"(d[3]), "+f"(d[4]), "+f"(d[5]), "+f"(d[6]), "+f"(d[7]), "+f"(d[8]), "+f"(d[9]), "+f"(d[10]), "+f"(d[11]), "+f"(d[12]), "+f"(d[13]), "+f"(d[14]), "+f"(d[15]), "+f"(d[16]), "+f"(d[17]), "+f"(d[18]), "+f"(d[19]), "+f"(d[20]), "+f"(d[21]), "+f"(d[22]), "+f"(d[23]), "+f"(d[24]), "+f"(d[25]), "+f"(d[26]), "+f"(d[27]), "+f"(d[28]), "+f"(d[29]), "+f"(d[30]), "+f"(d[31]), "+f"(d[32]), "+f"(d[33]), "+f"(d[34]), "+f"(d[35]), "+f"(d[36]), "+f"(d[37]), "+f"(d[38]), "+f"(d[39]), "+f"(d[40]), "+f"(d[41]), "+f"(d[42]), "+f"(d[43]), "+f"(d[44]), "+f"(d[45]), "+f"(d[46]), "+f"(d[47]), "+f"(d[48]), "+f"(d[49]), "+f"(d[50]), "+f"(d[51]), "+f"(d[52]), "+f"(d[53]), "+f"(d[54]), "+f"(d[55]), "+f"(d[56]), "+f"(d[57]), "+f"(d[58]), "+f"(d[59]), "+f"(d[60]), "+f"(d[61]), "+f"(d[62]), "+f"(d[63]), "+f"(d[64]), "+f"(d[65]), "+f"(d[66]), "+f"(d[67]), "+f"(d[68]), "+f"(d[69]), "+f"(d[70]), "+f"(d[71]), "+f"(d[72]), "+f"(d[73]), "+f"(d[74]), "+f"(d[75]), "+f"(d[76]), "+f"(d[77]), "+f"(d[78]), "+f"(d[79]), "+f"(d[80]), "+f"(d[81]), "+f"(d[82]), "+f"(d[83]), "+f"(d[84]), "+f"(d[85]), "+f"(d[86]), "+f"(d[87]), "+f"(d[88]), "+f"(d[89]), "+f"(d[90]), "+f"(d[91]), "+f"(d[92]), "+f"(d[93]), "+f"(d[94]), "+f"(d[95])
    : "r"(da), "r"(db), "r"(0x40000040u), "n"(SCALE_D));
}
template <int SCALE_D> __device__ __forceinline__ void wgmma_ss_n128(float (&d)[64], uint32_t da, uint32_t db) {
  asm volatile("{\n.reg .b64 da, db;\nmov.b64 da, {%64, %66};\nmov.b64 db, {%65, %66};\n"
    "wgmma.mma_async.sync.aligned.m64n128k16.f32.bf16.bf16 {%0, %1, %2, %3, %4, %5, %6, %7, %8, %9, %10, %11, %12, %13, %14, %15, %16, %17, %18, %19, %20, %21, %22, %23, %24, %25, %26, %27, %28, %29, %30, %31, %32, %33, %34, %35, %36, %37, %38, %39, %40, %41, %42, %43, %44, %45, %46, %47, %48, %49, %50, %51, %52, %53, %54, %55, %56, %57, %58, %59, %60, %61, %62, %63}, da, db, %67, 1, 1, 0, 1;\n}\n"
    : "+f"(d[0]), "+f"(d[1]), "+f"(d[2]), "+f"(d[3]), "+f"(d[4]), "+f"(d[5]), "+f"(d[6]), "+f"(d[7]), "+f"(d[8]), "+f"(d[9]), "+f"(d[10]), "+f"(d[11]), "+f"(d[12]), "+f"(d[13]), "+f"(d[14]), "+f"(d[15]), "+f"(d[16]), "+f"(d[17]), "+f"(d[18]), "+f"(d[19]), "+f"(d[20]), "+f"(d[21]), "+f"(d[22]), "+f"(d[23]), "+f"(d[24]), "+f"(d[25]), "+f"(d[26]), "+f"(d[27]), "+f"(d[28]), "+f"(d[29]), "+f"(d[30]), "+f"(d[31]), "+f"(d[32]), "+f"(d[33]), "+f"(d[34]), "+f"(d[35]), "+f"(d[36]), "+f"(d[37]), "+f"(d[38]), "+f"(d[39]), "+f"(d[40]), "+f"(d[41]), "+f"(d[42]), "+f"(d[43]), "+f"(d[44]), "+f"(d[45]), "+f"(d[46]), "+f"(d[47]), "+f"(d[48]), "+f"(d[49]), "+f"(d[50]), "+f"(d[51]), "+f"(d[52]), "+f"(d[53]), "+f"(d[54]), "+f"(d[55]), "+f"(d[56]), "+f"(d[57]), "+f"(d[58]), "+f"(d[59]), "+f"(d[60]), "+f"(d[61]), "+f"(d[62]), "+f"(d[63])
    : "r"(da), "r"(db), "r"(0x40000040u), "n"(SCALE_D));
}
template <int SCALE_D> __device__ __forceinline__ void wgmma_ss_n96(float (&d)[48], uint32_t da, uint32_t db) {
  asm volatile("{\n.reg .b64 da, db;\nmov.b64 da, {%48, %50};\nmov.b64 db, {%49, %50};\n"
    "wgmma.mma_async.sync.aligned.m64n96k16.f32.bf16.bf16 {%0, %1, %2, %3, %4, %5, %6, %7, %8, %9, %10, %11, %12, %13, %14, %15, %16, %17, %18, %19, %20, %21, %22, %23, %24, %25, %26, %27, %28, %29, %30, %31, %32, %33, %34, %35, %36, %37, %38, %39, %40, %41, %42, %43, %44, %45, %46, %47}, da, db, %51, 1, 1, 0, 1;\n}\n"
    : "+f"(d[0]), "+f"(d[1]), "+f"(d[2]), "+f"(d[3]), "+f"(d[4]), "+f"(d[5]), "+f"(d[6]), "+f"(d[7]), "+f"(d[8]), "+f"(d[9]), "+f"(d[10]), "+f"(d[11]), "+f"(d[12]), "+f"(d[13]), "+f"(d[14]), "+f"(d[15]), "+f"(d[16]), "+f"(d[17]), "+f"(d[18]), "+f"(d[19]), "+f"(d[20]), "+f"(d[21]), "+f"(d[22]), "+f"(d[23]), "+f"(d[24]), "+f"(d[25]), "+f"(d[26]), "+f"(d[27]), "+f"(d[28]), "+f"(d[29]), "+f"(d[30]), "+f"(d[31]), "+f"(d[32]), "+f"(d[33]), "+f"(d[34]), "+f"(d[35]), "+f"(d[36]), "+f"(d[37]), "+f"(d[38]), "+f"(d[39]), "+f"(d[40]), "+f"(d[41]), "+f"(d[42]), "+f"(d[43]), "+f"(d[44]), "+f"(d[45]), "+f"(d[46]), "+f"(d[47])
    : "r"(da), "r"(db), "r"(0x40000040u), "n"(SCALE_D));
}
template <int SCALE_D> __device__ __forceinline__ void wgmma_tt_n72(float (&d)[36], uint32_t da, uint32_t db) {
  asm volatile("{\n.reg .b64 da, db;\nmov.b64 da, {%36, %38};\nmov.b64 db, {%37, %38};\n"
    "wgmma.mma_async.sync.aligned.m64n72k16.f32.bf16.bf16 {%0, %1, %2, %3, %4, %5, %6, %7, %8, %9, %10, %11, %12, %13, %14, %15, %16, %17, %18, %19, %20, %21, %22, %23, %24, %25, %26, %27, %28, %29, %30, %31, %32, %33, %34, %35}, da, db, %39, 1, 1, 1, 1;\n}\n"
    : "+f"(d[0]), "+f"(d[1]), "+f"(d[2]), "+f"(d[3]), "+f"(d[4]), "+f"(d[5]), "+f"(d[6]), "+f"(d[7]), "+f"(d[8]), "+f"(d[9]), "+f"(d[10]), "+f"(d[11]), "+f"(d[12]), "+f"(d[13]), "+f"(d[14]), "+f"(d[15]), "+f"(d[16]), "+f"(d[17]), "+f"(d[18]), "+f"(d[19]), "+f"(d[20]), "+f"(d[21]), "+f"(d[22]), "+f"(d[23]), "+f"(d[24]), "+f"(d[25]), "+f"(d[26]), "+f"(d[27]), "+f"(d[28]), "+f"(d[29]), "+f"(d[30]), "+f"(d[31]), "+f"(d[32]), "+f"(d[33]), "+f"(d[34]), "+f"(d[35])
    : "r"(da), "r"(db), "r"(0x40000040u), "n"(SCALE_D));
}
template <int SCALE_D> __device__ __forceinline__ void wgmma_rs_n128(float (&d)[64], const uint4& a, uint32_t db) {
  asm volatile("{\n.reg .b64 db;\nmov.b64 db, {%68, %69};\n"
    "wgmma.mma_async.sync.aligned.m64n128k16.f32.bf16.bf16 {%0, %1, %2, %3, %4, %5, %6, %7, %8, %9, %10, %11, %12, %13, %14, %15, %16, %17, %18, %19, %20, %21, %22, %23, %24, %25, %26, %27, %28, %29, %30, %31, %32, %33, %34, %35, %36, %37, %38, %39, %40, %41, %42, %43, %44, %45, %46, %47, %48, %49, %50, %51, %52, %53, %54, %55, %56, %57, %58, %59, %60, %61, %62, %63}, {%64, %65, %66, %67}, db, %70, 1, 1, 1;\n}\n"
    : "+f"(d[0]), "+f"(d[1]), "+f"(d[2]), "+f"(d[3]), "+f"(d[4]), "+f"(d[5]), "+f"(d[6]), "+f"(d[7]), "+f"(d[8]), "+f"(d[9]), "+f"(d[10]), "+f"(d[11]), "+f"(d[12]), "+f"(d[13]), "+f"(d[14]), "+f"(d[15]), "+f"(d[16]), "+f"(d[17]), "+f"(d[18]), "+f"(d[19]), "+f"(d[20]), "+f"(d[21]), "+f"(d[22]), "+f"(d[23]), "+f"(d[24]), "+f"(d[25]), "+f"(d[26]), "+f"(d[27]), "+f"(d[28]), "+f"(d[29]), "+f"(d[30]), "+f"(d[31]), "+f"(d[32]), "+f"(d[33]), "+f"(d[34]), "+f"(d[35]), "+f"(d[36]), "+f"(d[37]), "+f"(d[38]), "+f"(d[39]), "+f"(d[40]), "+f"(d[41]), "+f"(d[42]), "+f"(d[43]), "+f"(d[44]), "+f"(d[45]), "+f"(d[46]), "+f"(d[47]), "+f"(d[48]), "+f"(d[49]), "+f"(d[50]), "+f"(d[51]), "+f"(d[52]), "+f"(d[53]), "+f"(d[54]), "+f"(d[55]), "+f"(d[56]), "+f"(d[57]), "+f"(d[58]), "+f"(d[59]), "+f"(d[60]), "+f"(d[61]), "+f"(d[62]), "+f"(d[63])
    : "r"(a.x), "r"(a.y), "r"(a.z), "r"(a.w), "r"(db), "r"(0x40000040u), "n"(SCALE_D));
}
template <int SCALE_D> __device__ __forceinline__ void wgmma_rs_n96(float (&d)[48], const uint4& a, uint32_t db) {
  asm volatile("{\n.reg .b64 db;\nmov.b64 db, {%52, %53};\n"
    "wgmma.mma_async.sync.aligned.m64n96k16.f32.bf16.bf16 {%0, %1, %2, %3, %4, %5, %6, %7, %8, %9, %10, %11, %12, %13, %14, %15, %16, %17, %18, %19, %20, %21, %22, %23, %24, %25, %26, %27, %28, %29, %30, %31, %32, %33, %34, %35, %36, %37, %38, %39, %40, %41, %42, %43, %44, %45, %46, %47}, {%48, %49, %50, %51}, db, %54, 1, 1, 1;\n}\n"
    : "+f"(d[0]), "+f"(d[1]), "+f"(d[2]), "+f"(d[3]), "+f"(d[4]), "+f"(d[5]), "+f"(d[6]), "+f"(d[7]), "+f"(d[8]), "+f"(d[9]), "+f"(d[10]), "+f"(d[11]), "+f"(d[12]), "+f"(d[13]), "+f"(d[14]), "+f"(d[15]), "+f"(d[16]), "+f"(d[17]), "+f"(d[18]), "+f"(d[19]), "+f"(d[20]), "+f"(d[21]), "+f"(d[22]), "+f"(d[23]), "+f"(d[24]), "+f"(d[25]), "+f"(d[26]), "+f"(d[27]), "+f"(d[28]), "+f"(d[29]), "+f"(d[30]), "+f"(d[31]), "+f"(d[32]), "+f"(d[33]), "+f"(d[34]), "+f"(d[35]), "+f"(d[36]), "+f"(d[37]), "+f"(d[38]), "+f"(d[39]), "+f"(d[40]), "+f"(d[41]), "+f"(d[42]), "+f"(d[43]), "+f"(d[44]), "+f"(d[45]), "+f"(d[46]), "+f"(d[47])
    : "r"(a.x), "r"(a.y), "r"(a.z), "r"(a.w), "r"(db), "r"(0x40000040u), "n"(SCALE_D));
}
template <int SCALE_D> __device__ __forceinline__ void wgmma_rs_n64(float (&d)[32], const uint4& a, uint32_t db) {
  asm volatile("{\n.reg .b64 db;\nmov.b64 db, {%36, %37};\n"
    "wgmma.mma_async.sync.aligned.m64n64k16.f32.bf16.bf16 {%0, %1, %2, %3, %4, %5, %6, %7, %8, %9, %10, %11, %12, %13, %14, %15, %16, %17, %18, %19, %20, %21, %22, %23, %24, %25, %26, %27, %28, %29, %30, %31}, {%32, %33, %34, %35}, db, %38, 1, 1, 1;\n}\n"
    : "+f"(d[0]), "+f"(d[1]), "+f"(d[2]), "+f"(d[3]), "+f"(d[4]), "+f"(d[5]), "+f"(d[6]), "+f"(d[7]), "+f"(d[8]), "+f"(d[9]), "+f"(d[10]), "+f"(d[11]), "+f"(d[12]), "+f"(d[13]), "+f"(d[14]), "+f"(d[15]), "+f"(d[16]), "+f"(d[17]), "+f"(d[18]), "+f"(d[19]), "+f"(d[20]), "+f"(d[21]), "+f"(d[22]), "+f"(d[23]), "+f"(d[24]), "+f"(d[25]), "+f"(d[26]), "+f"(d[27]), "+f"(d[28]), "+f"(d[29]), "+f"(d[30]), "+f"(d[31])
    : "r"(a.x), "r"(a.y), "r"(a.z), "r"(a.w), "r"(db), "r"(0x40000040u), "n"(SCALE_D));
}

constexpr float LOG2E = 1.4426950408889634f;
__device__ __forceinline__ float silu_f(float y) { return y * rcp(1.f + ex2(-y * LOG2E)); }

__device__ __forceinline__ void mish_tile(const float* c, float rs0, float rs1, float rl0, float rl1, uint4* dst, uint32_t tag) {
  float h[8], u[8], r[8];
#pragma unroll
  for (int i = 0; i < 8; i++) {
    const bool hi = (i >> 1) & 1;
    h[i] = c[i] * (hi ? rs1 : rs0);
    u[i] = ex2(fminf(c[i] * (hi ? rl1 : rl0), 28.853900817779268f));
  }
#pragma unroll
  for (int i = 0; i < 8; i++) { const float tt = u[i] + 2.f; r[i] = rcp(fmaf(u[i], tt, 2.f)); h[i] *= u[i] * tt; }
#pragma unroll
  for (int i = 0; i < 8; i++) h[i] *= r[i];
  stg_frag(dst, pack2(h[0], h[1]), pack2(h[2], h[3]), pack2(h[4], h[5]), pack2(h[6], h[7]), tag);
}
__device__ __forceinline__ float phi_c(float c, float rs, float rl) {
  const float e = ex2(c * rl) + 1e-6f;
  const float p = fmaf(c, rs, 1.000001f);
  return c > 0.f ? p : e;
}
__device__ __forceinline__ uint4 phi_tile(const float* c, float rs0, float rs1, float rl0, float rl1) {
  uint4 r;
  r.x = pack2(phi_c(c[0], rs0, rl0), phi_c(c[1], rs0, rl0)); r.y = pack2(phi_c(c[2], rs1, rl1), phi_c(c[3], rs1, rl1));
  r.z = pack2(phi_c(c[4], rs0, rl0), phi_c(c[5], rs0, rl0)); r.w = pack2(phi_c(c[6], rs1, rl1), phi_c(c[7], rs1, rl1));
  return r;
}
template <int NB> __device__ __forceinline__ void init_bias(float* acc, uint32_t bias_addr, float ir0, float ir1) {
#pragma unroll
  for (int nb = 0; nb < NB; nb++) {
    const float2 b = lds_f32x2(bias_addr + 32 * nb);
    acc[4 * nb] = b.x * ir0; acc[4 * nb + 1] = b.y * ir0; acc[4 * nb + 2] = b.x * ir1; acc[4 * nb + 3] = b.y * ir1;
  }
}

__global__ void __cluster_dims__(2, 1, 1) __launch_bounds__(384, 1)
fused_kernel(const __grid_constant__ CUtensorMap tm_x, const __grid_constant__ CUtensorMap tm_qkv,
             const __grid_constant__ CUtensorMap tm_w1, const __grid_constant__ CUtensorMap tm_w2a,
             const __grid_constant__ CUtensorMap tm_w2b, const __grid_constant__ CUtensorMap tm_wo,
             const __grid_constant__ CUtensorMap tm_out,
             const uint8_t* __restrict__ wqkv, const uint8_t* __restrict__ w1, const uint8_t* __restrict__ w2,
             const uint8_t* __restrict__ wo, const __nv_bfloat16* __restrict__ b1) {
  extern __shared__ __align__(1024) uint8_t smem_raw[];
  const uint32_t sb = smem_u32(smem_raw);
  const int tid = threadIdx.x, lane = tid & 31;
  const int warp = __shfl_sync(0xffffffffu, tid >> 5, 0);
  const int bid = blockIdx.x;
  const int crank = bid & 1, pidx = bid >> 1;
  const int nt = pidx & 3, khalf = (pidx >> 2) & 1;
  const int rb = (pidx >> 3) * 2 + crank;
  const int j = khalf + 2 * nt;
  const uint32_t bar0 = sb + OFF_BAR;
  PROF(0);

  if (warp >= 8) {
    asm volatile("setmaxnreg.dec.sync.aligned.u32 40;");
    if (warp == 8) {
      if (lane == 0) {
        if (sb & 1023u) asm volatile("trap;");
        for (int i = 0; i < NSLOT; i++) { mbar_init(bar0 + 8 * (BAR_FULL + i), 1); mbar_init(bar0 + 8 * (BAR_EMPTY + i), 16); }
        for (int i = BAR_X; i <= BAR_XT; i++) mbar_init(bar0 + 8 * i, 1);
        mbar_init(bar0 + 8 * BAR_PUB_KV, 8);
        mbar_init(bar0 + 8 * BAR_RDY_KV, 2);
        asm volatile("fence.mbarrier_init.release.cluster;" ::: "memory");
        fence_async_smem();
        for (int i = 0; i < 4; i++) {
          mbar_expect_tx(bar0 + 8 * (BAR_X + i), 32768);
          tma2d(sb + OFF_D + (2 * i) * 16384, &tm_x, 128 * i, rb * 128, bar0 + 8 * (BAR_X + i));
          tma2d(sb + OFF_D + (2 * i + 1) * 16384, &tm_x, 128 * i + 64, rb * 128, bar0 + 8 * (BAR_X + i));
        }
      }
      __syncwarp();
      cluster_arrive(); cluster_wait();
      if (lane == 0) {
        const int c_own = 128 * nt + 64 * khalf, c_par = 128 * nt + 64 * (1 - khalf);
#pragma unroll 1
        for (int st = 0; st < NSTAGES; st++) {
          const int slot = slot_of(st), use = use_of(st);
          const uint32_t full = bar0 + 8 * (BAR_FULL + slot);
          const uint32_t dst = sb + slot_off(slot);
          mbar_wait(bar0 + 8 * (BAR_EMPTY + slot), (use & 1) ^ (slot < 5 ? 1 : 0));
          if (st < 8) {
            mbar_expect_tx(full, 16384);
            tma2d_mc(dst + crank * 8192, &tm_w1, 224 * j + 64 * crank, 64 * st, full);
          } else if (st < 24) {
            mbar_expect_tx(full, 12288);
            const int k0 = 32 * (st - 8) + 16 * crank;
            tma2d_mc(dst + crank * 2048, &tm_qkv, 512 + 64 * j, k0, full);
            tma2d_mc(dst + 4096 + crank * 2048, &tm_qkv, 1024 + 64 * j, k0, full);
            tma2d_mc(dst + 8192 + crank * 2048, &tm_qkv, 64 * j, k0, full);
          } else if (st < 32) {
            mbar_expect_tx(full, 16384);
            tma2d_mc(dst + crank * 8192, &tm_w1, 224 * j + 128 + 64 * crank, 64 * (st - 24), full);
          } else if (st < 40) {
            mbar_expect_tx(full, 16384);
            const int i = st - 32;
            const int k0 = 224 * (4 * khalf + (i >> 1)) + 64 * (i & 1);
            tma2d_mc(dst + crank * 8192, &tm_w2a, crank ? c_par : c_own, k0, full);
          } else if (st < 48) {
            if (st == 40) {
              mbar_wait(bar0 + 8 * BAR_PUB_KV, 0);
              mbar_expect_tx(bar0 + 8 * BAR_XT, 16384);
              tma2d(sb + OFF_XT, &tm_x, c_own, rb * 128, bar0 + 8 * BAR_XT);
            }
            mbar_expect_tx(full, 12288);
            const int i = st - 40;
            const int k0 = 224 * (4 * khalf + (i >> 1)) + 128 + 48 * (i & 1);
            tma2d_mc(dst + crank * 6144, &tm_w2b, crank ? c_par : c_own, k0, full);
          } else {
            mbar_expect_tx(full, 8192);
            tma2d_mc(dst + crank * 4096, &tm_wo, c_own, 64 * (st - 48) + 32 * crank, full);
          }
        }
      }
      __syncwarp();
      cluster_arrive(); cluster_wait();
    } else {
      const int aw = warp - 9;
      unsigned dn; asm volatile("ld.relaxed.gpu.global.u32 %0, [%1];" : "=r"(dn) : "l"(&g_done) : "memory");
      cluster_arrive(); cluster_wait();
      const unsigned ep1 = dn / NCTA + 1u;
      if (aw == 0) {
        for (int i = lane; i < 224; i += 32) sts_f32(sb + OFF_B1 + 4 * i, __bfloat162float(b1[224 * j + i]));
#pragma unroll 4
        for (int i = 0; i < 16; i++) sts_v4(sb + OFF_ONES + (i * 32 + lane) * 16, 0x3F803F80u, 0x3F803F80u, 0x3F803F80u, 0x3F803F80u);
        fence_async_smem();
        __syncwarp();
        if (lane == 0) {
          mbar_arrive(bar0 + 8 * BAR_BIAS);
          mbar_wait(bar0 + 8 * BAR_PUB_KV, 0); PROF(3); fence_gpu(); red_inc(&g_cntKV[j * 8]); PROF(4);
        }
      } else {
        const int h0 = 2 * (aw - 1);
        if (aw == 1 && lane < 4) {
          const uint8_t* base = lane == 0 ? wqkv : lane == 1 ? w1 : lane == 2 ? w2 : wo;
          const uint32_t bytes = lane == 0 ? 12288u : lane == 3 ? 4096u : 14336u;
          asm volatile("cp.async.bulk.prefetch.L2.global [%0], %1;" ::"l"(base + (size_t)bid * bytes), "r"(bytes) : "memory");
        }
        if (rb == 0) {
          float4* z = reinterpret_cast<float4*>(&g_kv[ep1 & 1][(4 * j + h0) * 272]);
          for (int i = lane; i < 136; i += 32) z[i] = make_float4(0.f, 0.f, 0.f, 0.f);
        }
        const float* kvbuf = &g_kv[(ep1 & 1) ^ 1][(4 * j + h0) * 272];
        mbar_wait(bar0 + 8 * BAR_PUB_KV, 0);
        PROF(1);
        if (lane == 0) poll_ge(&g_cntKV[j * 8], 16u * ep1);
        __syncwarp();
        PROF(2);
        {
          const int d = lane >> 1, hf = lane & 1;
          const float* src = kvbuf + d * 16 + hf * 8;
          const uint32_t dst = sb + OFF_KVB + d * 128 + h0 * 2048;
          uint4 v[2][2]; float zz[2];
#pragma unroll
          for (int q = 0; q < 2; q++) {
            v[q][0] = ldg_cg(src + q * 272); v[q][1] = ldg_cg(src + q * 272 + 4);
            asm volatile("ld.global.cg.f32 %0, [%1];" : "=f"(zz[q]) : "l"(kvbuf + q * 272 + 256 + d) : "memory");
          }
#pragma unroll
          for (int q = 0; q < 2; q++) {
            const int hh = h0 + q;
            sts_v4(dst + q * 2048 + (((2 * hh + hf) ^ (d & 7)) << 4),
                   pack2(__uint_as_float(v[q][0].x), __uint_as_float(v[q][0].y)), pack2(__uint_as_float(v[q][0].z), __uint_as_float(v[q][0].w)),
                   pack2(__uint_as_float(v[q][1].x), __uint_as_float(v[q][1].y)), pack2(__uint_as_float(v[q][1].z), __uint_as_float(v[q][1].w)));
            const uint32_t z2 = pack2(zz[q], zz[q]);
            if (hf == 0) sts_v4(dst + 8192 + q * 2048 + ((hh ^ (d & 7)) << 4), z2, z2, z2, z2);
          }
        }
        fence_async_smem();
        __syncwarp();
        if (lane == 0) mbar_arrive(bar0 + 8 * BAR_RDY_KV);
        PROF(3);
      }
      __syncwarp();
      cluster_arrive(); cluster_wait();
    }
  } else {
    asm volatile("setmaxnreg.inc.sync.aligned.u32 232;");
    const int wg = warp >> 2;
    const int g = lane >> 2, t = lane & 3;
    const int lr0 = warp * 16 + g;
    const int slab = rb * 8 + warp;
    unsigned dn; asm volatile("ld.relaxed.gpu.global.u32 %0, [%1];" : "=r"(dn) : "l"(&g_done) : "memory");
    const uint32_t a_lo = dlo(sb + OFF_D + wg * 8192, 16);
    const uint32_t sb_lo = (sb & 0x3FFFFu) >> 4;
    const uint32_t ebar_l = mapa(bar0 + 8 * BAR_EMPTY, lane & 1);

#define B_LO(gs, off, lbo) (sb_lo + ((slot_off(slot_of(gs)) + (off)) >> 4) + (((lbo) >> 4) << 16))
#define STAGE_BEGIN(gs) do { mbar_wait(bar0 + 8 * (BAR_FULL + slot_of(gs)), use_of(gs) & 1); wg_fence(); } while (0)
#define RELEASE_SLOT(sl) do { if (lane < 2) mbar_arrive_remote(ebar_l + 8 * (sl)); } while (0)
#define STAGE_END(prev) do { wg_commit(); wg_wait<1>(); if ((prev) >= 0 && (prev) < 46) RELEASE_SLOT(slot_of((prev) < 0 ? 0 : (prev))); } while (0)
#define WARP_ARRIVE(b) do { __syncwarp(); if (lane == 0) mbar_arrive(bar0 + 8 * (b)); } while (0)

    uint4* act_out = g_act + (size_t)(slab * 112 + 14 * j) * 32 + lane;
    const uint32_t bias_addr = sb + OFF_B1 + 8 * t;
    float rs0, rs1;
    float pool[160];
    float (&acca)[64] = reinterpret_cast<float (&)[64]>(pool[0]);
    float (&accq)[96] = reinterpret_cast<float (&)[96]>(pool[64]);
    float (&accb)[48] = reinterpret_cast<float (&)[48]>(pool[0]);
    float (&accy)[64] = reinterpret_cast<float (&)[64]>(pool[64]);
    float (&accs)[32] = reinterpret_cast<float (&)[32]>(pool[0]);
    float rl0, rl1, ir0, ir1;
    const unsigned ep1 = dn / NCTA + 1u;
    const uint32_t tag = ep1 & 1u;
    {
      uint4 q[16], p[16];
      const int par = g & 1;
      const uint32_t rowa = sb + OFF_D + lr0 * 128;
      const uint32_t u0 = (uint32_t)(((par * 4 + t) ^ g) << 4), u1 = u0 ^ 64u;
      cluster_arrive(); cluster_wait();
      float sm[2][4], ga[2][4], gb[2][4];
#pragma unroll
      for (int a = 0; a < 2; a++) {
        sm[a][0] = sm[a][1] = sm[a][2] = sm[a][3] = 0.f;
        ga[a][0] = ga[a][1] = ga[a][2] = ga[a][3] = 0.f;
        gb[a][0] = gb[a][1] = gb[a][2] = gb[a][3] = 0.f;
      }
      const uint32_t ones = 0x3F803F80u;
#pragma unroll
      for (int c = 0; c < 8; c++) {
        if ((c & 1) == 0) mbar_wait(bar0 + 8 * (BAR_X + (c >> 1)), 0);
        q[2 * c] = lds_v4(rowa + c * 16384 + u0);     p[2 * c] = lds_v4(rowa + c * 16384 + 1024 + u0);
        q[2 * c + 1] = lds_v4(rowa + c * 16384 + u1); p[2 * c + 1] = lds_v4(rowa + c * 16384 + 1024 + u1);
#pragma unroll
        for (int h = 0; h < 2; h++) {
          const int i = 2 * c + h;
          mma16816(sm[0], q[i].x, p[i].x, q[i].y, p[i].y, ones, ones);
          mma16816(sm[1], q[i].z, p[i].z, q[i].w, p[i].w, ones, ones);
          mma16816(ga[0], q[i].x, p[i].x, q[i].y, p[i].y, q[i].x, q[i].y);
          mma16816(ga[1], q[i].z, p[i].z, q[i].w, p[i].w, q[i].z, q[i].w);
          mma16816(gb[0], q[i].x, p[i].x, q[i].y, p[i].y, p[i].x, p[i].y);
          mma16816(gb[1], q[i].z, p[i].z, q[i].w, p[i].w, p[i].z, p[i].w);
        }
      }
      const float m0 = (sm[0][0] + sm[1][0]) * (1.f / DM);
      const float m1 = (sm[0][2] + sm[1][2]) * (1.f / DM);
      const uint32_t mb0 = pack2(m0, m0), mb1 = pack2(m1, m1);
      PROF(12);
#pragma unroll
      for (int i = 0; i < 16; i++) {
        const uint32_t off = (uint32_t)(i >> 1) * 16384 + ((i & 1) ? u1 : u0);
        sts_v4(rowa + off, hsub2_bf16(q[i].x, mb0), hsub2_bf16(q[i].y, mb0), hsub2_bf16(q[i].z, mb0), hsub2_bf16(q[i].w, mb0));
        sts_v4(rowa + 1024 + off, hsub2_bf16(p[i].x, mb1), hsub2_bf16(p[i].y, mb1), hsub2_bf16(p[i].z, mb1), hsub2_bf16(p[i].w, mb1));
      }
      fence_async_smem();
      float d0 = par ? ga[0][1] + ga[1][1] : ga[0][0] + ga[1][0];
      float d1 = par ? gb[0][3] + gb[1][3] : gb[0][2] + gb[1][2];
      d0 = __shfl_sync(0xffffffffu, d0, (lane & ~3) | (g >> 1));
      d1 = __shfl_sync(0xffffffffu, d1, (lane & ~3) | (g >> 1));
      const float v0 = fmaxf(d0 * (1.f / DM) - m0 * m0, 0.f) + 1e-5f;
      const float v1 = fmaxf(d1 * (1.f / DM) - m1 * m1, 0.f) + 1e-5f;
      rs0 = rsqrtf(v0); rs1 = rsqrtf(v1);
      ir0 = v0 * rs0; ir1 = v1 * rs1;
      rl0 = rs0 * LOG2E; rl1 = rs1 * LOG2E;
      mbar_wait(bar0 + 8 * BAR_BIAS, 0);
      init_bias<16>(acca, bias_addr, ir0, ir1);
      named_bar_sync(1 + wg, 128);
      PROF(1);
    }
#pragma unroll
    for (int st = 0; st < 8; st++) {
      STAGE_BEGIN(st);
#pragma unroll
      for (int kk = 0; kk < 4; kk++) wgmma_ss_n128<1>(acca, a_lo + ((st * 16384 + kk * 32) >> 4), B_LO(st, kk * 2048, 8192));
      STAGE_END(st - 1);
      if (st == 0) zero_regs(accq);
    }
    PROF(2);
#pragma unroll
    for (int st = 0; st < 16; st++) {
      const int gs = 8 + st;
      STAGE_BEGIN(gs);
      const uint32_t as = a_lo + (((st >> 1) * 16384 + (st & 1) * 64) >> 4);
      wgmma_ss_n192<1>(accq, as, B_LO(gs, 0, 4096));
      wgmma_ss_n192<1>(accq, as + 2, B_LO(gs, 2048, 4096));
      STAGE_END(gs - 1);
      if (st == 0) fence_regs(acca);
      if (st < 8) mish_tile(acca + 8 * st, rs0, rs1, rl0, rl1, act_out + st * 32, tag);
      if (st == 7) PROF(3);
      if (st == 8) init_bias<12>(accb, bias_addr + 512, ir0, ir1);
    }
    PROF(4);
    const uint4* act_in = g_act + (size_t)(slab * 112 + 56 * khalf) * 32 + lane;
    const uint4* o_in = g_o + (size_t)(slab * 32) * 32 + lane;
    uint4 ab[4][4];
    auto a_ptr = [&](int rs, int kk) -> const uint4* {
      if (rs < 8) return act_in + (14 * (rs >> 1) + 4 * (rs & 1) + kk) * 32;
      if (rs < 16) return act_in + (14 * ((rs - 8) >> 1) + 8 + 3 * (rs & 1) + kk) * 32;
      return o_in + (4 * (rs - 16) + kk) * 32;
    };
    auto load_a = [&](int rs) {
      if (rs < 24) {
#pragma unroll
        for (int kk = 0; kk < 4; kk++) if (!(rs >= 8 && rs < 16 && kk == 3)) ab[rs & 3][kk] = ldg_frag(a_ptr(rs, kk));
      }
    };
    auto check_a = [&](int rs) {
      if (rs >= 8 && rs < 16) validate3(ab[rs & 3], a_ptr(rs, 0), tag);
      else validate4(ab[rs & 3], a_ptr(rs, 0), tag);
    };
    auto keep_a = [&](int rs) {
#pragma unroll
      for (int kk = 0; kk < 4; kk++) if (!(rs >= 8 && rs < 16 && kk == 3)) fence_u4(ab[rs & 3][kk]);
    };
    uint4 pq[4];
    {
      const int m = lane >> 3, rr = lane & 7;
      const uint32_t srow = sb + OFF_D + (warp * 16 + (m & 1) * 8 + rr) * 128;
      const uint32_t ka = dlo(sb + OFF_PK + wg * 8192, 16);
      const uint32_t vb = dlo(sb + OFF_V + wg * 8192, OFF_ONES - (OFF_V + wg * 8192));
      float (&acck)[36] = reinterpret_cast<float (&)[36]>(pool[64]);
#pragma unroll
      for (int st = 0; st < 8; st++) {
        const int gs = 24 + st;
        STAGE_BEGIN(gs);
#pragma unroll
        for (int kk = 0; kk < 4; kk++) wgmma_ss_n96<1>(accb, a_lo + ((st * 16384 + kk * 32) >> 4), B_LO(gs, kk * 2048, 8192));
        if (st == 3) {
          wgmma_tt_n72<0>(acck, ka, vb);
#pragma unroll
          for (int kk = 1; kk < 4; kk++) wgmma_tt_n72<1>(acck, ka + kk * 128, vb + kk * 128);
        }
        STAGE_END(gs - 1);
        if (st >= 4) RELEASE_SLOT(5 + (st - 1) - 3);
        if (st == 0) {
          fence_regs(accq);
          pq[0] = phi_tile(accq + 64, rs0, rs1, rl0, rl1); pq[1] = phi_tile(accq + 72, rs0, rs1, rl0, rl1);
          pq[2] = phi_tile(accq + 80, rs0, rs1, rl0, rl1); pq[3] = phi_tile(accq + 88, rs0, rs1, rl0, rl1);
        } else if (st == 1) {
#pragma unroll
          for (int i = 0; i < 4; i++) {
            const uint4 r = phi_tile(accq + 8 * i, rs0, rs1, rl0, rl1);
            stmatrix_x4(srow + OFF_PK + (((2 * i + (m >> 1)) ^ rr) << 4), r.x, r.y, r.z, r.w);
          }
        } else if (st == 2) {
#pragma unroll
          for (int i = 0; i < 4; i++) {
            const float* c = accq + 32 + 8 * i;
            stmatrix_x4(srow + OFF_V + (((2 * i + (m >> 1)) ^ rr) << 4),
                        pack2(c[0] * rs0, c[1] * rs0), pack2(c[2] * rs1, c[3] * rs1), pack2(c[4] * rs0, c[5] * rs0), pack2(c[6] * rs1, c[7] * rs1));
          }
          fence_async_smem();
          named_bar_sync(1 + wg, 128);
        } else if (st == 4) {
          fence_regs(acck);
          const int wq = warp & 3;
          float* hb = &g_kv[(ep1 & 1) ^ 1][(4 * j + wq) * 272];
          float* a0p = hb + g * 16 + 2 * t;
#pragma unroll
          for (int w = 0; w < 4; w++) {
            if (wq == w) {
              red_add_v2(a0p, acck[8 * w], acck[8 * w + 1]); red_add_v2(a0p + 128, acck[8 * w + 2], acck[8 * w + 3]);
              red_add_v2(a0p + 8, acck[8 * w + 4], acck[8 * w + 5]); red_add_v2(a0p + 136, acck[8 * w + 6], acck[8 * w + 7]);
            }
          }
          if (t == 0) { red_add_f32(hb + 256 + g, acck[32]); red_add_f32(hb + 264 + g, acck[34]); }
#pragma unroll
          for (int i = 0; i < 4; i++) sts_v4(sb + OFF_KVB + warp * 2048 + i * 512 + lane * 16, 0u, 0u, 0u, 0u);
          WARP_ARRIVE(BAR_PUB_KV);
        } else if (st == 5) {
          load_a(0); load_a(1); load_a(2);
        }
        PROF(21 + st);
      }
    }
    PROF(5);
#pragma unroll
    for (int st = 0; st < 8; st++) {
      const int gs = 32 + st;
      check_a(st);
      STAGE_BEGIN(gs);
#pragma unroll
      for (int kk = 0; kk < 4; kk++) {
        if (st == 0 && kk == 0) wgmma_rs_n128<0>(accy, ab[st & 3][kk], B_LO(gs, kk * 2048, 8192));
        else wgmma_rs_n128<1>(accy, ab[st & 3][kk], B_LO(gs, kk * 2048, 8192));
      }
      if (st == 4) {
        mbar_wait(bar0 + 8 * BAR_RDY_KV, 0);
        PROF(7);
        const uint32_t kb = dlo(sb + OFF_KVB, 8192);
        wgmma_rs_n96<0>(accb, pq[0], kb);
#pragma unroll
        for (int kk = 1; kk < 4; kk++) wgmma_rs_n96<1>(accb, pq[kk], kb + kk * 128);
      }
      STAGE_END(gs - 1);
      if (st == 0) { RELEASE_SLOT(9); fence_regs(accb); }
      else keep_a(st - 1);
      if (st == 5) {
        fence_regs(accb);
#pragma unroll
        for (int kk = 0; kk < 4; kk++) fence_u4(pq[kk]);
        uint4* o_out = g_o + (size_t)(slab * 32 + 4 * j) * 32 + lane;
#pragma unroll
        for (int hh = 0; hh < 4; hh++) {
          const float i0 = __fdividef(1.f, accb[32 + 4 * hh] + 1e-6f), i1 = __fdividef(1.f, accb[34 + 4 * hh] + 1e-6f);
          const float* n = accb + 8 * hh;
          stg_frag(o_out + hh * 32, pack2(n[0] * i0, n[1] * i0), pack2(n[2] * i1, n[3] * i1), pack2(n[4] * i0, n[5] * i0), pack2(n[6] * i1, n[7] * i1), tag);
        }
      }
      load_a(st + 3);
      if (st < 2) {
#pragma unroll
        for (int i = 3 * st; i < 3 * st + 3; i++)
          mish_tile(accb + 8 * i, rs0, rs1, rl0, rl1, act_out + (8 + i) * 32, tag);
      }
      PROF(13 + st);
    }
    PROF(6);
#pragma unroll
    for (int st = 0; st < 8; st++) {
      const int gs = 40 + st, rs = 8 + st;
      check_a(rs);
      STAGE_BEGIN(gs);
#pragma unroll
      for (int kk = 0; kk < 3; kk++) wgmma_rs_n128<1>(accy, ab[rs & 3][kk], B_LO(gs, kk * 2048, 6144));
      STAGE_END(gs - 1);
      keep_a(rs - 1);
      load_a(rs + 3);
    }
    PROF(8);
#pragma unroll
    for (int st = 0; st < 8; st++) {
      const int gs = 48 + st, rs = 16 + st;
      check_a(rs);
      STAGE_BEGIN(gs);
#pragma unroll
      for (int kk = 0; kk < 4; kk++) {
        if (st == 0 && kk == 0) wgmma_rs_n64<0>(accs, ab[rs & 3][kk], B_LO(gs, kk * 2048, 8192));
        else wgmma_rs_n64<1>(accs, ab[rs & 3][kk], B_LO(gs, kk * 2048, 8192));
      }
      STAGE_END(gs - 1);
      keep_a(rs - 1);
      load_a(rs + 3);
      if (st == 0) {
        fence_regs(accy);
        float4* yp = g_yp + (size_t)((bid * 8 + warp) * 8) * 32 + lane;
#pragma unroll
        for (int q = 0; q < 8; q++) {
          const uint32_t v0 = (__float_as_uint(accy[32 + 4 * q]) & ~1u) | tag, v1 = (__float_as_uint(accy[33 + 4 * q]) & ~1u) | tag;
          const uint32_t v2 = (__float_as_uint(accy[34 + 4 * q]) & ~1u) | tag, v3 = (__float_as_uint(accy[35 + 4 * q]) & ~1u) | tag;
          asm volatile("st.relaxed.gpu.global.v4.u32 [%0], {%1,%2,%3,%4};" ::"l"(yp + q * 32), "r"(v0), "r"(v1), "r"(v2), "r"(v3) : "memory");
        }
      }
    }
    PROF(9);
    {
      const float4* yp = g_yp + (size_t)(((bid ^ 8) * 8 + warp) * 8) * 32 + lane;
      uint4 pv[8];
      uint32_t it = 0;
      wg_wait<0>();
      keep_a(23);
      fence_regs(accs);
      while (true) {
        uint32_t bad = 0;
#pragma unroll
        for (int q = 0; q < 8; q++)
          asm volatile("ld.relaxed.gpu.global.v4.u32 {%0,%1,%2,%3}, [%4];" : "=r"(pv[q].x), "=r"(pv[q].y), "=r"(pv[q].z), "=r"(pv[q].w) : "l"(yp + q * 32) : "memory");
#pragma unroll
        for (int q = 0; q < 8; q++) bad |= (pv[q].x ^ tag) | (pv[q].y ^ tag) | (pv[q].z ^ tag) | (pv[q].w ^ tag);
        if (!__any_sync(0xffffffffu, bad & 1u)) break;
        if (++it > (1u << 20)) asm volatile("trap;");
      }
      PROF(10);
      mbar_wait(bar0 + 8 * BAR_XT, 0);
      const uint32_t xa = sb + OFF_XT + lr0 * 128 + 4 * t;
#pragma unroll
      for (int q = 0; q < 8; q++) {
        const uint32_t a0 = xa + ((q ^ g) << 4), a1 = a0 + 1024;
        const uint32_t x0 = lds_u32(a0), x1 = lds_u32(a1);
        const float y0 = accy[4 * q] + __uint_as_float(pv[q].x), y1 = accy[4 * q + 1] + __uint_as_float(pv[q].y);
        const float y2 = accy[4 * q + 2] + __uint_as_float(pv[q].z), y3 = accy[4 * q + 3] + __uint_as_float(pv[q].w);
        const float o0 = fmaf(accs[4 * q], silu_f(y0), bf_lo(x0)), o1 = fmaf(accs[4 * q + 1], silu_f(y1), bf_hi(x0));
        const float o2 = fmaf(accs[4 * q + 2], silu_f(y2), bf_lo(x1)), o3 = fmaf(accs[4 * q + 3], silu_f(y3), bf_hi(x1));
        sts_u32(a0, pack2(o0, o1));
        sts_u32(a1, pack2(o2, o3));
      }
      fence_async_smem();
      __syncwarp();
      if (lane == 0) {
        asm volatile("cp.async.bulk.tensor.2d.global.shared::cta.bulk_group [%0, {%2, %3}], [%1];"
                     ::"l"(&tm_out), "r"(sb + OFF_XT + warp * 2048), "r"(128 * nt + 64 * khalf), "r"(rb * 128 + warp * 16) : "memory");
        asm volatile("cp.async.bulk.commit_group;" ::: "memory");
        asm volatile("cp.async.bulk.wait_group.read 0;" ::: "memory");
      }
    }
    PROF(11);
    if (tid == 0) red_inc(&g_done);
    __syncwarp();
    cluster_arrive(); cluster_wait();
  }
}

typedef CUresult (*EncodeFn)(CUtensorMap*, CUtensorMapDataType, cuuint32_t, void*, const cuuint64_t*, const cuuint64_t*,
                             const cuuint32_t*, const cuuint32_t*, CUtensorMapInterleave, CUtensorMapSwizzle,
                             CUtensorMapL2promotion, CUtensorMapFloatOOBfill);

void make_map(EncodeFn enc, CUtensorMap* tm, const void* ptr, int rows, int cols, int box_rows) {
  cuuint64_t gd[2] = {(cuuint64_t)cols, (cuuint64_t)rows};
  cuuint64_t gs[1] = {(cuuint64_t)cols * 2};
  cuuint32_t bd[2] = {64, (cuuint32_t)box_rows};
  cuuint32_t es[2] = {1, 1};
  enc(tm, CU_TENSOR_MAP_DATA_TYPE_BFLOAT16, 2, const_cast<void*>(ptr), gd, gs, bd, es, CU_TENSOR_MAP_INTERLEAVE_NONE,
      CU_TENSOR_MAP_SWIZZLE_128B, CU_TENSOR_MAP_L2_PROMOTION_L2_128B, CU_TENSOR_MAP_FLOAT_OOB_FILL_NONE);
}

}

extern "C" void kernel_launch(void* const* d_in, const int* in_sizes, int n_in, void* d_out, int out_size) {
  const __nv_bfloat16* x = (const __nv_bfloat16*)d_in[0];
  const void* wqkv = d_in[1];
  const void* wo = d_in[2];
  const void* w1 = d_in[4];
  const __nv_bfloat16* b1 = (const __nv_bfloat16*)d_in[5];
  const void* w2 = d_in[6];
  static EncodeFn enc = nullptr;
  if (!enc) {
    cudaDriverEntryPointQueryResult qr;
    void* fn = nullptr;
    cudaGetDriverEntryPoint("cuTensorMapEncodeTiled", &fn, cudaEnableDefault, &qr);
    enc = (EncodeFn)fn;
    cudaFuncSetAttribute(fused_kernel, cudaFuncAttributeMaxDynamicSharedMemorySize, SMEM_ALLOC);
  }
  CUtensorMap tx, tq, t1, t2a, t2b, to, tout;
  make_map(enc, &tx, x, 2048, DM, 128);
  make_map(enc, &tq, wqkv, DM, 3 * DM, 16);
  make_map(enc, &t1, w1, DM, FF, 64);
  make_map(enc, &t2a, w2, FF, DM, 64);
  make_map(enc, &t2b, w2, FF, DM, 48);
  make_map(enc, &to, wo, DM, DM, 32);
  make_map(enc, &tout, d_out, 2048, DM, 16);
  fused_kernel<<<NCTA, 384, SMEM_ALLOC>>>(tx, tq, t1, t2a, t2b, to, tout, (const uint8_t*)wqkv, (const uint8_t*)w1,
                                          (const uint8_t*)w2, (const uint8_t*)wo, b1);
}
```

```cpp
#include <cuda_runtime.h>
#include <cuda_bf16.h>
#include <cuda.h>
#include <stdint.h>

namespace {

constexpr int DM = 512, FF = 1792;
constexpr int NCTA = 128;
constexpr int NRING = 5;
constexpr int NSLOT = 10;
constexpr int SLOT_BYTES = 16384;
constexpr int OFF_D = 0;
constexpr int OFF_PK = 0, OFF_V = 16384;
constexpr int OFF_KVB = 0;
constexpr int OFF_XT = 16384;
constexpr int OFF_RING = 131072;
constexpr int OFF_MISC = OFF_RING + NRING * SLOT_BYTES;
constexpr int OFF_ONES = OFF_MISC;
constexpr int OFF_BAR = OFF_MISC + 8192;
constexpr int OFF_B1 = OFF_MISC + 8704;
constexpr int SMEM_ALLOC = OFF_MISC + 9728;

enum { BAR_FULL = 0, BAR_EMPTY = NSLOT, BAR_X = 2 * NSLOT, BAR_BIAS = BAR_X + 4, BAR_XT,
       BAR_PUB_KV, BAR_RDY_KV, BAR_COUNT };
static_assert(BAR_COUNT <= 40, "too many barriers");

constexpr int NSTAGES = 56;
constexpr int O_STAGE = 7;
__host__ __device__ constexpr int slot_of(int gs) {
  if (gs < 32) return gs % 5;
  const int p = (gs - 32) % 10;
  return p < 5 ? 5 + p : (p - 3) % 5;
}
__host__ __device__ constexpr int use_of(int gs) {
  if (gs < 32) return gs / 5;
  const int sl = slot_of(gs);
  return (gs - 32) / 10 + (sl < 5 ? (sl < 2 ? 7 : 6) : 0);
}
__host__ __device__ constexpr int slot_off(int sl) { return sl < 5 ? OFF_RING + sl * SLOT_BYTES : OFF_D + (sl - 2) * SLOT_BYTES; }

__device__ uint4 g_act[128 * 112 * 32];
__device__ uint4 g_o[128 * 32 * 32];
__device__ float4 g_yp[NCTA * 8 * 8 * 32];
__device__ float g_kv[2][32 * 272];
__device__ unsigned g_cntKV[8 * 8];
__device__ unsigned g_done;

#define PROF(i)

__device__ __forceinline__ uint32_t smem_u32(const void* p) { return (uint32_t)__cvta_generic_to_shared(p); }
__device__ __forceinline__ void mbar_init(uint32_t bar, uint32_t cnt) { asm volatile("mbarrier.init.shared::cta.b64 [%0], %1;" ::"r"(bar), "r"(cnt)); }
__device__ __forceinline__ void mbar_expect_tx(uint32_t bar, uint32_t bytes) { asm volatile("mbarrier.arrive.expect_tx.shared::cta.b64 _, [%0], %1;" ::"r"(bar), "r"(bytes) : "memory"); }
__device__ __forceinline__ void mbar_arrive(uint32_t bar) { asm volatile("mbarrier.arrive.shared::cta.b64 _, [%0];" ::"r"(bar) : "memory"); }
__device__ __forceinline__ void mbar_wait(uint32_t bar, uint32_t parity) {
  asm volatile("{\n.reg .pred P1;\n.reg .u32 cnt;\n"
               "mbarrier.try_wait.parity.shared::cta.b64 P1, [%0], %1;\n@P1 bra DONE;\n"
               "mov.u32 cnt, 0;\n"
               "LAB_WAIT:\n"
               "mbarrier.try_wait.parity.shared::cta.b64 P1, [%0], %1;\n@P1 bra DONE;\n"
               "add.u32 cnt, cnt, 1;\nsetp.lt.u32 P1, cnt, 16777216;\n@P1 bra LAB_WAIT;\ntrap;\n"
               "DONE:\n}" ::"r"(bar), "r"(parity) : "memory");
}
__device__ __forceinline__ void tma2d(uint32_t dst, const CUtensorMap* tm, int c0, int c1, uint32_t bar) {
  asm volatile("cp.async.bulk.tensor.2d.shared::cluster.global.mbarrier::complete_tx::bytes [%0], [%1, {%3, %4}], [%2];" ::"r"(dst), "l"(tm), "r"(bar), "r"(c0), "r"(c1) : "memory");
}
__device__ __forceinline__ void wg_fence() { asm volatile("wgmma.fence.sync.aligned;" ::: "memory"); }
__device__ __forceinline__ void wg_commit() { asm volatile("wgmma.commit_group.sync.aligned;" ::: "memory"); }
template <int N> __device__ __forceinline__ void wg_wait() { asm volatile("wgmma.wait_group.sync.aligned %0;" ::"n"(N) : "memory"); }
template <int N> __device__ __forceinline__ void zero_regs(float (&d)[N]) {
#pragma unroll
  for (int i = 0; i < N; i++) d[i] = 0.f;
}
template <int N> __device__ __forceinline__ void fence_regs(float (&d)[N]) {
#pragma unroll
  for (int i = 0; i < N; i++) asm volatile("" : "+f"(d[i])::"memory");
}
__device__ __forceinline__ void fence_u4(uint4& v) { asm volatile("" : "+r"(v.x), "+r"(v.y), "+r"(v.z), "+r"(v.w)::"memory"); }
__device__ __forceinline__ void named_bar_sync(int id, int n) { asm volatile("bar.sync %0, %1;" ::"r"(id), "r"(n) : "memory"); }
__device__ __forceinline__ void fence_gpu() { asm volatile("fence.acq_rel.gpu;" ::: "memory"); }
__device__ __forceinline__ void fence_async_smem() { asm volatile("fence.proxy.async.shared::cta;" ::: "memory"); }
__device__ __forceinline__ constexpr uint32_t dlo(uint32_t addr, uint32_t lbo_bytes) { return ((addr & 0x3FFFFu) >> 4) | ((lbo_bytes >> 4) << 16); }
__device__ __forceinline__ void mma16816(float (&c)[4], uint32_t a0, uint32_t a1, uint32_t a2, uint32_t a3, uint32_t b0, uint32_t b1) {
  asm volatile("mma.sync.aligned.m16n8k16.row.col.f32.bf16.bf16.f32 {%0,%1,%2,%3}, {%4,%5,%6,%7}, {%8,%9}, {%0,%1,%2,%3};"
               : "+f"(c[0]), "+f"(c[1]), "+f"(c[2]), "+f"(c[3]) : "r"(a0), "r"(a1), "r"(a2), "r"(a3), "r"(b0), "r"(b1));
}
__device__ __forceinline__ void stmatrix_x4(uint32_t addr, uint32_t a, uint32_t b, uint32_t c, uint32_t d) {
  asm volatile("stmatrix.sync.aligned.m8n8.x4.shared.b16 [%0], {%1,%2,%3,%4};" ::"r"(addr), "r"(a), "r"(b), "r"(c), "r"(d) : "memory");
}
__device__ __forceinline__ uint32_t pack2(float lo, float hi) { uint32_t r; asm("cvt.rn.bf16x2.f32 %0, %1, %2;" : "=r"(r) : "f"(hi), "f"(lo)); return r; }
__device__ __forceinline__ float ex2(float x) { float r; asm("ex2.approx.ftz.f32 %0, %1;" : "=f"(r) : "f"(x)); return r; }
__device__ __forceinline__ float rcp(float x) { float r; asm("rcp.approx.ftz.f32 %0, %1;" : "=f"(r) : "f"(x)); return r; }
__device__ __forceinline__ float bf_lo(uint32_t v) { return __uint_as_float(v << 16); }
__device__ __forceinline__ float bf_hi(uint32_t v) { return __uint_as_float(v & 0xffff0000u); }
__device__ __forceinline__ uint32_t hsub2_bf16(uint32_t a, uint32_t b) {
  __nv_bfloat162 x = *reinterpret_cast<__nv_bfloat162*>(&a), y = *reinterpret_cast<__nv_bfloat162*>(&b);
  __nv_bfloat162 r = __hsub2(x, y);
  return *reinterpret_cast<uint32_t*>(&r);
}
__device__ __forceinline__ uint4 ldg_cg(const void* p) {
  uint4 v; asm volatile("ld.global.cg.v4.u32 {%0,%1,%2,%3}, [%4];" : "=r"(v.x), "=r"(v.y), "=r"(v.z), "=r"(v.w) : "l"(p) : "memory"); return v;
}
__device__ __forceinline__ void stg_frag(void* p, uint32_t a, uint32_t b, uint32_t c, uint32_t d, uint32_t tag) {
  asm volatile("st.relaxed.gpu.global.v4.u32 [%0], {%1,%2,%3,%4};" ::"l"(p), "r"((a & ~1u) | tag), "r"(b), "r"(c), "r"(d) : "memory");
}
__device__ __forceinline__ uint4 ldg_frag(const void* p) {
  uint4 v; asm volatile("ld.relaxed.gpu.global.v4.u32 {%0,%1,%2,%3}, [%4];" : "=r"(v.x), "=r"(v.y), "=r"(v.z), "=r"(v.w) : "l"(p) : "memory"); return v;
}
__device__ __forceinline__ void validate4(uint4 (&v)[4], const void* p, uint32_t tag4) {
  asm volatile("{\n.reg .pred P1;\n.reg .u32 cnt, tb, it;\n"
               "mov.u32 it, 0;\n"
               "LAB_CHECK:\n"
               "lop3.b32 tb, %0, %4, %8, 0x80;\nand.b32 tb, tb, %12;\n"
               "lop3.b32 cnt, %0, %4, %8, 0xFE;\nor.b32 cnt, cnt, %12;\n"
               "xor.b32 tb, tb, %17;\nxor.b32 cnt, cnt, %17;\nor.b32 tb, tb, cnt;\nand.b32 tb, tb, 1;\n"
               "setp.eq.u32 P1, tb, 0;\n@P1 bra DONE;\n"
               "ld.relaxed.gpu.global.v4.u32 {%0,%1,%2,%3}, [%16];\n"
               "ld.relaxed.gpu.global.v4.u32 {%4,%5,%6,%7}, [%16+512];\n"
               "ld.relaxed.gpu.global.v4.u32 {%8,%9,%10,%11}, [%16+1024];\n"
               "ld.relaxed.gpu.global.v4.u32 {%12,%13,%14,%15}, [%16+1536];\n"
               "add.u32 it, it, 1;\nsetp.lt.u32 P1, it, 4194304;\n@P1 bra LAB_CHECK;\ntrap;\n"
               "DONE:\n}"
               : "+r"(v[0].x), "+r"(v[0].y), "+r"(v[0].z), "+r"(v[0].w), "+r"(v[1].x), "+r"(v[1].y), "+r"(v[1].z), "+r"(v[1].w),
                 "+r"(v[2].x), "+r"(v[2].y), "+r"(v[2].z), "+r"(v[2].w), "+r"(v[3].x), "+r"(v[3].y), "+r"(v[3].z), "+r"(v[3].w)
               : "l"(p), "r"(tag4) : "memory");
}
__device__ __forceinline__ void validate3(uint4 (&v)[4], const void* p, uint32_t tag4) {
  asm volatile("{\n.reg .pred P1;\n.reg .u32 cnt, tb, it;\n"
               "mov.u32 it, 0;\n"
               "LAB_CHECK:\n"
               "lop3.b32 tb, %0, %4, %8, 0x80;\n"
               "lop3.b32 cnt, %0, %4, %8, 0xFE;\n"
               "xor.b32 tb, tb, %13;\nxor.b32 cnt, cnt, %13;\nor.b32 tb, tb, cnt;\nand.b32 tb, tb, 1;\n"
               "setp.eq.u32 P1, tb, 0;\n@P1 bra DONE;\n"
               "ld.relaxed.gpu.global.v4.u32 {%0,%1,%2,%3}, [%12];\n"
               "ld.relaxed.gpu.global.v4.u32 {%4,%5,%6,%7}, [%12+512];\n"
               "ld.relaxed.gpu.global.v4.u32 {%8,%9,%10,%11}, [%12+1024];\n"
               "add.u32 it, it, 1;\nsetp.lt.u32 P1, it, 4194304;\n@P1 bra LAB_CHECK;\ntrap;\n"
               "DONE:\n}"
               : "+r"(v[0].x), "+r"(v[0].y), "+r"(v[0].z), "+r"(v[0].w), "+r"(v[1].x), "+r"(v[1].y), "+r"(v[1].z), "+r"(v[1].w),
                 "+r"(v[2].x), "+r"(v[2].y), "+r"(v[2].z), "+r"(v[2].w)
               : "l"(p), "r"(tag4) : "memory");
}
__device__ __forceinline__ void sts_v4(uint32_t addr, uint32_t a, uint32_t b, uint32_t c, uint32_t d) {
  asm volatile("st.shared.v4.u32 [%0], {%1,%2,%3,%4};" ::"r"(addr), "r"(a), "r"(b), "r"(c), "r"(d) : "memory");
}
__device__ __forceinline__ void sts_f32(uint32_t addr, float v) { asm volatile("st.shared.f32 [%0], %1;" ::"r"(addr), "f"(v) : "memory"); }
__device__ __forceinline__ uint4 lds_v4(uint32_t addr) { uint4 v; asm volatile("ld.shared.v4.u32 {%0,%1,%2,%3}, [%4];" : "=r"(v.x), "=r"(v.y), "=r"(v.z), "=r"(v.w) : "r"(addr) : "memory"); return v; }
__device__ __forceinline__ uint32_t lds_u32(uint32_t addr) { uint32_t v; asm volatile("ld.shared.u32 %0, [%1];" : "=r"(v) : "r"(addr) : "memory"); return v; }
__device__ __forceinline__ void sts_u32(uint32_t addr, uint32_t v) { asm volatile("st.shared.u32 [%0], %1;" ::"r"(addr), "r"(v) : "memory"); }
__device__ __forceinline__ float2 lds_f32x2(uint32_t addr) { float2 v; asm volatile("ld.shared.v2.f32 {%0,%1}, [%2];" : "=f"(v.x), "=f"(v.y) : "r"(addr) : "memory"); return v; }
__device__ __forceinline__ void red_add_v2(float* p, float a, float b) { asm volatile("red.relaxed.gpu.global.add.v2.f32 [%0], {%1,%2};" ::"l"(p), "f"(a), "f"(b) : "memory"); }
__device__ __forceinline__ void red_add_f32(float* p, float a) { asm volatile("red.relaxed.gpu.global.add.f32 [%0], %1;" ::"l"(p), "f"(a) : "memory"); }
__device__ __forceinline__ void red_inc(unsigned* cnt) { asm volatile("red.relaxed.gpu.global.add.u32 [%0], 1;" ::"l"(cnt) : "memory"); }
__device__ __forceinline__ void poll_ge(const unsigned* cnt, unsigned target) {
  asm volatile("{\n.reg .pred P1;\n.reg .u32 cnt, v;\n.reg .s32 d;\n"
               "mov.u32 cnt, 0;\n"
               "LAB_POLL:\n"
               "ld.relaxed.gpu.global.u32 v, [%0];\nsub.s32 d, v, %1;\nsetp.ge.s32 P1, d, 0;\n@P1 bra DONE;\n"
               "add.u32 cnt, cnt, 1;\nsetp.lt.u32 P1, cnt, 4194304;\n@P1 bra LAB_POLL;\ntrap;\n"
               "DONE:\nld.acquire.gpu.global.u32 v, [%0];\n}" ::"l"(cnt), "r"(target) : "memory");
}

template <int SCALE_D> __device__ __forceinline__ void wgmma_ss_n192(float (&d)[96], uint32_t da, uint32_t db) {
  asm volatile("{\n.reg .b64 da, db;\nmov.b64 da, {%96, %98};\nmov.b64 db, {%97, %98};\n"
    "wgmma.mma_async.sync.aligned.m64n192k16.f32.bf16.bf16 {%0, %1, %2, %3, %4, %5, %6, %7, %8, %9, %10, %11, %12, %13, %14, %15, %16, %17, %18, %19, %20, %21, %22, %23, %24, %25, %26, %27, %28, %29, %30, %31, %32, %33, %34, %35, %36, %37, %38, %39, %40, %41, %42, %43, %44, %45, %46, %47, %48, %49, %50, %51, %52, %53, %54, %55, %56, %57, %58, %59, %60, %61, %62, %63, %64, %65, %66, %67, %68, %69, %70, %71, %72, %73, %74, %75, %76, %77, %78, %79, %80, %81, %82, %83, %84, %85, %86, %87, %88, %89, %90, %91, %92, %93, %94, %95}, da, db, %99, 1, 1, 0, 1;\n}\n"
    : "+f"(d[0]), "+f"(d[1]), "+f"(d[2]), "+f"(d[3]), "+f"(d[4]), "+f"(d[5]), "+f"(d[6]), "+f"(d[7]), "+f"(d[8]), "+f"(d[9]), "+f"(d[10]), "+f"(d[11]), "+f"(d[12]), "+f"(d[13]), "+f"(d[14]), "+f"(d[15]), "+f"(d[16]), "+f"(d[17]), "+f"(d[18]), "+f"(d[19]), "+f"(d[20]), "+f"(d[21]), "+f"(d[22]), "+f"(d[23]), "+f"(d[24]), "+f"(d[25]), "+f"(d[26]), "+f"(d[27]), "+f"(d[28]), "+f"(d[29]), "+f"(d[30]), "+f"(d[31]), "+f"(d[32]), "+f"(d[33]), "+f"(d[34]), "+f"(d[35]), "+f"(d[36]), "+f"(d[37]), "+f"(d[38]), "+f"(d[39]), "+f"(d[40]), "+f"(d[41]), "+f"(d[42]), "+f"(d[43]), "+f"(d[44]), "+f"(d[45]), "+f"(d[46]), "+f"(d[47]), "+f"(d[48]), "+f"(d[49]), "+f"(d[50]), "+f"(d[51]), "+f"(d[52]), "+f"(d[53]), "+f"(d[54]), "+f"(d[55]), "+f"(d[56]), "+f"(d[57]), "+f"(d[58]), "+f"(d[59]), "+f"(d[60]), "+f"(d[61]), "+f"(d[62]), "+f"(d[63]), "+f"(d[64]), "+f"(d[65]), "+f"(d[66]), "+f"(d[67]), "+f"(d[68]), "+f"(d[69]), "+f"(d[70]), "+f"(d[71]), "+f"(d[72]), "+f"(d[73]), "+f"(d[74]), "+f"(d[75]), "+f"(d[76]), "+f"(d[77]), "+f"(d[78]), "+f"(d[79]), "+f"(d[80]), "+f"(d[81]), "+f"(d[82]), "+f"(d[83]), "+f"(d[84]), "+f"(d[85]), "+f"(d[86]), "+f"(d[87]), "+f"(d[88]), "+f"(d[89]), "+f"(d[90]), "+f"(d[91]), "+f"(d[92]), "+f"(d[93]), "+f"(d[94]), "+f"(d[95])
    : "r"(da), "r"(db), "r"(0x40000040u), "n"(SCALE_D));
}
template <int SCALE_D> __device__ __forceinline__ void wgmma_ss_n128(float (&d)[64], uint32_t da, uint32_t db) {
  asm volatile("{\n.reg .b64 da, db;\nmov.b64 da, {%64, %66};\nmov.b64 db, {%65, %66};\n"
    "wgmma.mma_async.sync.aligned.m64n128k16.f32.bf16.bf16 {%0, %1, %2, %3, %4, %5, %6, %7, %8, %9, %10, %11, %12, %13, %14, %15, %16, %17, %18, %19, %20, %21, %22, %23, %24, %25, %26, %27, %28, %29, %30, %31, %32, %33, %34, %35, %36, %37, %38, %39, %40, %41, %42, %43, %44, %45, %46, %47, %48, %49, %50, %51, %52, %53, %54, %55, %56, %57, %58, %59, %60, %61, %62, %63}, da, db, %67, 1, 1, 0, 1;\n}\n"
    : "+f"(d[0]), "+f"(d[1]), "+f"(d[2]), "+f"(d[3]), "+f"(d[4]), "+f"(d[5]), "+f"(d[6]), "+f"(d[7]), "+f"(d[8]), "+f"(d[9]), "+f"(d[10]), "+f"(d[11]), "+f"(d[12]), "+f"(d[13]), "+f"(d[14]), "+f"(d[15]), "+f"(d[16]), "+f"(d[17]), "+f"(d[18]), "+f"(d[19]), "+f"(d[20]), "+f"(d[21]), "+f"(d[22]), "+f"(d[23]), "+f"(d[24]), "+f"(d[25]), "+f"(d[26]), "+f"(d[27]), "+f"(d[28]), "+f"(d[29]), "+f"(d[30]), "+f"(d[31]), "+f"(d[32]), "+f"(d[33]), "+f"(d[34]), "+f"(d[35]), "+f"(d[36]), "+f"(d[37]), "+f"(d[38]), "+f"(d[39]), "+f"(d[40]), "+f"(d[41]), "+f"(d[42]), "+f"(d[43]), "+f"(d[44]), "+f"(d[45]), "+f"(d[46]), "+f"(d[47]), "+f"(d[48]), "+f"(d[49]), "+f"(d[50]), "+f"(d[51]), "+f"(d[52]), "+f"(d[53]), "+f"(d[54]), "+f"(d[55]), "+f"(d[56]), "+f"(d[57]), "+f"(d[58]), "+f"(d[59]), "+f"(d[60]), "+f"(d[61]), "+f"(d[62]), "+f"(d[63])
    : "r"(da), "r"(db), "r"(0x40000040u), "n"(SCALE_D));
}
template <int SCALE_D> __device__ __forceinline__ void wgmma_ss_n96(float (&d)[48], uint32_t da, uint32_t db) {
  asm volatile("{\n.reg .b64 da, db;\nmov.b64 da, {%48, %50};\nmov.b64 db, {%49, %50};\n"
    "wgmma.mma_async.sync.aligned.m64n96k16.f32.bf16.bf16 {%0, %1, %2, %3, %4, %5, %6, %7, %8, %9, %10, %11, %12, %13, %14, %15, %16, %17, %18, %19, %20, %21, %22, %23, %24, %25, %26, %27, %28, %29, %30, %31, %32, %33, %34, %35, %36, %37, %38, %39, %40, %41, %42, %43, %44, %45, %46, %47}, da, db, %51, 1, 1, 0, 1;\n}\n"
    : "+f"(d[0]), "+f"(d[1]), "+f"(d[2]), "+f"(d[3]), "+f"(d[4]), "+f"(d[5]), "+f"(d[6]), "+f"(d[7]), "+f"(d[8]), "+f"(d[9]), "+f"(d[10]), "+f"(d[11]), "+f"(d[12]), "+f"(d[13]), "+f"(d[14]), "+f"(d[15]), "+f"(d[16]), "+f"(d[17]), "+f"(d[18]), "+f"(d[19]), "+f"(d[20]), "+f"(d[21]), "+f"(d[22]), "+f"(d[23]), "+f"(d[24]), "+f"(d[25]), "+f"(d[26]), "+f"(d[27]), "+f"(d[28]), "+f"(d[29]), "+f"(d[30]), "+f"(d[31]), "+f"(d[32]), "+f"(d[33]), "+f"(d[34]), "+f"(d[35]), "+f"(d[36]), "+f"(d[37]), "+f"(d[38]), "+f"(d[39]), "+f"(d[40]), "+f"(d[41]), "+f"(d[42]), "+f"(d[43]), "+f"(d[44]), "+f"(d[45]), "+f"(d[46]), "+f"(d[47])
    : "r"(da), "r"(db), "r"(0x40000040u), "n"(SCALE_D));
}
template <int SCALE_D> __device__ __forceinline__ void wgmma_tt_n72(float (&d)[36], uint32_t da, uint32_t db) {
  asm volatile("{\n.reg .b64 da, db;\nmov.b64 da, {%36, %38};\nmov.b64 db, {%37, %38};\n"
    "wgmma.mma_async.sync.aligned.m64n72k16.f32.bf16.bf16 {%0, %1, %2, %3, %4, %5, %6, %7, %8, %9, %10, %11, %12, %13, %14, %15, %16, %17, %18, %19, %20, %21, %22, %23, %24, %25, %26, %27, %28, %29, %30, %31, %32, %33, %34, %35}, da, db, %39, 1, 1, 1, 1;\n}\n"
    : "+f"(d[0]), "+f"(d[1]), "+f"(d[2]), "+f"(d[3]), "+f"(d[4]), "+f"(d[5]), "+f"(d[6]), "+f"(d[7]), "+f"(d[8]), "+f"(d[9]), "+f"(d[10]), "+f"(d[11]), "+f"(d[12]), "+f"(d[13]), "+f"(d[14]), "+f"(d[15]), "+f"(d[16]), "+f"(d[17]), "+f"(d[18]), "+f"(d[19]), "+f"(d[20]), "+f"(d[21]), "+f"(d[22]), "+f"(d[23]), "+f"(d[24]), "+f"(d[25]), "+f"(d[26]), "+f"(d[27]), "+f"(d[28]), "+f"(d[29]), "+f"(d[30]), "+f"(d[31]), "+f"(d[32]), "+f"(d[33]), "+f"(d[34]), "+f"(d[35])
    : "r"(da), "r"(db), "r"(0x40000040u), "n"(SCALE_D));
}
template <int SCALE_D> __device__ __forceinline__ void wgmma_rs_n128(float (&d)[64], const uint4& a, uint32_t db) {
  asm volatile("{\n.reg .b64 db;\nmov.b64 db, {%68, %69};\n"
    "wgmma.mma_async.sync.aligned.m64n128k16.f32.bf16.bf16 {%0, %1, %2, %3, %4, %5, %6, %7, %8, %9, %10, %11, %12, %13, %14, %15, %16, %17, %18, %19, %20, %21, %22, %23, %24, %25, %26, %27, %28, %29, %30, %31, %32, %33, %34, %35, %36, %37, %38, %39, %40, %41, %42, %43, %44, %45, %46, %47, %48, %49, %50, %51, %52, %53, %54, %55, %56, %57, %58, %59, %60, %61, %62, %63}, {%64, %65, %66, %67}, db, %70, 1, 1, 1;\n}\n"
    : "+f"(d[0]), "+f"(d[1]), "+f"(d[2]), "+f"(d[3]), "+f"(d[4]), "+f"(d[5]), "+f"(d[6]), "+f"(d[7]), "+f"(d[8]), "+f"(d[9]), "+f"(d[10]), "+f"(d[11]), "+f"(d[12]), "+f"(d[13]), "+f"(d[14]), "+f"(d[15]), "+f"(d[16]), "+f"(d[17]), "+f"(d[18]), "+f"(d[19]), "+f"(d[20]), "+f"(d[21]), "+f"(d[22]), "+f"(d[23]), "+f"(d[24]), "+f"(d[25]), "+f"(d[26]), "+f"(d[27]), "+f"(d[28]), "+f"(d[29]), "+f"(d[30]), "+f"(d[31]), "+f"(d[32]), "+f"(d[33]), "+f"(d[34]), "+f"(d[35]), "+f"(d[36]), "+f"(d[37]), "+f"(d[38]), "+f"(d[39]), "+f"(d[40]), "+f"(d[41]), "+f"(d[42]), "+f"(d[43]), "+f"(d[44]), "+f"(d[45]), "+f"(d[46]), "+f"(d[47]), "+f"(d[48]), "+f"(d[49]), "+f"(d[50]), "+f"(d[51]), "+f"(d[52]), "+f"(d[53]), "+f"(d[54]), "+f"(d[55]), "+f"(d[56]), "+f"(d[57]), "+f"(d[58]), "+f"(d[59]), "+f"(d[60]), "+f"(d[61]), "+f"(d[62]), "+f"(d[63])
    : "r"(a.x), "r"(a.y), "r"(a.z), "r"(a.w), "r"(db), "r"(0x40000040u), "n"(SCALE_D));
}
template <int SCALE_D> __device__ __forceinline__ void wgmma_rs_n96(float (&d)[48], const uint4& a, uint32_t db) {
  asm volatile("{\n.reg .b64 db;\nmov.b64 db, {%52, %53};\n"
    "wgmma.mma_async.sync.aligned.m64n96k16.f32.bf16.bf16 {%0, %1, %2, %3, %4, %5, %6, %7, %8, %9, %10, %11, %12, %13, %14, %15, %16, %17, %18, %19, %20, %21, %22, %23, %24, %25, %26, %27, %28, %29, %30, %31, %32, %33, %34, %35, %36, %37, %38, %39, %40, %41, %42, %43, %44, %45, %46, %47}, {%48, %49, %50, %51}, db, %54, 1, 1, 1;\n}\n"
    : "+f"(d[0]), "+f"(d[1]), "+f"(d[2]), "+f"(d[3]), "+f"(d[4]), "+f"(d[5]), "+f"(d[6]), "+f"(d[7]), "+f"(d[8]), "+f"(d[9]), "+f"(d[10]), "+f"(d[11]), "+f"(d[12]), "+f"(d[13]), "+f"(d[14]), "+f"(d[15]), "+f"(d[16]), "+f"(d[17]), "+f"(d[18]), "+f"(d[19]), "+f"(d[20]), "+f"(d[21]), "+f"(d[22]), "+f"(d[23]), "+f"(d[24]), "+f"(d[25]), "+f"(d[26]), "+f"(d[27]), "+f"(d[28]), "+f"(d[29]), "+f"(d[30]), "+f"(d[31]), "+f"(d[32]), "+f"(d[33]), "+f"(d[34]), "+f"(d[35]), "+f"(d[36]), "+f"(d[37]), "+f"(d[38]), "+f"(d[39]), "+f"(d[40]), "+f"(d[41]), "+f"(d[42]), "+f"(d[43]), "+f"(d[44]), "+f"(d[45]), "+f"(d[46]), "+f"(d[47])
    : "r"(a.x), "r"(a.y), "r"(a.z), "r"(a.w), "r"(db), "r"(0x40000040u), "n"(SCALE_D));
}
template <int SCALE_D> __device__ __forceinline__ void wgmma_rs_n64(float (&d)[32], const uint4& a, uint32_t db) {
  asm volatile("{\n.reg .b64 db;\nmov.b64 db, {%36, %37};\n"
    "wgmma.mma_async.sync.aligned.m64n64k16.f32.bf16.bf16 {%0, %1, %2, %3, %4, %5, %6, %7, %8, %9, %10, %11, %12, %13, %14, %15, %16, %17, %18, %19, %20, %21, %22, %23, %24, %25, %26, %27, %28, %29, %30, %31}, {%32, %33, %34, %35}, db, %38, 1, 1, 1;\n}\n"
    : "+f"(d[0]), "+f"(d[1]), "+f"(d[2]), "+f"(d[3]), "+f"(d[4]), "+f"(d[5]), "+f"(d[6]), "+f"(d[7]), "+f"(d[8]), "+f"(d[9]), "+f"(d[10]), "+f"(d[11]), "+f"(d[12]), "+f"(d[13]), "+f"(d[14]), "+f"(d[15]), "+f"(d[16]), "+f"(d[17]), "+f"(d[18]), "+f"(d[19]), "+f"(d[20]), "+f"(d[21]), "+f"(d[22]), "+f"(d[23]), "+f"(d[24]), "+f"(d[25]), "+f"(d[26]), "+f"(d[27]), "+f"(d[28]), "+f"(d[29]), "+f"(d[30]), "+f"(d[31])
    : "r"(a.x), "r"(a.y), "r"(a.z), "r"(a.w), "r"(db), "r"(0x40000040u), "n"(SCALE_D));
}

constexpr float LOG2E = 1.4426950408889634f;
__device__ __forceinline__ float silu_f(float y) { return y * rcp(1.f + ex2(-y * LOG2E)); }

__device__ __forceinline__ void mish_tile(const float* c, float rs0, float rs1, float rl0, float rl1, uint4* dst, uint32_t tag) {
  float h[8], u[8], r[8];
#pragma unroll
  for (int i = 0; i < 8; i++) {
    const bool hi = (i >> 1) & 1;
    h[i] = c[i] * (hi ? rs1 : rs0);
    u[i] = ex2(fminf(c[i] * (hi ? rl1 : rl0), 28.853900817779268f));
  }
#pragma unroll
  for (int i = 0; i < 8; i++) { const float tt = u[i] + 2.f; r[i] = rcp(fmaf(u[i], tt, 2.f)); h[i] *= u[i] * tt; }
#pragma unroll
  for (int i = 0; i < 8; i++) h[i] *= r[i];
  stg_frag(dst, pack2(h[0], h[1]), pack2(h[2], h[3]), pack2(h[4], h[5]), pack2(h[6], h[7]), tag);
}
__device__ __forceinline__ float phi_c(float c, float rs, float rl) {
  const float e = ex2(c * rl) + 1e-6f;
  const float p = fmaf(c, rs, 1.000001f);
  return c > 0.f ? p : e;
}
__device__ __forceinline__ uint4 phi_tile(const float* c, float rs0, float rs1, float rl0, float rl1) {
  uint4 r;
  r.x = pack2(phi_c(c[0], rs0, rl0), phi_c(c[1], rs0, rl0)); r.y = pack2(phi_c(c[2], rs1, rl1), phi_c(c[3], rs1, rl1));
  r.z = pack2(phi_c(c[4], rs0, rl0), phi_c(c[5], rs0, rl0)); r.w = pack2(phi_c(c[6], rs1, rl1), phi_c(c[7], rs1, rl1));
  return r;
}
template <int NB> __device__ __forceinline__ void init_bias(float* acc, uint32_t bias_addr, float ir0, float ir1) {
#pragma unroll
  for (int nb = 0; nb < NB; nb++) {
    const float2 b = lds_f32x2(bias_addr + 32 * nb);
    acc[4 * nb] = b.x * ir0; acc[4 * nb + 1] = b.y * ir0; acc[4 * nb + 2] = b.x * ir1; acc[4 * nb + 3] = b.y * ir1;
  }
}

__global__ void __launch_bounds__(384, 1)
fused_kernel(const __grid_constant__ CUtensorMap tm_x, const __grid_constant__ CUtensorMap tm_qkv,
             const __grid_constant__ CUtensorMap tm_w1, const __grid_constant__ CUtensorMap tm_w2a,
             const __grid_constant__ CUtensorMap tm_w2b, const __grid_constant__ CUtensorMap tm_wo,
             const __grid_constant__ CUtensorMap tm_out,
             const uint8_t* __restrict__ wqkv, const uint8_t* __restrict__ w1, const uint8_t* __restrict__ w2,
             const uint8_t* __restrict__ wo, const __nv_bfloat16* __restrict__ b1) {
  extern __shared__ __align__(1024) uint8_t smem_raw[];
  const uint32_t sb = smem_u32(smem_raw);
  const int tid = threadIdx.x, lane = tid & 31;
  const int warp = __shfl_sync(0xffffffffu, tid >> 5, 0);
  const int bid = blockIdx.x;
#define MAPV 0
  const int khalf = (bid >> 4) & 1, rb = (bid >> 5) * 4 + ((bid >> 2) & 3), nt = bid & 3;
  const int pbid = bid ^ 16;
  const int j = khalf + 2 * nt;
  const uint32_t bar0 = sb + OFF_BAR;
  PROF(0);

  if (warp >= 8) {
    asm volatile("setmaxnreg.dec.sync.aligned.u32 40;");
    if (warp == 8) {
      if (lane == 0) {
        if (sb & 1023u) asm volatile("trap;");
        for (int i = 0; i < NSLOT; i++) { mbar_init(bar0 + 8 * (BAR_FULL + i), 1); mbar_init(bar0 + 8 * (BAR_EMPTY + i), 8); }
        for (int i = BAR_X; i <= BAR_XT; i++) mbar_init(bar0 + 8 * i, 1);
        mbar_init(bar0 + 8 * BAR_PUB_KV, 8);
        mbar_init(bar0 + 8 * BAR_RDY_KV, 2);
        asm volatile("fence.mbarrier_init.release.cluster;" ::: "memory");
        fence_async_smem();
        for (int i = 0; i < 4; i++) {
          mbar_expect_tx(bar0 + 8 * (BAR_X + i), 32768);
          tma2d(sb + OFF_D + (2 * i) * 16384, &tm_x, 128 * i, rb * 128, bar0 + 8 * (BAR_X + i));
          tma2d(sb + OFF_D + (2 * i + 1) * 16384, &tm_x, 128 * i + 64, rb * 128, bar0 + 8 * (BAR_X + i));
        }
      }
      __syncwarp();
      named_bar_sync(0, 384);
      if (lane == 0) {
        const int c_own = 128 * nt + 64 * khalf, c_par = 128 * nt + 64 * (1 - khalf);
#pragma unroll 1
        for (int st = 0; st < NSTAGES; st++) {
          const int slot = slot_of(st), use = use_of(st);
          const uint32_t full = bar0 + 8 * (BAR_FULL + slot);
          const uint32_t dst = sb + slot_off(slot);
          mbar_wait(bar0 + 8 * (BAR_EMPTY + slot), (use & 1) ^ (slot < 5 ? 1 : 0));
          if (st < 8) {
            mbar_expect_tx(full, 16384);
            const int k0 = 64 * st, c0 = 224 * j;
            tma2d(dst, &tm_w1, c0, k0, full);
            tma2d(dst + 8192, &tm_w1, c0 + 64, k0, full);
          } else if (st < 24) {
            mbar_expect_tx(full, 12288);
            const int k0 = 32 * (st - 8);
            tma2d(dst, &tm_qkv, 512 + 64 * j, k0, full);
            tma2d(dst + 4096, &tm_qkv, 1024 + 64 * j, k0, full);
            tma2d(dst + 8192, &tm_qkv, 64 * j, k0, full);
          } else if (st < 32) {
            mbar_expect_tx(full, 16384);
            const int k0 = 64 * (st - 24), c0 = 224 * j + 128;
            tma2d(dst, &tm_w1, c0, k0, full);
            tma2d(dst + 8192, &tm_w1, c0 + 64, k0, full);
          } else if (st < 40) {
            mbar_expect_tx(full, 16384);
            const int i = st - 32;
            const int k0 = 224 * (4 * khalf + (i >> 1)) + 64 * (i & 1);
            tma2d(dst, &tm_w2a, c_own, k0, full);
            tma2d(dst + 8192, &tm_w2a, c_par, k0, full);
          } else if (st < 48) {
            if (st == 40) {
              mbar_wait(bar0 + 8 * BAR_PUB_KV, 0);
              mbar_expect_tx(bar0 + 8 * BAR_XT, 16384);
              tma2d(sb + OFF_XT, &tm_x, c_own, rb * 128, bar0 + 8 * BAR_XT);
            }
            mbar_expect_tx(full, 12288);
            const int i = st - 40;
            const int k0 = 224 * (4 * khalf + (i >> 1)) + 128 + 48 * (i & 1);
            tma2d(dst, &tm_w2b, c_own, k0, full);
            tma2d(dst + 6144, &tm_w2b, c_par, k0, full);
          } else {
            mbar_expect_tx(full, 8192);
            tma2d(dst, &tm_wo, c_own, 64 * (st - 48), full);
          }
        }
      }
    } else {
      const int aw = warp - 9;
      unsigned dn; asm volatile("ld.relaxed.gpu.global.u32 %0, [%1];" : "=r"(dn) : "l"(&g_done) : "memory");
      named_bar_sync(0, 384);
      const unsigned ep1 = dn / NCTA + 1u;
      if (aw == 0) {
        for (int i = lane; i < 224; i += 32) sts_f32(sb + OFF_B1 + 4 * i, __bfloat162float(b1[224 * j + i]));
#pragma unroll 4
        for (int i = 0; i < 16; i++) sts_v4(sb + OFF_ONES + (i * 32 + lane) * 16, 0x3F803F80u, 0x3F803F80u, 0x3F803F80u, 0x3F803F80u);
        fence_async_smem();
        __syncwarp();
        if (lane == 0) {
          mbar_arrive(bar0 + 8 * BAR_BIAS);
          mbar_wait(bar0 + 8 * BAR_PUB_KV, 0); PROF(3); fence_gpu(); red_inc(&g_cntKV[j * 8]); PROF(4);
        }
      } else {
        const int h0 = 2 * (aw - 1);
        if (aw == 1 && lane < 4) {
          const uint8_t* base = lane == 0 ? wqkv : lane == 1 ? w1 : lane == 2 ? w2 : wo;
          const uint32_t bytes = lane == 0 ? 12288u : lane == 3 ? 4096u : 14336u;
          asm volatile("cp.async.bulk.prefetch.L2.global [%0], %1;" ::"l"(base + (size_t)bid * bytes), "r"(bytes) : "memory");
        }
        if (rb == 0) {
          float4* z = reinterpret_cast<float4*>(&g_kv[ep1 & 1][(4 * j + h0) * 272]);
          for (int i = lane; i < 136; i += 32) z[i] = make_float4(0.f, 0.f, 0.f, 0.f);
        }
        const float* kvbuf = &g_kv[(ep1 & 1) ^ 1][(4 * j + h0) * 272];
        mbar_wait(bar0 + 8 * BAR_PUB_KV, 0);
        PROF(1);
        if (lane == 0) poll_ge(&g_cntKV[j * 8], 16u * ep1);
        __syncwarp();
        PROF(2);
        {
          const int d = lane >> 1, hf = lane & 1;
          const float* src = kvbuf + d * 16 + hf * 8;
          const uint32_t dst = sb + OFF_KVB + d * 128 + h0 * 2048;
          uint4 v[2][2]; float zz[2];
#pragma unroll
          for (int q = 0; q < 2; q++) {
            v[q][0] = ldg_cg(src + q * 272); v[q][1] = ldg_cg(src + q * 272 + 4);
            asm volatile("ld.global.cg.f32 %0, [%1];" : "=f"(zz[q]) : "l"(kvbuf + q * 272 + 256 + d) : "memory");
          }
#pragma unroll
          for (int q = 0; q < 2; q++) {
            const int hh = h0 + q;
            sts_v4(dst + q * 2048 + (((2 * hh + hf) ^ (d & 7)) << 4),
                   pack2(__uint_as_float(v[q][0].x), __uint_as_float(v[q][0].y)), pack2(__uint_as_float(v[q][0].z), __uint_as_float(v[q][0].w)),
                   pack2(__uint_as_float(v[q][1].x), __uint_as_float(v[q][1].y)), pack2(__uint_as_float(v[q][1].z), __uint_as_float(v[q][1].w)));
            const uint32_t z2 = pack2(zz[q], zz[q]);
            if (hf == 0) sts_v4(dst + 8192 + q * 2048 + ((hh ^ (d & 7)) << 4), z2, z2, z2, z2);
          }
        }
        fence_async_smem();
        __syncwarp();
        if (lane == 0) mbar_arrive(bar0 + 8 * BAR_RDY_KV);
        PROF(3);
      }
    }
  } else {
    asm volatile("setmaxnreg.inc.sync.aligned.u32 232;");
    const int wg = warp >> 2;
    const int g = lane >> 2, t = lane & 3;
    const int lr0 = warp * 16 + g;
    const int slab = rb * 8 + warp;
    unsigned dn; asm volatile("ld.relaxed.gpu.global.u32 %0, [%1];" : "=r"(dn) : "l"(&g_done) : "memory");
    const uint32_t a_lo = dlo(sb + OFF_D + wg * 8192, 16);
    const uint32_t sb_lo = sb >> 4;

#define B_LO(gs, off, lbo) (sb_lo + ((slot_off(slot_of(gs)) + (off)) >> 4) + (((lbo) >> 4) << 16))
#define WAIT_FULL(gs) do { if ((gs) < NSTAGES) mbar_wait(bar0 + 8 * (BAR_FULL + slot_of((gs) < NSTAGES ? (gs) : 0)), use_of((gs) < NSTAGES ? (gs) : 0) & 1); } while (0)
#define RELEASE_SLOT(sl) do { if (lane == 0) mbar_arrive(bar0 + 8 * (BAR_EMPTY + (sl))); } while (0)
#define RELEASE_STAGE(gs) do { if ((gs) >= 0 && (gs) < 46) RELEASE_SLOT(slot_of((gs) < 0 ? 0 : (gs))); } while (0)
#define WARP_ARRIVE(b) do { __syncwarp(); if (lane == 0) mbar_arrive(bar0 + 8 * (b)); } while (0)

    uint4* act_out = g_act + (size_t)(slab * 112 + 14 * j) * 32 + lane;
    const uint32_t bias_addr = sb + OFF_B1 + 8 * t;
    float rs0, rs1;
    float pool[160];
    float (&acca)[64] = reinterpret_cast<float (&)[64]>(pool[0]);
    float (&accq)[96] = reinterpret_cast<float (&)[96]>(pool[64]);
    float (&accb)[48] = reinterpret_cast<float (&)[48]>(pool[0]);
    float (&accy)[64] = reinterpret_cast<float (&)[64]>(pool[64]);
    float (&accs)[32] = reinterpret_cast<float (&)[32]>(pool[0]);
    float rl0, rl1, ir0, ir1;
    const unsigned ep1 = dn / NCTA + 1u;
    const uint32_t tag = ep1 & 1u;
    {
      uint4 q[16], p[16];
      const int par = g & 1;
      const uint32_t rowa = sb + OFF_D + lr0 * 128;
      const uint32_t u0 = (uint32_t)(((par * 4 + t) ^ g) << 4), u1 = u0 ^ 64u;
      named_bar_sync(0, 384);
      float sm[2][4], ga[2][4], gb[2][4];
#pragma unroll
      for (int a = 0; a < 2; a++) {
        sm[a][0] = sm[a][1] = sm[a][2] = sm[a][3] = 0.f;
        ga[a][0] = ga[a][1] = ga[a][2] = ga[a][3] = 0.f;
        gb[a][0] = gb[a][1] = gb[a][2] = gb[a][3] = 0.f;
      }
      const uint32_t ones = 0x3F803F80u;
#pragma unroll
      for (int c = 0; c < 8; c++) {
        if ((c & 1) == 0) mbar_wait(bar0 + 8 * (BAR_X + (c >> 1)), 0);
        q[2 * c] = lds_v4(rowa + c * 16384 + u0);     p[2 * c] = lds_v4(rowa + c * 16384 + 1024 + u0);
        q[2 * c + 1] = lds_v4(rowa + c * 16384 + u1); p[2 * c + 1] = lds_v4(rowa + c * 16384 + 1024 + u1);
#pragma unroll
        for (int h = 0; h < 2; h++) {
          const int i = 2 * c + h;
          mma16816(sm[0], q[i].x, p[i].x, q[i].y, p[i].y, ones, ones);
          mma16816(sm[1], q[i].z, p[i].z, q[i].w, p[i].w, ones, ones);
          mma16816(ga[0], q[i].x, p[i].x, q[i].y, p[i].y, q[i].x, q[i].y);
          mma16816(ga[1], q[i].z, p[i].z, q[i].w, p[i].w, q[i].z, q[i].w);
          mma16816(gb[0], q[i].x, p[i].x, q[i].y, p[i].y, p[i].x, p[i].y);
          mma16816(gb[1], q[i].z, p[i].z, q[i].w, p[i].w, p[i].z, p[i].w);
        }
      }
      const float m0 = (sm[0][0] + sm[1][0]) * (1.f / DM);
      const float m1 = (sm[0][2] + sm[1][2]) * (1.f / DM);
      const uint32_t mb0 = pack2(m0, m0), mb1 = pack2(m1, m1);
      PROF(12);
#pragma unroll
      for (int i = 0; i < 16; i++) {
        const uint32_t off = (uint32_t)(i >> 1) * 16384 + ((i & 1) ? u1 : u0);
        sts_v4(rowa + off, hsub2_bf16(q[i].x, mb0), hsub2_bf16(q[i].y, mb0), hsub2_bf16(q[i].z, mb0), hsub2_bf16(q[i].w, mb0));
        sts_v4(rowa + 1024 + off, hsub2_bf16(p[i].x, mb1), hsub2_bf16(p[i].y, mb1), hsub2_bf16(p[i].z, mb1), hsub2_bf16(p[i].w, mb1));
      }
      fence_async_smem();
      float d0 = par ? ga[0][1] + ga[1][1] : ga[0][0] + ga[1][0];
      float d1 = par ? gb[0][3] + gb[1][3] : gb[0][2] + gb[1][2];
      d0 = __shfl_sync(0xffffffffu, d0, (lane & ~3) | (g >> 1));
      d1 = __shfl_sync(0xffffffffu, d1, (lane & ~3) | (g >> 1));
      const float v0 = fmaxf(d0 * (1.f / DM) - m0 * m0, 0.f) + 1e-5f;
      const float v1 = fmaxf(d1 * (1.f / DM) - m1 * m1, 0.f) + 1e-5f;
      rs0 = rsqrtf(v0); rs1 = rsqrtf(v1);
      ir0 = v0 * rs0; ir1 = v1 * rs1;
      rl0 = rs0 * LOG2E; rl1 = rs1 * LOG2E;
      mbar_wait(bar0 + 8 * BAR_BIAS, 0);
      init_bias<16>(acca, bias_addr, ir0, ir1);
      named_bar_sync(1 + wg, 128);
      PROF(1);
    }
    const uint4* act_in = g_act + (size_t)(slab * 112 + 56 * khalf) * 32 + lane;
    const uint4* o_in = g_o + (size_t)(slab * 32) * 32 + lane;
    uint4 ab[4][4];
    auto a_ptr = [&](int rs, int kk) -> const uint4* {
      if (rs < 8) return act_in + (14 * (rs >> 1) + 4 * (rs & 1) + kk) * 32;
      if (rs < 16) return act_in + (14 * ((rs - 8) >> 1) + 8 + 3 * (rs & 1) + kk) * 32;
      return o_in + (4 * (rs - 16) + kk) * 32;
    };
    auto load_a = [&](int rs) {
      if (rs < 24) {
#pragma unroll
        for (int kk = 0; kk < 4; kk++) if (!(rs >= 8 && rs < 16 && kk == 3)) ab[rs & 3][kk] = ldg_frag(a_ptr(rs, kk));
      }
    };
    auto check_a = [&](int rs) {
      if (rs >= 24) return;
      if (rs >= 8 && rs < 16) validate3(ab[rs & 3], a_ptr(rs, 0), tag);
      else validate4(ab[rs & 3], a_ptr(rs, 0), tag);
    };
    auto keep_a = [&](int rs) {
      if (rs < 0) return;
#pragma unroll
      for (int kk = 0; kk < 4; kk++) if (!(rs >= 8 && rs < 16 && kk == 3)) fence_u4(ab[rs & 3][kk]);
    };
    WAIT_FULL(0);
#pragma unroll
    for (int st = 0; st < 8; st++) {
      wg_fence();
#pragma unroll
      for (int kk = 0; kk < 4; kk++) wgmma_ss_n128<1>(acca, a_lo + ((st * 16384 + kk * 32) >> 4), B_LO(st, kk * 2048, 8192));
      wg_commit();
      RELEASE_STAGE(st - 2);
      if (st == 0) zero_regs(accq);
      WAIT_FULL(st + 1);
      wg_wait<1>();
    }
    PROF(2);
#pragma unroll
    for (int st = 0; st < 16; st++) {
      const int gs = 8 + st;
      const uint32_t as = a_lo + (((st >> 1) * 16384 + (st & 1) * 64) >> 4);
      wg_fence();
      wgmma_ss_n192<1>(accq, as, B_LO(gs, 0, 4096));
      wgmma_ss_n192<1>(accq, as + 2, B_LO(gs, 2048, 4096));
      wg_commit();
      RELEASE_STAGE(gs - 2);
      if (st == 1) fence_regs(acca);
      if (st >= 1 && st < 9) mish_tile(acca + 8 * (st - 1), rs0, rs1, rl0, rl1, act_out + (st - 1) * 32, tag);
      if (st == 9) init_bias<12>(accb, bias_addr + 512, ir0, ir1);
      WAIT_FULL(gs + 1);
      wg_wait<1>();
      if (st == 8) PROF(3);
    }
    PROF(4);
    uint4 pq[4];
    {
      const int m = lane >> 3, rr = lane & 7;
      const uint32_t srow = sb + OFF_D + (warp * 16 + (m & 1) * 8 + rr) * 128;
      const uint32_t ka = dlo(sb + OFF_PK + wg * 8192, 16);
      const uint32_t vb = dlo(sb + OFF_V + wg * 8192, OFF_ONES - (OFF_V + wg * 8192));
      float (&acck)[36] = reinterpret_cast<float (&)[36]>(pool[64]);
#pragma unroll
      for (int st = 0; st < 8; st++) {
        const int gs = 24 + st;
        wg_fence();
#pragma unroll
        for (int kk = 0; kk < 4; kk++) wgmma_ss_n96<1>(accb, a_lo + ((st * 16384 + kk * 32) >> 4), B_LO(gs, kk * 2048, 8192));
        if (st == 4) {
          wgmma_tt_n72<0>(acck, ka, vb);
#pragma unroll
          for (int kk = 1; kk < 4; kk++) wgmma_tt_n72<1>(acck, ka + kk * 128, vb + kk * 128);
        }
        wg_commit();
        RELEASE_STAGE(gs - 2);
        if (st >= 5) RELEASE_SLOT(5 + (st - 2) - 3);
        if (st == 1) {
          fence_regs(accq);
          pq[0] = phi_tile(accq + 64, rs0, rs1, rl0, rl1); pq[1] = phi_tile(accq + 72, rs0, rs1, rl0, rl1);
          pq[2] = phi_tile(accq + 80, rs0, rs1, rl0, rl1); pq[3] = phi_tile(accq + 88, rs0, rs1, rl0, rl1);
        } else if (st == 2) {
#pragma unroll
          for (int i = 0; i < 4; i++) {
            const uint4 r = phi_tile(accq + 8 * i, rs0, rs1, rl0, rl1);
            stmatrix_x4(srow + OFF_PK + (((2 * i + (m >> 1)) ^ rr) << 4), r.x, r.y, r.z, r.w);
          }
        } else if (st == 3) {
#pragma unroll
          for (int i = 0; i < 4; i++) {
            const float* c = accq + 32 + 8 * i;
            stmatrix_x4(srow + OFF_V + (((2 * i + (m >> 1)) ^ rr) << 4),
                        pack2(c[0] * rs0, c[1] * rs0), pack2(c[2] * rs1, c[3] * rs1), pack2(c[4] * rs0, c[5] * rs0), pack2(c[6] * rs1, c[7] * rs1));
          }
          fence_async_smem();
          named_bar_sync(1 + wg, 128);
        } else if (st == 5) {
          load_a(0); load_a(1);
        } else if (st == 6) {
          fence_regs(acck);
          const int wq = warp & 3;
          float* hb = &g_kv[(ep1 & 1) ^ 1][(4 * j + wq) * 272];
          float* a0p = hb + g * 16 + 2 * t;
#pragma unroll
          for (int w = 0; w < 4; w++) {
            if (wq == w) {
              red_add_v2(a0p, acck[8 * w], acck[8 * w + 1]); red_add_v2(a0p + 128, acck[8 * w + 2], acck[8 * w + 3]);
              red_add_v2(a0p + 8, acck[8 * w + 4], acck[8 * w + 5]); red_add_v2(a0p + 136, acck[8 * w + 6], acck[8 * w + 7]);
            }
          }
          if (t == 0) { red_add_f32(hb + 256 + g, acck[32]); red_add_f32(hb + 264 + g, acck[34]); }
#pragma unroll
          for (int i = 0; i < 4; i++) sts_v4(sb + OFF_KVB + warp * 2048 + i * 512 + lane * 16, 0u, 0u, 0u, 0u);
          WARP_ARRIVE(BAR_PUB_KV);
        }
        if (st == 7) check_a(0);
        WAIT_FULL(gs + 1);
        wg_wait<1>();
      }
    }
    PROF(5);
#pragma unroll
    for (int rs = 0; rs < 24; rs++) {
      const int gs = 32 + rs;
      if (rs == O_STAGE) mbar_wait(bar0 + 8 * BAR_RDY_KV, 0);
      wg_fence();
      if (rs < 8) {
#pragma unroll
        for (int kk = 0; kk < 4; kk++) {
          if (rs == 0 && kk == 0) wgmma_rs_n128<0>(accy, ab[rs & 3][kk], B_LO(gs, kk * 2048, 8192));
          else wgmma_rs_n128<1>(accy, ab[rs & 3][kk], B_LO(gs, kk * 2048, 8192));
        }
      } else if (rs < 16) {
#pragma unroll
        for (int kk = 0; kk < 3; kk++) wgmma_rs_n128<1>(accy, ab[rs & 3][kk], B_LO(gs, kk * 2048, 6144));
      } else {
#pragma unroll
        for (int kk = 0; kk < 4; kk++) {
          if (rs == 16 && kk == 0) wgmma_rs_n64<0>(accs, ab[rs & 3][kk], B_LO(gs, kk * 2048, 8192));
          else wgmma_rs_n64<1>(accs, ab[rs & 3][kk], B_LO(gs, kk * 2048, 8192));
        }
      }
      if (rs == O_STAGE) {
        const uint32_t kb = dlo(sb + OFF_KVB, 8192);
        wgmma_rs_n96<0>(accb, pq[0], kb);
#pragma unroll
        for (int kk = 1; kk < 4; kk++) wgmma_rs_n96<1>(accb, pq[kk], kb + kk * 128);
      }
      wg_commit();
      RELEASE_STAGE(gs - 2);
      if (rs < 2) RELEASE_SLOT(8 + rs);
      keep_a(rs - 2);
      load_a(rs + 2);
      if (rs == 1) fence_regs(accb);
      if (rs == 1 || rs == 2) {
#pragma unroll
        for (int i = 3 * (rs - 1); i < 3 * (rs - 1) + 3; i++)
          mish_tile(accb + 8 * i, rs0, rs1, rl0, rl1, act_out + (8 + i) * 32, tag);
      }
      if (rs == O_STAGE + 2) {
        fence_regs(accb);
#pragma unroll
        for (int kk = 0; kk < 4; kk++) fence_u4(pq[kk]);
        uint4* o_out = g_o + (size_t)(slab * 32 + 4 * j) * 32 + lane;
#pragma unroll
        for (int hh = 0; hh < 4; hh++) {
          const float i0 = __fdividef(1.f, accb[32 + 4 * hh] + 1e-6f), i1 = __fdividef(1.f, accb[34 + 4 * hh] + 1e-6f);
          const float* n = accb + 8 * hh;
          stg_frag(o_out + hh * 32, pack2(n[0] * i0, n[1] * i0), pack2(n[2] * i1, n[3] * i1), pack2(n[4] * i0, n[5] * i0), pack2(n[6] * i1, n[7] * i1), tag);
        }
      }
      if (rs == 17) {
        fence_regs(accy);
        float4* yp = g_yp + (size_t)((bid * 8 + warp) * 8) * 32 + lane;
#pragma unroll
        for (int q = 0; q < 8; q++) {
          const uint32_t v0 = (__float_as_uint(accy[32 + 4 * q]) & ~1u) | tag, v1 = (__float_as_uint(accy[33 + 4 * q]) & ~1u) | tag;
          const uint32_t v2 = (__float_as_uint(accy[34 + 4 * q]) & ~1u) | tag, v3 = (__float_as_uint(accy[35 + 4 * q]) & ~1u) | tag;
          asm volatile("st.relaxed.gpu.global.v4.u32 [%0], {%1,%2,%3,%4};" ::"l"(yp + q * 32), "r"(v0), "r"(v1), "r"(v2), "r"(v3) : "memory");
        }
      }
      check_a(rs + 1);
      WAIT_FULL(gs + 1);
      wg_wait<1>();
      if (rs == 7) PROF(6);
      if (rs == 15) PROF(8);
    }
    PROF(9);
    {
      const float4* yp = g_yp + (size_t)((pbid * 8 + warp) * 8) * 32 + lane;
      uint4 pv[8];
      uint32_t it = 0;
      wg_wait<0>();
      keep_a(22); keep_a(23);
      fence_regs(accs);
      while (true) {
        uint32_t bad = 0;
#pragma unroll
        for (int q = 0; q < 8; q++)
          asm volatile("ld.relaxed.gpu.global.v4.u32 {%0,%1,%2,%3}, [%4];" : "=r"(pv[q].x), "=r"(pv[q].y), "=r"(pv[q].z), "=r"(pv[q].w) : "l"(yp + q * 32) : "memory");
#pragma unroll
        for (int q = 0; q < 8; q++) bad |= (pv[q].x ^ tag) | (pv[q].y ^ tag) | (pv[q].z ^ tag) | (pv[q].w ^ tag);
        if (!__any_sync(0xffffffffu, bad & 1u)) break;
        if (++it > (1u << 20)) asm volatile("trap;");
      }
      PROF(10);
      mbar_wait(bar0 + 8 * BAR_XT, 0);
      const uint32_t xa = sb + OFF_XT + lr0 * 128 + 4 * t;
#pragma unroll
      for (int q = 0; q < 8; q++) {
        const uint32_t a0 = xa + ((q ^ g) << 4), a1 = a0 + 1024;
        const uint32_t x0 = lds_u32(a0), x1 = lds_u32(a1);
        const float y0 = accy[4 * q] + __uint_as_float(pv[q].x), y1 = accy[4 * q + 1] + __uint_as_float(pv[q].y);
        const float y2 = accy[4 * q + 2] + __uint_as_float(pv[q].z), y3 = accy[4 * q + 3] + __uint_as_float(pv[q].w);
        const float o0 = fmaf(accs[4 * q], silu_f(y0), bf_lo(x0)), o1 = fmaf(accs[4 * q + 1], silu_f(y1), bf_hi(x0));
        const float o2 = fmaf(accs[4 * q + 2], silu_f(y2), bf_lo(x1)), o3 = fmaf(accs[4 * q + 3], silu_f(y3), bf_hi(x1));
        sts_u32(a0, pack2(o0, o1));
        sts_u32(a1, pack2(o2, o3));
      }
      fence_async_smem();
      __syncwarp();
      if (lane == 0) {
        asm volatile("cp.async.bulk.tensor.2d.global.shared::cta.bulk_group [%0, {%2, %3}], [%1];"
                     ::"l"(&tm_out), "r"(sb + OFF_XT + warp * 2048), "r"(128 * nt + 64 * khalf), "r"(rb * 128 + warp * 16) : "memory");
        asm volatile("cp.async.bulk.commit_group;" ::: "memory");
        asm volatile("cp.async.bulk.wait_group.read 0;" ::: "memory");
      }
    }
    PROF(11);
    if (tid == 0) red_inc(&g_done);
  }
}

typedef CUresult (*EncodeFn)(CUtensorMap*, CUtensorMapDataType, cuuint32_t, void*, const cuuint64_t*, const cuuint64_t*,
                             const cuuint32_t*, const cuuint32_t*, CUtensorMapInterleave, CUtensorMapSwizzle,
                             CUtensorMapL2promotion, CUtensorMapFloatOOBfill);

void make_map(EncodeFn enc, CUtensorMap* tm, const void* ptr, int rows, int cols, int box_rows) {
  cuuint64_t gd[2] = {(cuuint64_t)cols, (cuuint64_t)rows};
  cuuint64_t gs[1] = {(cuuint64_t)cols * 2};
  cuuint32_t bd[2] = {64, (cuuint32_t)box_rows};
  cuuint32_t es[2] = {1, 1};
  enc(tm, CU_TENSOR_MAP_DATA_TYPE_BFLOAT16, 2, const_cast<void*>(ptr), gd, gs, bd, es, CU_TENSOR_MAP_INTERLEAVE_NONE,
      CU_TENSOR_MAP_SWIZZLE_128B, CU_TENSOR_MAP_L2_PROMOTION_L2_128B, CU_TENSOR_MAP_FLOAT_OOB_FILL_NONE);
}

}

extern "C" void kernel_launch(void* const* d_in, const int* in_sizes, int n_in, void* d_out, int out_size) {
  const __nv_bfloat16* x = (const __nv_bfloat16*)d_in[0];
  const void* wqkv = d_in[1];
  const void* wo = d_in[2];
  const void* w1 = d_in[4];
  const __nv_bfloat16* b1 = (const __nv_bfloat16*)d_in[5];
  const void* w2 = d_in[6];
  static EncodeFn enc = nullptr;
  if (!enc) {
    cudaDriverEntryPointQueryResult qr;
    void* fn = nullptr;
    cudaGetDriverEntryPoint("cuTensorMapEncodeTiled", &fn, cudaEnableDefault, &qr);
    enc = (EncodeFn)fn;
    cudaFuncSetAttribute(fused_kernel, cudaFuncAttributeMaxDynamicSharedMemorySize, SMEM_ALLOC);
  }
  CUtensorMap tx, tq, t1, t2a, t2b, to, tout;
  make_map(enc, &tx, x, 2048, DM, 128);
  make_map(enc, &tq, wqkv, DM, 3 * DM, 32);
  make_map(enc, &t1, w1, DM, FF, 64);
  make_map(enc, &t2a, w2, FF, DM, 64);
  make_map(enc, &t2b, w2, FF, DM, 48);
  make_map(enc, &to, wo, DM, DM, 64);
  make_map(enc, &tout, d_out, 2048, DM, 16);
  fused_kernel<<<NCTA, 384, SMEM_ALLOC>>>(tx, tq, t1, t2a, t2b, to, tout, (const uint8_t*)wqkv, (const uint8_t*)w1,
                                          (const uint8_t*)w2, (const uint8_t*)wo, b1);
}
```

```cpp
#include <cuda_runtime.h>
#include <cuda_bf16.h>
#include <cuda.h>
#include <stdint.h>

namespace {

constexpr int DM = 512, FF = 1792;
constexpr int NCTA = 128;
constexpr int NRING = 5;
constexpr int NSLOT = 10;
constexpr int SLOT_BYTES = 16384;
constexpr int OFF_D = 0;
constexpr int OFF_PK = 0, OFF_V = 16384;
constexpr int OFF_KVB = 0;
constexpr int OFF_XT = 16384;
constexpr int OFF_RING = 131072;
constexpr int OFF_MISC = OFF_RING + NRING * SLOT_BYTES;
constexpr int OFF_ONES = OFF_MISC;
constexpr int OFF_BAR = OFF_MISC + 8192;
constexpr int OFF_B1 = OFF_MISC + 8704;
constexpr int SMEM_ALLOC = OFF_MISC + 9728;

enum { BAR_FULL = 0, BAR_EMPTY = NSLOT, BAR_X = 2 * NSLOT, BAR_BIAS = BAR_X + 4, BAR_XT,
       BAR_PUB_KV, BAR_RDY_KV, BAR_COUNT };
static_assert(BAR_COUNT <= 40, "too many barriers");

constexpr int NSTAGES = 56;
constexpr int O_STAGE = 7;
__host__ __device__ constexpr int slot_of(int gs) {
  if (gs < 32) return gs % 5;
  const int p = (gs - 32) % 10;
  return p < 5 ? 5 + p : (p - 3) % 5;
}
__host__ __device__ constexpr int use_of(int gs) {
  if (gs < 32) return gs / 5;
  const int sl = slot_of(gs);
  return (gs - 32) / 10 + (sl < 5 ? (sl < 2 ? 7 : 6) : 0);
}
__host__ __device__ constexpr int slot_off(int sl) { return sl < 5 ? OFF_RING + sl * SLOT_BYTES : OFF_D + (sl - 2) * SLOT_BYTES; }

__device__ uint4 g_act[128 * 112 * 32];
__device__ uint4 g_o[128 * 32 * 32];
__device__ float4 g_yp[NCTA * 8 * 8 * 32];
__device__ float g_kv[2][32 * 272];
__device__ unsigned g_cntKV[8 * 8];
__device__ unsigned g_done;

#define PROF(i)

__device__ __forceinline__ uint32_t smem_u32(const void* p) { return (uint32_t)__cvta_generic_to_shared(p); }
__device__ __forceinline__ void mbar_init(uint32_t bar, uint32_t cnt) { asm volatile("mbarrier.init.shared::cta.b64 [%0], %1;" ::"r"(bar), "r"(cnt)); }
__device__ __forceinline__ void mbar_expect_tx(uint32_t bar, uint32_t bytes) { asm volatile("mbarrier.arrive.expect_tx.shared::cta.b64 _, [%0], %1;" ::"r"(bar), "r"(bytes) : "memory"); }
__device__ __forceinline__ void mbar_arrive(uint32_t bar) { asm volatile("mbarrier.arrive.shared::cta.b64 _, [%0];" ::"r"(bar) : "memory"); }
__device__ __forceinline__ void mbar_wait(uint32_t bar, uint32_t parity) {
  asm volatile("{\n.reg .pred P1;\n.reg .u32 cnt;\n"
               "mbarrier.try_wait.parity.shared::cta.b64 P1, [%0], %1;\n@P1 bra DONE;\n"
               "mov.u32 cnt, 0;\n"
               "LAB_WAIT:\n"
               "mbarrier.try_wait.parity.shared::cta.b64 P1, [%0], %1;\n@P1 bra DONE;\n"
               "add.u32 cnt, cnt, 1;\nsetp.lt.u32 P1, cnt, 16777216;\n@P1 bra LAB_WAIT;\ntrap;\n"
               "DONE:\n}" ::"r"(bar), "r"(parity) : "memory");
}
__device__ __forceinline__ void tma2d(uint32_t dst, const CUtensorMap* tm, int c0, int c1, uint32_t bar) {
  asm volatile("cp.async.bulk.tensor.2d.shared::cluster.global.mbarrier::complete_tx::bytes [%0], [%1, {%3, %4}], [%2];" ::"r"(dst), "l"(tm), "r"(bar), "r"(c0), "r"(c1) : "memory");
}
__device__ __forceinline__ void wg_fence() { asm volatile("wgmma.fence.sync.aligned;" ::: "memory"); }
__device__ __forceinline__ void wg_commit() { asm volatile("wgmma.commit_group.sync.aligned;" ::: "memory"); }
template <int N> __device__ __forceinline__ void wg_wait() { asm volatile("wgmma.wait_group.sync.aligned %0;" ::"n"(N) : "memory"); }
template <int N> __device__ __forceinline__ void zero_regs(float (&d)[N]) {
#pragma unroll
  for (int i = 0; i < N; i++) d[i] = 0.f;
}
template <int N> __device__ __forceinline__ void fence_regs(float (&d)[N]) {
#pragma unroll
  for (int i = 0; i < N; i++) asm volatile("" : "+f"(d[i])::"memory");
}
__device__ __forceinline__ void fence_u4(uint4& v) { asm volatile("" : "+r"(v.x), "+r"(v.y), "+r"(v.z), "+r"(v.w)::"memory"); }
__device__ __forceinline__ void named_bar_sync(int id, int n) { asm volatile("bar.sync %0, %1;" ::"r"(id), "r"(n) : "memory"); }
__device__ __forceinline__ void fence_gpu() { asm volatile("fence.acq_rel.gpu;" ::: "memory"); }
__device__ __forceinline__ void fence_async_smem() { asm volatile("fence.proxy.async.shared::cta;" ::: "memory"); }
__device__ __forceinline__ constexpr uint32_t dlo(uint32_t addr, uint32_t lbo_bytes) { return ((addr & 0x3FFFFu) >> 4) | ((lbo_bytes >> 4) << 16); }
__device__ __forceinline__ void mma16816(float (&c)[4], uint32_t a0, uint32_t a1, uint32_t a2, uint32_t a3, uint32_t b0, uint32_t b1) {
  asm volatile("mma.sync.aligned.m16n8k16.row.col.f32.bf16.bf16.f32 {%0,%1,%2,%3}, {%4,%5,%6,%7}, {%8,%9}, {%0,%1,%2,%3};"
               : "+f"(c[0]), "+f"(c[1]), "+f"(c[2]), "+f"(c[3]) : "r"(a0), "r"(a1), "r"(a2), "r"(a3), "r"(b0), "r"(b1));
}
__device__ __forceinline__ void stmatrix_x4(uint32_t addr, uint32_t a, uint32_t b, uint32_t c, uint32_t d) {
  asm volatile("stmatrix.sync.aligned.m8n8.x4.shared.b16 [%0], {%1,%2,%3,%4};" ::"r"(addr), "r"(a), "r"(b), "r"(c), "r"(d) : "memory");
}
__device__ __forceinline__ uint32_t pack2(float lo, float hi) { uint32_t r; asm("cvt.rn.bf16x2.f32 %0, %1, %2;" : "=r"(r) : "f"(hi), "f"(lo)); return r; }
__device__ __forceinline__ float ex2(float x) { float r; asm("ex2.approx.ftz.f32 %0, %1;" : "=f"(r) : "f"(x)); return r; }
__device__ __forceinline__ float rcp(float x) { float r; asm("rcp.approx.ftz.f32 %0, %1;" : "=f"(r) : "f"(x)); return r; }
__device__ __forceinline__ float bf_lo(uint32_t v) { return __uint_as_float(v << 16); }
__device__ __forceinline__ float bf_hi(uint32_t v) { return __uint_as_float(v & 0xffff0000u); }
__device__ __forceinline__ uint32_t hsub2_bf16(uint32_t a, uint32_t b) {
  __nv_bfloat162 x = *reinterpret_cast<__nv_bfloat162*>(&a), y = *reinterpret_cast<__nv_bfloat162*>(&b);
  __nv_bfloat162 r = __hsub2(x, y);
  return *reinterpret_cast<uint32_t*>(&r);
}
__device__ __forceinline__ uint4 ldg_cg(const void* p) {
  uint4 v; asm volatile("ld.global.cg.v4.u32 {%0,%1,%2,%3}, [%4];" : "=r"(v.x), "=r"(v.y), "=r"(v.z), "=r"(v.w) : "l"(p) : "memory"); return v;
}
__device__ __forceinline__ void stg_frag(void* p, uint32_t a, uint32_t b, uint32_t c, uint32_t d, uint32_t tag) {
  asm volatile("st.relaxed.gpu.global.v4.u32 [%0], {%1,%2,%3,%4};" ::"l"(p), "r"((a & ~1u) | tag), "r"(b), "r"(c), "r"(d) : "memory");
}
__device__ __forceinline__ uint4 ldg_frag(const void* p) {
  uint4 v; asm volatile("ld.relaxed.gpu.global.v4.u32 {%0,%1,%2,%3}, [%4];" : "=r"(v.x), "=r"(v.y), "=r"(v.z), "=r"(v.w) : "l"(p) : "memory"); return v;
}
__device__ __forceinline__ void validate4(uint4 (&v)[4], const void* p, uint32_t tag4) {
  asm volatile("{\n.reg .pred P1;\n.reg .u32 cnt, tb, it;\n"
               "mov.u32 it, 0;\n"
               "LAB_CHECK:\n"
               "lop3.b32 tb, %0, %4, %8, 0x80;\nand.b32 tb, tb, %12;\n"
               "lop3.b32 cnt, %0, %4, %8, 0xFE;\nor.b32 cnt, cnt, %12;\n"
               "xor.b32 tb, tb, %17;\nxor.b32 cnt, cnt, %17;\nor.b32 tb, tb, cnt;\nand.b32 tb, tb, 1;\n"
               "setp.eq.u32 P1, tb, 0;\n@P1 bra DONE;\n"
               "ld.relaxed.gpu.global.v4.u32 {%0,%1,%2,%3}, [%16];\n"
               "ld.relaxed.gpu.global.v4.u32 {%4,%5,%6,%7}, [%16+512];\n"
               "ld.relaxed.gpu.global.v4.u32 {%8,%9,%10,%11}, [%16+1024];\n"
               "ld.relaxed.gpu.global.v4.u32 {%12,%13,%14,%15}, [%16+1536];\n"
               "add.u32 it, it, 1;\nsetp.lt.u32 P1, it, 4194304;\n@P1 bra LAB_CHECK;\ntrap;\n"
               "DONE:\n}"
               : "+r"(v[0].x), "+r"(v[0].y), "+r"(v[0].z), "+r"(v[0].w), "+r"(v[1].x), "+r"(v[1].y), "+r"(v[1].z), "+r"(v[1].w),
                 "+r"(v[2].x), "+r"(v[2].y), "+r"(v[2].z), "+r"(v[2].w), "+r"(v[3].x), "+r"(v[3].y), "+r"(v[3].z), "+r"(v[3].w)
               : "l"(p), "r"(tag4) : "memory");
}
__device__ __forceinline__ void validate3(uint4 (&v)[4], const void* p, uint32_t tag4) {
  asm volatile("{\n.reg .pred P1;\n.reg .u32 cnt, tb, it;\n"
               "mov.u32 it, 0;\n"
               "LAB_CHECK:\n"
               "lop3.b32 tb, %0, %4, %8, 0x80;\n"
               "lop3.b32 cnt, %0, %4, %8, 0xFE;\n"
               "xor.b32 tb, tb, %13;\nxor.b32 cnt, cnt, %13;\nor.b32 tb, tb, cnt;\nand.b32 tb, tb, 1;\n"
               "setp.eq.u32 P1, tb, 0;\n@P1 bra DONE;\n"
               "ld.relaxed.gpu.global.v4.u32 {%0,%1,%2,%3}, [%12];\n"
               "ld.relaxed.gpu.global.v4.u32 {%4,%5,%6,%7}, [%12+512];\n"
               "ld.relaxed.gpu.global.v4.u32 {%8,%9,%10,%11}, [%12+1024];\n"
               "add.u32 it, it, 1;\nsetp.lt.u32 P1, it, 4194304;\n@P1 bra LAB_CHECK;\ntrap;\n"
               "DONE:\n}"
               : "+r"(v[0].x), "+r"(v[0].y), "+r"(v[0].z), "+r"(v[0].w), "+r"(v[1].x), "+r"(v[1].y), "+r"(v[1].z), "+r"(v[1].w),
                 "+r"(v[2].x), "+r"(v[2].y), "+r"(v[2].z), "+r"(v[2].w)
               : "l"(p), "r"(tag4) : "memory");
}
__device__ __forceinline__ void sts_v4(uint32_t addr, uint32_t a, uint32_t b, uint32_t c, uint32_t d) {
  asm volatile("st.shared.v4.u32 [%0], {%1,%2,%3,%4};" ::"r"(addr), "r"(a), "r"(b), "r"(c), "r"(d) : "memory");
}
__device__ __forceinline__ void sts_f32(uint32_t addr, float v) { asm volatile("st.shared.f32 [%0], %1;" ::"r"(addr), "f"(v) : "memory"); }
__device__ __forceinline__ uint4 lds_v4(uint32_t addr) { uint4 v; asm volatile("ld.shared.v4.u32 {%0,%1,%2,%3}, [%4];" : "=r"(v.x), "=r"(v.y), "=r"(v.z), "=r"(v.w) : "r"(addr) : "memory"); return v; }
__device__ __forceinline__ uint32_t lds_u32(uint32_t addr) { uint32_t v; asm volatile("ld.shared.u32 %0, [%1];" : "=r"(v) : "r"(addr) : "memory"); return v; }
__device__ __forceinline__ void sts_u32(uint32_t addr, uint32_t v) { asm volatile("st.shared.u32 [%0], %1;" ::"r"(addr), "r"(v) : "memory"); }
__device__ __forceinline__ float2 lds_f32x2(uint32_t addr) { float2 v; asm volatile("ld.shared.v2.f32 {%0,%1}, [%2];" : "=f"(v.x), "=f"(v.y) : "r"(addr) : "memory"); return v; }
__device__ __forceinline__ void red_add_v2(float* p, float a, float b) { asm volatile("red.relaxed.gpu.global.add.v2.f32 [%0], {%1,%2};" ::"l"(p), "f"(a), "f"(b) : "memory"); }
__device__ __forceinline__ void red_add_f32(float* p, float a) { asm volatile("red.relaxed.gpu.global.add.f32 [%0], %1;" ::"l"(p), "f"(a) : "memory"); }
__device__ __forceinline__ void red_inc(unsigned* cnt) { asm volatile("red.relaxed.gpu.global.add.u32 [%0], 1;" ::"l"(cnt) : "memory"); }
__device__ __forceinline__ void poll_ge(const unsigned* cnt, unsigned target) {
  asm volatile("{\n.reg .pred P1;\n.reg .u32 cnt, v;\n.reg .s32 d;\n"
               "mov.u32 cnt, 0;\n"
               "LAB_POLL:\n"
               "ld.relaxed.gpu.global.u32 v, [%0];\nsub.s32 d, v, %1;\nsetp.ge.s32 P1, d, 0;\n@P1 bra DONE;\n"
               "add.u32 cnt, cnt, 1;\nsetp.lt.u32 P1, cnt, 4194304;\n@P1 bra LAB_POLL;\ntrap;\n"
               "DONE:\nld.acquire.gpu.global.u32 v, [%0];\n}" ::"l"(cnt), "r"(target) : "memory");
}

template <int SCALE_D> __device__ __forceinline__ void wgmma_ss_n192(float (&d)[96], uint32_t da, uint32_t db) {
  asm volatile("{\n.reg .b64 da, db;\nmov.b64 da, {%96, %98};\nmov.b64 db, {%97, %98};\n"
    "wgmma.mma_async.sync.aligned.m64n192k16.f32.bf16.bf16 {%0, %1, %2, %3, %4, %5, %6, %7, %8, %9, %10, %11, %12, %13, %14, %15, %16, %17, %18, %19, %20, %21, %22, %23, %24, %25, %26, %27, %28, %29, %30, %31, %32, %33, %34, %35, %36, %37, %38, %39, %40, %41, %42, %43, %44, %45, %46, %47, %48, %49, %50, %51, %52, %53, %54, %55, %56, %57, %58, %59, %60, %61, %62, %63, %64, %65, %66, %67, %68, %69, %70, %71, %72, %73, %74, %75, %76, %77, %78, %79, %80, %81, %82, %83, %84, %85, %86, %87, %88, %89, %90, %91, %92, %93, %94, %95}, da, db, %99, 1, 1, 0, 1;\n}\n"
    : "+f"(d[0]), "+f"(d[1]), "+f"(d[2]), "+f"(d[3]), "+f"(d[4]), "+f"(d[5]), "+f"(d[6]), "+f"(d[7]), "+f"(d[8]), "+f"(d[9]), "+f"(d[10]), "+f"(d[11]), "+f"(d[12]), "+f"(d[13]), "+f"(d[14]), "+f"(d[15]), "+f"(d[16]), "+f"(d[17]), "+f"(d[18]), "+f"(d[19]), "+f"(d[20]), "+f"(d[21]), "+f"(d[22]), "+f"(d[23]), "+f"(d[24]), "+f"(d[25]), "+f"(d[26]), "+f"(d[27]), "+f"(d[28]), "+f"(d[29]), "+f"(d[30]), "+f"(d[31]), "+f"(d[32]), "+f"(d[33]), "+f"(d[34]), "+f"(d[35]), "+f"(d[36]), "+f"(d[37]), "+f"(d[38]), "+f"(d[39]), "+f"(d[40]), "+f"(d[41]), "+f"(d[42]), "+f"(d[43]), "+f"(d[44]), "+f"(d[45]), "+f"(d[46]), "+f"(d[47]), "+f"(d[48]), "+f"(d[49]), "+f"(d[50]), "+f"(d[51]), "+f"(d[52]), "+f"(d[53]), "+f"(d[54]), "+f"(d[55]), "+f"(d[56]), "+f"(d[57]), "+f"(d[58]), "+f"(d[59]), "+f"(d[60]), "+f"(d[61]), "+f"(d[62]), "+f"(d[63]), "+f"(d[64]), "+f"(d[65]), "+f"(d[66]), "+f"(d[67]), "+f"(d[68]), "+f"(d[69]), "+f"(d[70]), "+f"(d[71]), "+f"(d[72]), "+f"(d[73]), "+f"(d[74]), "+f"(d[75]), "+f"(d[76]), "+f"(d[77]), "+f"(d[78]), "+f"(d[79]), "+f"(d[80]), "+f"(d[81]), "+f"(d[82]), "+f"(d[83]), "+f"(d[84]), "+f"(d[85]), "+f"(d[86]), "+f"(d[87]), "+f"(d[88]), "+f"(d[89]), "+f"(d[90]), "+f"(d[91]), "+f"(d[92]), "+f"(d[93]), "+f"(d[94]), "+f"(d[95])
    : "r"(da), "r"(db), "r"(0x40000040u), "n"(SCALE_D));
}
template <int SCALE_D> __device__ __forceinline__ void wgmma_ss_n128(float (&d)[64], uint32_t da, uint32_t db) {
  asm volatile("{\n.reg .b64 da, db;\nmov.b64 da, {%64, %66};\nmov.b64 db, {%65, %66};\n"
    "wgmma.mma_async.sync.aligned.m64n128k16.f32.bf16.bf16 {%0, %1, %2, %3, %4, %5, %6, %7, %8, %9, %10, %11, %12, %13, %14, %15, %16, %17, %18, %19, %20, %21, %22, %23, %24, %25, %26, %27, %28, %29, %30, %31, %32, %33, %34, %35, %36, %37, %38, %39, %40, %41, %42, %43, %44, %45, %46, %47, %48, %49, %50, %51, %52, %53, %54, %55, %56, %57, %58, %59, %60, %61, %62, %63}, da, db, %67, 1, 1, 0, 1;\n}\n"
    : "+f"(d[0]), "+f"(d[1]), "+f"(d[2]), "+f"(d[3]), "+f"(d[4]), "+f"(d[5]), "+f"(d[6]), "+f"(d[7]), "+f"(d[8]), "+f"(d[9]), "+f"(d[10]), "+f"(d[11]), "+f"(d[12]), "+f"(d[13]), "+f"(d[14]), "+f"(d[15]), "+f"(d[16]), "+f"(d[17]), "+f"(d[18]), "+f"(d[19]), "+f"(d[20]), "+f"(d[21]), "+f"(d[22]), "+f"(d[23]), "+f"(d[24]), "+f"(d[25]), "+f"(d[26]), "+f"(d[27]), "+f"(d[28]), "+f"(d[29]), "+f"(d[30]), "+f"(d[31]), "+f"(d[32]), "+f"(d[33]), "+f"(d[34]), "+f"(d[35]), "+f"(d[36]), "+f"(d[37]), "+f"(d[38]), "+f"(d[39]), "+f"(d[40]), "+f"(d[41]), "+f"(d[42]), "+f"(d[43]), "+f"(d[44]), "+f"(d[45]), "+f"(d[46]), "+f"(d[47]), "+f"(d[48]), "+f"(d[49]), "+f"(d[50]), "+f"(d[51]), "+f"(d[52]), "+f"(d[53]), "+f"(d[54]), "+f"(d[55]), "+f"(d[56]), "+f"(d[57]), "+f"(d[58]), "+f"(d[59]), "+f"(d[60]), "+f"(d[61]), "+f"(d[62]), "+f"(d[63])
    : "r"(da), "r"(db), "r"(0x40000040u), "n"(SCALE_D));
}
template <int SCALE_D> __device__ __forceinline__ void wgmma_ss_n96(float (&d)[48], uint32_t da, uint32_t db) {
  asm volatile("{\n.reg .b64 da, db;\nmov.b64 da, {%48, %50};\nmov.b64 db, {%49, %50};\n"
    "wgmma.mma_async.sync.aligned.m64n96k16.f32.bf16.bf16 {%0, %1, %2, %3, %4, %5, %6, %7, %8, %9, %10, %11, %12, %13, %14, %15, %16, %17, %18, %19, %20, %21, %22, %23, %24, %25, %26, %27, %28, %29, %30, %31, %32, %33, %34, %35, %36, %37, %38, %39, %40, %41, %42, %43, %44, %45, %46, %47}, da, db, %51, 1, 1, 0, 1;\n}\n"
    : "+f"(d[0]), "+f"(d[1]), "+f"(d[2]), "+f"(d[3]), "+f"(d[4]), "+f"(d[5]), "+f"(d[6]), "+f"(d[7]), "+f"(d[8]), "+f"(d[9]), "+f"(d[10]), "+f"(d[11]), "+f"(d[12]), "+f"(d[13]), "+f"(d[14]), "+f"(d[15]), "+f"(d[16]), "+f"(d[17]), "+f"(d[18]), "+f"(d[19]), "+f"(d[20]), "+f"(d[21]), "+f"(d[22]), "+f"(d[23]), "+f"(d[24]), "+f"(d[25]), "+f"(d[26]), "+f"(d[27]), "+f"(d[28]), "+f"(d[29]), "+f"(d[30]), "+f"(d[31]), "+f"(d[32]), "+f"(d[33]), "+f"(d[34]), "+f"(d[35]), "+f"(d[36]), "+f"(d[37]), "+f"(d[38]), "+f"(d[39]), "+f"(d[40]), "+f"(d[41]), "+f"(d[42]), "+f"(d[43]), "+f"(d[44]), "+f"(d[45]), "+f"(d[46]), "+f"(d[47])
    : "r"(da), "r"(db), "r"(0x40000040u), "n"(SCALE_D));
}
template <int SCALE_D> __device__ __forceinline__ void wgmma_tt_n72(float (&d)[36], uint32_t da, uint32_t db) {
  asm volatile("{\n.reg .b64 da, db;\nmov.b64 da, {%36, %38};\nmov.b64 db, {%37, %38};\n"
    "wgmma.mma_async.sync.aligned.m64n72k16.f32.bf16.bf16 {%0, %1, %2, %3, %4, %5, %6, %7, %8, %9, %10, %11, %12, %13, %14, %15, %16, %17, %18, %19, %20, %21, %22, %23, %24, %25, %26, %27, %28, %29, %30, %31, %32, %33, %34, %35}, da, db, %39, 1, 1, 1, 1;\n}\n"
    : "+f"(d[0]), "+f"(d[1]), "+f"(d[2]), "+f"(d[3]), "+f"(d[4]), "+f"(d[5]), "+f"(d[6]), "+f"(d[7]), "+f"(d[8]), "+f"(d[9]), "+f"(d[10]), "+f"(d[11]), "+f"(d[12]), "+f"(d[13]), "+f"(d[14]), "+f"(d[15]), "+f"(d[16]), "+f"(d[17]), "+f"(d[18]), "+f"(d[19]), "+f"(d[20]), "+f"(d[21]), "+f"(d[22]), "+f"(d[23]), "+f"(d[24]), "+f"(d[25]), "+f"(d[26]), "+f"(d[27]), "+f"(d[28]), "+f"(d[29]), "+f"(d[30]), "+f"(d[31]), "+f"(d[32]), "+f"(d[33]), "+f"(d[34]), "+f"(d[35])
    : "r"(da), "r"(db), "r"(0x40000040u), "n"(SCALE_D));
}
template <int SCALE_D> __device__ __forceinline__ void wgmma_rs_n128(float (&d)[64], const uint4& a, uint32_t db) {
  asm volatile("{\n.reg .b64 db;\nmov.b64 db, {%68, %69};\n"
    "wgmma.mma_async.sync.aligned.m64n128k16.f32.bf16.bf16 {%0, %1, %2, %3, %4, %5, %6, %7, %8, %9, %10, %11, %12, %13, %14, %15, %16, %17, %18, %19, %20, %21, %22, %23, %24, %25, %26, %27, %28, %29, %30, %31, %32, %33, %34, %35, %36, %37, %38, %39, %40, %41, %42, %43, %44, %45, %46, %47, %48, %49, %50, %51, %52, %53, %54, %55, %56, %57, %58, %59, %60, %61, %62, %63}, {%64, %65, %66, %67}, db, %70, 1, 1, 1;\n}\n"
    : "+f"(d[0]), "+f"(d[1]), "+f"(d[2]), "+f"(d[3]), "+f"(d[4]), "+f"(d[5]), "+f"(d[6]), "+f"(d[7]), "+f"(d[8]), "+f"(d[9]), "+f"(d[10]), "+f"(d[11]), "+f"(d[12]), "+f"(d[13]), "+f"(d[14]), "+f"(d[15]), "+f"(d[16]), "+f"(d[17]), "+f"(d[18]), "+f"(d[19]), "+f"(d[20]), "+f"(d[21]), "+f"(d[22]), "+f"(d[23]), "+f"(d[24]), "+f"(d[25]), "+f"(d[26]), "+f"(d[27]), "+f"(d[28]), "+f"(d[29]), "+f"(d[30]), "+f"(d[31]), "+f"(d[32]), "+f"(d[33]), "+f"(d[34]), "+f"(d[35]), "+f"(d[36]), "+f"(d[37]), "+f"(d[38]), "+f"(d[39]), "+f"(d[40]), "+f"(d[41]), "+f"(d[42]), "+f"(d[43]), "+f"(d[44]), "+f"(d[45]), "+f"(d[46]), "+f"(d[47]), "+f"(d[48]), "+f"(d[49]), "+f"(d[50]), "+f"(d[51]), "+f"(d[52]), "+f"(d[53]), "+f"(d[54]), "+f"(d[55]), "+f"(d[56]), "+f"(d[57]), "+f"(d[58]), "+f"(d[59]), "+f"(d[60]), "+f"(d[61]), "+f"(d[62]), "+f"(d[63])
    : "r"(a.x), "r"(a.y), "r"(a.z), "r"(a.w), "r"(db), "r"(0x40000040u), "n"(SCALE_D));
}
template <int SCALE_D> __device__ __forceinline__ void wgmma_rs_n96(float (&d)[48], const uint4& a, uint32_t db) {
  asm volatile("{\n.reg .b64 db;\nmov.b64 db, {%52, %53};\n"
    "wgmma.mma_async.sync.aligned.m64n96k16.f32.bf16.bf16 {%0, %1, %2, %3, %4, %5, %6, %7, %8, %9, %10, %11, %12, %13, %14, %15, %16, %17, %18, %19, %20, %21, %22, %23, %24, %25, %26, %27, %28, %29, %30, %31, %32, %33, %34, %35, %36, %37, %38, %39, %40, %41, %42, %43, %44, %45, %46, %47}, {%48, %49, %50, %51}, db, %54, 1, 1, 1;\n}\n"
    : "+f"(d[0]), "+f"(d[1]), "+f"(d[2]), "+f"(d[3]), "+f"(d[4]), "+f"(d[5]), "+f"(d[6]), "+f"(d[7]), "+f"(d[8]), "+f"(d[9]), "+f"(d[10]), "+f"(d[11]), "+f"(d[12]), "+f"(d[13]), "+f"(d[14]), "+f"(d[15]), "+f"(d[16]), "+f"(d[17]), "+f"(d[18]), "+f"(d[19]), "+f"(d[20]), "+f"(d[21]), "+f"(d[22]), "+f"(d[23]), "+f"(d[24]), "+f"(d[25]), "+f"(d[26]), "+f"(d[27]), "+f"(d[28]), "+f"(d[29]), "+f"(d[30]), "+f"(d[31]), "+f"(d[32]), "+f"(d[33]), "+f"(d[34]), "+f"(d[35]), "+f"(d[36]), "+f"(d[37]), "+f"(d[38]), "+f"(d[39]), "+f"(d[40]), "+f"(d[41]), "+f"(d[42]), "+f"(d[43]), "+f"(d[44]), "+f"(d[45]), "+f"(d[46]), "+f"(d[47])
    : "r"(a.x), "r"(a.y), "r"(a.z), "r"(a.w), "r"(db), "r"(0x40000040u), "n"(SCALE_D));
}
template <int SCALE_D> __device__ __forceinline__ void wgmma_rs_n64(float (&d)[32], const uint4& a, uint32_t db) {
  asm volatile("{\n.reg .b64 db;\nmov.b64 db, {%36, %37};\n"
    "wgmma.mma_async.sync.aligned.m64n64k16.f32.bf16.bf16 {%0, %1, %2, %3, %4, %5, %6, %7, %8, %9, %10, %11, %12, %13, %14, %15, %16, %17, %18, %19, %20, %21, %22, %23, %24, %25, %26, %27, %28, %29, %30, %31}, {%32, %33, %34, %35}, db, %38, 1, 1, 1;\n}\n"
    : "+f"(d[0]), "+f"(d[1]), "+f"(d[2]), "+f"(d[3]), "+f"(d[4]), "+f"(d[5]), "+f"(d[6]), "+f"(d[7]), "+f"(d[8]), "+f"(d[9]), "+f"(d[10]), "+f"(d[11]), "+f"(d[12]), "+f"(d[13]), "+f"(d[14]), "+f"(d[15]), "+f"(d[16]), "+f"(d[17]), "+f"(d[18]), "+f"(d[19]), "+f"(d[20]), "+f"(d[21]), "+f"(d[22]), "+f"(d[23]), "+f"(d[24]), "+f"(d[25]), "+f"(d[26]), "+f"(d[27]), "+f"(d[28]), "+f"(d[29]), "+f"(d[30]), "+f"(d[31])
    : "r"(a.x), "r"(a.y), "r"(a.z), "r"(a.w), "r"(db), "r"(0x40000040u), "n"(SCALE_D));
}

constexpr float LOG2E = 1.4426950408889634f;
__device__ __forceinline__ float silu_f(float y) { return y * rcp(1.f + ex2(-y * LOG2E)); }

__device__ __forceinline__ void mish_tile(const float* c, float rs0, float rs1, float rl0, float rl1, uint4* dst, uint32_t tag) {
  float h[8], u[8], r[8];
#pragma unroll
  for (int i = 0; i < 8; i++) {
    const bool hi = (i >> 1) & 1;
    h[i] = c[i] * (hi ? rs1 : rs0);
    u[i] = ex2(fminf(c[i] * (hi ? rl1 : rl0), 28.853900817779268f));
  }
#pragma unroll
  for (int i = 0; i < 8; i++) { const float tt = u[i] + 2.f; r[i] = rcp(fmaf(u[i], tt, 2.f)); h[i] *= u[i] * tt; }
#pragma unroll
  for (int i = 0; i < 8; i++) h[i] *= r[i];
  stg_frag(dst, pack2(h[0], h[1]), pack2(h[2], h[3]), pack2(h[4], h[5]), pack2(h[6], h[7]), tag);
}
__device__ __forceinline__ float phi_c(float c, float rs, float rl) {
  const float e = ex2(c * rl) + 1e-6f;
  const float p = fmaf(c, rs, 1.000001f);
  return c > 0.f ? p : e;
}
__device__ __forceinline__ uint4 phi_tile(const float* c, float rs0, float rs1, float rl0, float rl1) {
  uint4 r;
  r.x = pack2(phi_c(c[0], rs0, rl0), phi_c(c[1], rs0, rl0)); r.y = pack2(phi_c(c[2], rs1, rl1), phi_c(c[3], rs1, rl1));
  r.z = pack2(phi_c(c[4], rs0, rl0), phi_c(c[5], rs0, rl0)); r.w = pack2(phi_c(c[6], rs1, rl1), phi_c(c[7], rs1, rl1));
  return r;
}
template <int NB> __device__ __forceinline__ void init_bias(float* acc, uint32_t bias_addr, float ir0, float ir1) {
#pragma unroll
  for (int nb = 0; nb < NB; nb++) {
    const float2 b = lds_f32x2(bias_addr + 32 * nb);
    acc[4 * nb] = b.x * ir0; acc[4 * nb + 1] = b.y * ir0; acc[4 * nb + 2] = b.x * ir1; acc[4 * nb + 3] = b.y * ir1;
  }
}

__global__ void __launch_bounds__(384, 1)
fused_kernel(const __grid_constant__ CUtensorMap tm_x, const __grid_constant__ CUtensorMap tm_qkv,
             const __grid_constant__ CUtensorMap tm_w1, const __grid_constant__ CUtensorMap tm_w2a,
             const __grid_constant__ CUtensorMap tm_w2b, const __grid_constant__ CUtensorMap tm_wo,
             const __grid_constant__ CUtensorMap tm_out,
             const uint8_t* __restrict__ wqkv, const uint8_t* __restrict__ w1, const uint8_t* __restrict__ w2,
             const uint8_t* __restrict__ wo, const __nv_bfloat16* __restrict__ b1) {
  extern __shared__ __align__(1024) uint8_t smem_raw[];
  const uint32_t sb = smem_u32(smem_raw);
  const int tid = threadIdx.x, lane = tid & 31;
  const int warp = __shfl_sync(0xffffffffu, tid >> 5, 0);
  const int bid = blockIdx.x;
#define MAPV 0
  const int khalf = (bid >> 4) & 1, rb = (bid >> 5) * 4 + ((bid >> 2) & 3), nt = bid & 3;
  const int pbid = bid ^ 16;
  const int j = khalf + 2 * nt;
  const uint32_t bar0 = sb + OFF_BAR;
  PROF(0);

  if (warp >= 8) {
    asm volatile("setmaxnreg.dec.sync.aligned.u32 40;");
    if (warp == 8) {
      if (lane == 0) {
        if (sb & 1023u) asm volatile("trap;");
        for (int i = 0; i < NSLOT; i++) { mbar_init(bar0 + 8 * (BAR_FULL + i), 1); mbar_init(bar0 + 8 * (BAR_EMPTY + i), 8); }
        for (int i = BAR_X; i <= BAR_XT; i++) mbar_init(bar0 + 8 * i, 1);
        mbar_init(bar0 + 8 * BAR_PUB_KV, 8);
        mbar_init(bar0 + 8 * BAR_RDY_KV, 2);
        asm volatile("fence.mbarrier_init.release.cluster;" ::: "memory");
        fence_async_smem();
        for (int i = 0; i < 4; i++) {
          mbar_expect_tx(bar0 + 8 * (BAR_X + i), 32768);
          tma2d(sb + OFF_D + (2 * i) * 16384, &tm_x, 128 * i, rb * 128, bar0 + 8 * (BAR_X + i));
          tma2d(sb + OFF_D + (2 * i + 1) * 16384, &tm_x, 128 * i + 64, rb * 128, bar0 + 8 * (BAR_X + i));
        }
      }
      __syncwarp();
      named_bar_sync(0, 384);
      if (lane == 0) {
        const int c_own = 128 * nt + 64 * khalf, c_par = 128 * nt + 64 * (1 - khalf);
#pragma unroll 1
        for (int st = 0; st < NSTAGES; st++) {
          const int slot = slot_of(st), use = use_of(st);
          const uint32_t full = bar0 + 8 * (BAR_FULL + slot);
          const uint32_t dst = sb + slot_off(slot);
          mbar_wait(bar0 + 8 * (BAR_EMPTY + slot), (use & 1) ^ (slot < 5 ? 1 : 0));
          if (st < 8) {
            mbar_expect_tx(full, 16384);
            const int k0 = 64 * st, c0 = 224 * j;
            tma2d(dst, &tm_w1, c0, k0, full);
            tma2d(dst + 8192, &tm_w1, c0 + 64, k0, full);
          } else if (st < 24) {
            mbar_expect_tx(full, 12288);
            const int k0 = 32 * (st - 8);
            tma2d(dst, &tm_qkv, 512 + 64 * j, k0, full);
            tma2d(dst + 4096, &tm_qkv, 1024 + 64 * j, k0, full);
            tma2d(dst + 8192, &tm_qkv, 64 * j, k0, full);
          } else if (st < 32) {
            mbar_expect_tx(full, 16384);
            const int k0 = 64 * (st - 24), c0 = 224 * j + 128;
            tma2d(dst, &tm_w1, c0, k0, full);
            tma2d(dst + 8192, &tm_w1, c0 + 64, k0, full);
          } else if (st < 40) {
            mbar_expect_tx(full, 16384);
            const int i = st - 32;
            const int k0 = 224 * (4 * khalf + (i >> 1)) + 64 * (i & 1);
            tma2d(dst, &tm_w2a, c_own, k0, full);
            tma2d(dst + 8192, &tm_w2a, c_par, k0, full);
          } else if (st < 48) {
            if (st == 40) {
              mbar_wait(bar0 + 8 * BAR_PUB_KV, 0);
              mbar_expect_tx(bar0 + 8 * BAR_XT, 16384);
              tma2d(sb + OFF_XT, &tm_x, c_own, rb * 128, bar0 + 8 * BAR_XT);
            }
            mbar_expect_tx(full, 12288);
            const int i = st - 40;
            const int k0 = 224 * (4 * khalf + (i >> 1)) + 128 + 48 * (i & 1);
            tma2d(dst, &tm_w2b, c_own, k0, full);
            tma2d(dst + 6144, &tm_w2b, c_par, k0, full);
          } else {
            mbar_expect_tx(full, 8192);
            tma2d(dst, &tm_wo, c_own, 64 * (st - 48), full);
          }
        }
      }
    } else {
      const int aw = warp - 9;
      unsigned dn; asm volatile("ld.relaxed.gpu.global.u32 %0, [%1];" : "=r"(dn) : "l"(&g_done) : "memory");
      named_bar_sync(0, 384);
      const unsigned ep1 = dn / NCTA + 1u;
      if (aw == 0) {
        for (int i = lane; i < 224; i += 32) sts_f32(sb + OFF_B1 + 4 * i, __bfloat162float(b1[224 * j + i]));
#pragma unroll 4
        for (int i = 0; i < 16; i++) sts_v4(sb + OFF_ONES + (i * 32 + lane) * 16, 0x3F803F80u, 0x3F803F80u, 0x3F803F80u, 0x3F803F80u);
        fence_async_smem();
        __syncwarp();
        if (lane == 0) {
          mbar_arrive(bar0 + 8 * BAR_BIAS);
          mbar_wait(bar0 + 8 * BAR_PUB_KV, 0); PROF(3); fence_gpu(); red_inc(&g_cntKV[j * 8]); PROF(4);
        }
      } else {
        const int h0 = 2 * (aw - 1);
        if (aw == 1 && lane < 4) {
          const uint8_t* base = lane == 0 ? wqkv : lane == 1 ? w1 : lane == 2 ? w2 : wo;
          const uint32_t bytes = lane == 0 ? 12288u : lane == 3 ? 4096u : 14336u;
          asm volatile("cp.async.bulk.prefetch.L2.global [%0], %1;" ::"l"(base + (size_t)bid * bytes), "r"(bytes) : "memory");
        }
        if (rb == 0) {
          float4* z = reinterpret_cast<float4*>(&g_kv[ep1 & 1][(4 * j + h0) * 272]);
          for (int i = lane; i < 136; i += 32) z[i] = make_float4(0.f, 0.f, 0.f, 0.f);
        }
        const float* kvbuf = &g_kv[(ep1 & 1) ^ 1][(4 * j + h0) * 272];
        mbar_wait(bar0 + 8 * BAR_PUB_KV, 0);
        PROF(1);
        if (lane == 0) poll_ge(&g_cntKV[j * 8], 16u * ep1);
        __syncwarp();
        PROF(2);
        {
          const int d = lane >> 1, hf = lane & 1;
          const float* src = kvbuf + d * 16 + hf * 8;
          const uint32_t dst = sb + OFF_KVB + d * 128 + h0 * 2048;
          uint4 v[2][2]; float zz[2];
#pragma unroll
          for (int q = 0; q < 2; q++) {
            v[q][0] = ldg_cg(src + q * 272); v[q][1] = ldg_cg(src + q * 272 + 4);
            asm volatile("ld.global.cg.f32 %0, [%1];" : "=f"(zz[q]) : "l"(kvbuf + q * 272 + 256 + d) : "memory");
          }
#pragma unroll
          for (int q = 0; q < 2; q++) {
            const int hh = h0 + q;
            sts_v4(dst + q * 2048 + (((2 * hh + hf) ^ (d & 7)) << 4),
                   pack2(__uint_as_float(v[q][0].x), __uint_as_float(v[q][0].y)), pack2(__uint_as_float(v[q][0].z), __uint_as_float(v[q][0].w)),
                   pack2(__uint_as_float(v[q][1].x), __uint_as_float(v[q][1].y)), pack2(__uint_as_float(v[q][1].z), __uint_as_float(v[q][1].w)));
            const uint32_t z2 = pack2(zz[q], zz[q]);
            if (hf == 0) sts_v4(dst + 8192 + q * 2048 + ((hh ^ (d & 7)) << 4), z2, z2, z2, z2);
          }
        }
        fence_async_smem();
        __syncwarp();
        if (lane == 0) mbar_arrive(bar0 + 8 * BAR_RDY_KV);
        PROF(3);
      }
    }
  } else {
    asm volatile("setmaxnreg.inc.sync.aligned.u32 232;");
    const int wg = warp >> 2;
    const int g = lane >> 2, t = lane & 3;
    const int lr0 = warp * 16 + g;
    const int slab = rb * 8 + warp;
    unsigned dn; asm volatile("ld.relaxed.gpu.global.u32 %0, [%1];" : "=r"(dn) : "l"(&g_done) : "memory");
    const uint32_t a_lo = dlo(sb + OFF_D + wg * 8192, 16);
    const uint32_t sb_lo = sb >> 4;

#define B_LO(gs, off, lbo) (sb_lo + ((slot_off(slot_of(gs)) + (off)) >> 4) + (((lbo) >> 4) << 16))
#define WAIT_FULL(gs) do { if ((gs) < NSTAGES) mbar_wait(bar0 + 8 * (BAR_FULL + slot_of((gs) < NSTAGES ? (gs) : 0)), use_of((gs) < NSTAGES ? (gs) : 0) & 1); } while (0)
#define RELEASE_SLOT(sl) do { if (lane == 0) mbar_arrive(bar0 + 8 * (BAR_EMPTY + (sl))); } while (0)
#define RELEASE_STAGE(gs) do { if ((gs) >= 0 && (gs) < 46) RELEASE_SLOT(slot_of((gs) < 0 ? 0 : (gs))); } while (0)
#define WARP_ARRIVE(b) do { __syncwarp(); if (lane == 0) mbar_arrive(bar0 + 8 * (b)); } while (0)

    uint4* act_out = g_act + (size_t)(slab * 112 + 14 * j) * 32 + lane;
    const uint32_t bias_addr = sb + OFF_B1 + 8 * t;
    float rs0, rs1;
    float pool[160];
    float (&acca)[64] = reinterpret_cast<float (&)[64]>(pool[0]);
    float (&accq)[96] = reinterpret_cast<float (&)[96]>(pool[64]);
    float (&accb)[48] = reinterpret_cast<float (&)[48]>(pool[0]);
    float (&accy)[64] = reinterpret_cast<float (&)[64]>(pool[64]);
    float (&accs)[32] = reinterpret_cast<float (&)[32]>(pool[0]);
    float rl0, rl1, ir0, ir1;
    const unsigned ep1 = dn / NCTA + 1u;
    const uint32_t tag = ep1 & 1u;
    {
      uint4 q[16], p[16];
      const int par = g & 1;
      const uint32_t rowa = sb + OFF_D + lr0 * 128;
      const uint32_t u0 = (uint32_t)(((par * 4 + t) ^ g) << 4), u1 = u0 ^ 64u;
      named_bar_sync(0, 384);
      float sm[2][4], ga[2][4], gb[2][4];
#pragma unroll
      for (int a = 0; a < 2; a++) {
        sm[a][0] = sm[a][1] = sm[a][2] = sm[a][3] = 0.f;
        ga[a][0] = ga[a][1] = ga[a][2] = ga[a][3] = 0.f;
        gb[a][0] = gb[a][1] = gb[a][2] = gb[a][3] = 0.f;
      }
      const uint32_t ones = 0x3F803F80u;
#pragma unroll
      for (int c = 0; c < 8; c++) {
        if ((c & 1) == 0) mbar_wait(bar0 + 8 * (BAR_X + (c >> 1)), 0);
        q[2 * c] = lds_v4(rowa + c * 16384 + u0);     p[2 * c] = lds_v4(rowa + c * 16384 + 1024 + u0);
        q[2 * c + 1] = lds_v4(rowa + c * 16384 + u1); p[2 * c + 1] = lds_v4(rowa + c * 16384 + 1024 + u1);
#pragma unroll
        for (int h = 0; h < 2; h++) {
          const int i = 2 * c + h;
          mma16816(sm[0], q[i].x, p[i].x, q[i].y, p[i].y, ones, ones);
          mma16816(sm[1], q[i].z, p[i].z, q[i].w, p[i].w, ones, ones);
          mma16816(ga[0], q[i].x, p[i].x, q[i].y, p[i].y, q[i].x, q[i].y);
          mma16816(ga[1], q[i].z, p[i].z, q[i].w, p[i].w, q[i].z, q[i].w);
          mma16816(gb[0], q[i].x, p[i].x, q[i].y, p[i].y, p[i].x, p[i].y);
          mma16816(gb[1], q[i].z, p[i].z, q[i].w, p[i].w, p[i].z, p[i].w);
        }
      }
      const float m0 = (sm[0][0] + sm[1][0]) * (1.f / DM);
      const float m1 = (sm[0][2] + sm[1][2]) * (1.f / DM);
      const uint32_t mb0 = pack2(m0, m0), mb1 = pack2(m1, m1);
      PROF(12);
#pragma unroll
      for (int i = 0; i < 16; i++) {
        const uint32_t off = (uint32_t)(i >> 1) * 16384 + ((i & 1) ? u1 : u0);
        sts_v4(rowa + off, hsub2_bf16(q[i].x, mb0), hsub2_bf16(q[i].y, mb0), hsub2_bf16(q[i].z, mb0), hsub2_bf16(q[i].w, mb0));
        sts_v4(rowa + 1024 + off, hsub2_bf16(p[i].x, mb1), hsub2_bf16(p[i].y, mb1), hsub2_bf16(p[i].z, mb1), hsub2_bf16(p[i].w, mb1));
      }
      fence_async_smem();
      float d0 = par ? ga[0][1] + ga[1][1] : ga[0][0] + ga[1][0];
      float d1 = par ? gb[0][3] + gb[1][3] : gb[0][2] + gb[1][2];
      d0 = __shfl_sync(0xffffffffu, d0, (lane & ~3) | (g >> 1));
      d1 = __shfl_sync(0xffffffffu, d1, (lane & ~3) | (g >> 1));
      const float v0 = fmaxf(d0 * (1.f / DM) - m0 * m0, 0.f) + 1e-5f;
      const float v1 = fmaxf(d1 * (1.f / DM) - m1 * m1, 0.f) + 1e-5f;
      rs0 = rsqrtf(v0); rs1 = rsqrtf(v1);
      ir0 = v0 * rs0; ir1 = v1 * rs1;
      rl0 = rs0 * LOG2E; rl1 = rs1 * LOG2E;
      mbar_wait(bar0 + 8 * BAR_BIAS, 0);
      init_bias<16>(acca, bias_addr, ir0, ir1);
      named_bar_sync(1 + wg, 128);
      PROF(1);
    }
    const uint4* act_in = g_act + (size_t)(slab * 112 + 56 * khalf) * 32 + lane;
    const uint4* o_in = g_o + (size_t)(slab * 32) * 32 + lane;
    uint4 ab[4][4];
    auto a_ptr = [&](int rs, int kk) -> const uint4* {
      if (rs < 8) return act_in + (14 * (rs >> 1) + 4 * (rs & 1) + kk) * 32;
      if (rs < 16) return act_in + (14 * ((rs - 8) >> 1) + 8 + 3 * (rs & 1) + kk) * 32;
      return o_in + (4 * (rs - 16) + kk) * 32;
    };
    auto load_a = [&](int rs) {
      if (rs < 24) {
#pragma unroll
        for (int kk = 0; kk < 4; kk++) if (!(rs >= 8 && rs < 16 && kk == 3)) ab[rs & 3][kk] = ldg_frag(a_ptr(rs, kk));
      }
    };
    auto check_a = [&](int rs) {
      if (rs >= 24) return;
      if (rs >= 8 && rs < 16) validate3(ab[rs & 3], a_ptr(rs, 0), tag);
      else validate4(ab[rs & 3], a_ptr(rs, 0), tag);
    };
    auto keep_a = [&](int rs) {
      if (rs < 0) return;
#pragma unroll
      for (int kk = 0; kk < 4; kk++) if (!(rs >= 8 && rs < 16 && kk == 3)) fence_u4(ab[rs & 3][kk]);
    };
    WAIT_FULL(0);
#pragma unroll
    for (int st = 0; st < 8; st++) {
      wg_fence();
#pragma unroll
      for (int kk = 0; kk < 4; kk++) wgmma_ss_n128<1>(acca, a_lo + ((st * 16384 + kk * 32) >> 4), B_LO(st, kk * 2048, 8192));
      wg_commit();
      RELEASE_STAGE(st - 2);
      if (st == 0) zero_regs(accq);
      WAIT_FULL(st + 1);
      wg_wait<1>();
    }
    PROF(2);
#pragma unroll
    for (int st = 0; st < 16; st++) {
      const int gs = 8 + st;
      const uint32_t as = a_lo + (((st >> 1) * 16384 + (st & 1) * 64) >> 4);
      wg_fence();
      wgmma_ss_n192<1>(accq, as, B_LO(gs, 0, 4096));
      wgmma_ss_n192<1>(accq, as + 2, B_LO(gs, 2048, 4096));
      wg_commit();
      RELEASE_STAGE(gs - 2);
      if (st == 1) fence_regs(acca);
      if (st >= 1 && st < 9) mish_tile(acca + 8 * (st - 1), rs0, rs1, rl0, rl1, act_out + (st - 1) * 32, tag);
      if (st == 9) init_bias<12>(accb, bias_addr + 512, ir0, ir1);
      WAIT_FULL(gs + 1);
      wg_wait<1>();
      if (st == 8) PROF(3);
    }
    PROF(4);
    uint4 pq[4];
    {
      const int m = lane >> 3, rr = lane & 7;
      const uint32_t srow = sb + OFF_D + (warp * 16 + (m & 1) * 8 + rr) * 128;
      const uint32_t ka = dlo(sb + OFF_PK + wg * 8192, 16);
      const uint32_t vb = dlo(sb + OFF_V + wg * 8192, OFF_ONES - (OFF_V + wg * 8192));
      float (&acck)[36] = reinterpret_cast<float (&)[36]>(pool[64]);
#pragma unroll
      for (int st = 0; st < 8; st++) {
        const int gs = 24 + st;
        wg_fence();
#pragma unroll
        for (int kk = 0; kk < 4; kk++) wgmma_ss_n96<1>(accb, a_lo + ((st * 16384 + kk * 32) >> 4), B_LO(gs, kk * 2048, 8192));
        if (st == 4) {
          wgmma_tt_n72<0>(acck, ka, vb);
#pragma unroll
          for (int kk = 1; kk < 4; kk++) wgmma_tt_n72<1>(acck, ka + kk * 128, vb + kk * 128);
        }
        wg_commit();
        RELEASE_STAGE(gs - 2);
        if (st >= 5) RELEASE_SLOT(5 + (st - 2) - 3);
        if (st == 1) {
          fence_regs(accq);
          pq[0] = phi_tile(accq + 64, rs0, rs1, rl0, rl1); pq[1] = phi_tile(accq + 72, rs0, rs1, rl0, rl1);
          pq[2] = phi_tile(accq + 80, rs0, rs1, rl0, rl1); pq[3] = phi_tile(accq + 88, rs0, rs1, rl0, rl1);
        } else if (st == 2) {
#pragma unroll
          for (int i = 0; i < 4; i++) {
            const uint4 r = phi_tile(accq + 8 * i, rs0, rs1, rl0, rl1);
            stmatrix_x4(srow + OFF_PK + (((2 * i + (m >> 1)) ^ rr) << 4), r.x, r.y, r.z, r.w);
          }
        } else if (st == 3) {
#pragma unroll
          for (int i = 0; i < 4; i++) {
            const float* c = accq + 32 + 8 * i;
            stmatrix_x4(srow + OFF_V + (((2 * i + (m >> 1)) ^ rr) << 4),
                        pack2(c[0] * rs0, c[1] * rs0), pack2(c[2] * rs1, c[3] * rs1), pack2(c[4] * rs0, c[5] * rs0), pack2(c[6] * rs1, c[7] * rs1));
          }
          fence_async_smem();
          named_bar_sync(1 + wg, 128);
        } else if (st == 5) {
          load_a(0); load_a(1); load_a(2);
        } else if (st == 6) {
          fence_regs(acck);
          const int wq = warp & 3;
          float* hb = &g_kv[(ep1 & 1) ^ 1][(4 * j + wq) * 272];
          float* a0p = hb + g * 16 + 2 * t;
#pragma unroll
          for (int w = 0; w < 4; w++) {
            if (wq == w) {
              red_add_v2(a0p, acck[8 * w], acck[8 * w + 1]); red_add_v2(a0p + 128, acck[8 * w + 2], acck[8 * w + 3]);
              red_add_v2(a0p + 8, acck[8 * w + 4], acck[8 * w + 5]); red_add_v2(a0p + 136, acck[8 * w + 6], acck[8 * w + 7]);
            }
          }
          if (t == 0) { red_add_f32(hb + 256 + g, acck[32]); red_add_f32(hb + 264 + g, acck[34]); }
#pragma unroll
          for (int i = 0; i < 4; i++) sts_v4(sb + OFF_KVB + warp * 2048 + i * 512 + lane * 16, 0u, 0u, 0u, 0u);
          WARP_ARRIVE(BAR_PUB_KV);
        }
        if (st == 7) check_a(0);
        WAIT_FULL(gs + 1);
        wg_wait<1>();
      }
    }
    PROF(5);
#pragma unroll
    for (int rs = 0; rs < 24; rs++) {
      const int gs = 32 + rs;
      if (rs == O_STAGE) mbar_wait(bar0 + 8 * BAR_RDY_KV, 0);
      wg_fence();
      if (rs < 8) {
#pragma unroll
        for (int kk = 0; kk < 4; kk++) {
          if (rs == 0 && kk == 0) wgmma_rs_n128<0>(accy, ab[rs & 3][kk], B_LO(gs, kk * 2048, 8192));
          else wgmma_rs_n128<1>(accy, ab[rs & 3][kk], B_LO(gs, kk * 2048, 8192));
        }
      } else if (rs < 16) {
#pragma unroll
        for (int kk = 0; kk < 3; kk++) wgmma_rs_n128<1>(accy, ab[rs & 3][kk], B_LO(gs, kk * 2048, 6144));
      } else {
#pragma unroll
        for (int kk = 0; kk < 4; kk++) {
          if (rs == 16 && kk == 0) wgmma_rs_n64<0>(accs, ab[rs & 3][kk], B_LO(gs, kk * 2048, 8192));
          else wgmma_rs_n64<1>(accs, ab[rs & 3][kk], B_LO(gs, kk * 2048, 8192));
        }
      }
      if (rs == O_STAGE) {
        const uint32_t kb = dlo(sb + OFF_KVB, 8192);
        wgmma_rs_n96<0>(accb, pq[0], kb);
#pragma unroll
        for (int kk = 1; kk < 4; kk++) wgmma_rs_n96<1>(accb, pq[kk], kb + kk * 128);
      }
      wg_commit();
      RELEASE_STAGE(gs - 2);
      if (rs < 2) RELEASE_SLOT(8 + rs);
      if (rs == 1) fence_regs(accb);
      if (rs == 1 || rs == 2) {
#pragma unroll
        for (int i = 3 * (rs - 1); i < 3 * (rs - 1) + 3; i++)
          mish_tile(accb + 8 * i, rs0, rs1, rl0, rl1, act_out + (8 + i) * 32, tag);
      }
      if (rs == O_STAGE + 2) {
        fence_regs(accb);
#pragma unroll
        for (int kk = 0; kk < 4; kk++) fence_u4(pq[kk]);
        uint4* o_out = g_o + (size_t)(slab * 32 + 4 * j) * 32 + lane;
#pragma unroll
        for (int hh = 0; hh < 4; hh++) {
          const float i0 = __fdividef(1.f, accb[32 + 4 * hh] + 1e-6f), i1 = __fdividef(1.f, accb[34 + 4 * hh] + 1e-6f);
          const float* n = accb + 8 * hh;
          stg_frag(o_out + hh * 32, pack2(n[0] * i0, n[1] * i0), pack2(n[2] * i1, n[3] * i1), pack2(n[4] * i0, n[5] * i0), pack2(n[6] * i1, n[7] * i1), tag);
        }
      }
      if (rs == 17) {
        fence_regs(accy);
        float4* yp = g_yp + (size_t)((bid * 8 + warp) * 8) * 32 + lane;
#pragma unroll
        for (int q = 0; q < 8; q++) {
          const uint32_t v0 = (__float_as_uint(accy[32 + 4 * q]) & ~1u) | tag, v1 = (__float_as_uint(accy[33 + 4 * q]) & ~1u) | tag;
          const uint32_t v2 = (__float_as_uint(accy[34 + 4 * q]) & ~1u) | tag, v3 = (__float_as_uint(accy[35 + 4 * q]) & ~1u) | tag;
          asm volatile("st.relaxed.gpu.global.v4.u32 [%0], {%1,%2,%3,%4};" ::"l"(yp + q * 32), "r"(v0), "r"(v1), "r"(v2), "r"(v3) : "memory");
        }
      }
      check_a(rs + 1);
      WAIT_FULL(gs + 1);
      wg_wait<1>();
      keep_a(rs - 1);
      load_a(rs + 3);
      if (rs == 7) PROF(6);
      if (rs == 15) PROF(8);
    }
    PROF(9);
    {
      const float4* yp = g_yp + (size_t)((pbid * 8 + warp) * 8) * 32 + lane;
      uint4 pv[8];
      uint32_t it = 0;
      wg_wait<0>();
      keep_a(23);
      fence_regs(accs);
      while (true) {
        uint32_t bad = 0;
#pragma unroll
        for (int q = 0; q < 8; q++)
          asm volatile("ld.relaxed.gpu.global.v4.u32 {%0,%1,%2,%3}, [%4];" : "=r"(pv[q].x), "=r"(pv[q].y), "=r"(pv[q].z), "=r"(pv[q].w) : "l"(yp + q * 32) : "memory");
#pragma unroll
        for (int q = 0; q < 8; q++) bad |= (pv[q].x ^ tag) | (pv[q].y ^ tag) | (pv[q].z ^ tag) | (pv[q].w ^ tag);
        if (!__any_sync(0xffffffffu, bad & 1u)) break;
        if (++it > (1u << 20)) asm volatile("trap;");
      }
      PROF(10);
      mbar_wait(bar0 + 8 * BAR_XT, 0);
      const uint32_t xa = sb + OFF_XT + lr0 * 128 + 4 * t;
#pragma unroll
      for (int q = 0; q < 8; q++) {
        const uint32_t a0 = xa + ((q ^ g) << 4), a1 = a0 + 1024;
        const uint32_t x0 = lds_u32(a0), x1 = lds_u32(a1);
        const float y0 = accy[4 * q] + __uint_as_float(pv[q].x), y1 = accy[4 * q + 1] + __uint_as_float(pv[q].y);
        const float y2 = accy[4 * q + 2] + __uint_as_float(pv[q].z), y3 = accy[4 * q + 3] + __uint_as_float(pv[q].w);
        const float o0 = fmaf(accs[4 * q], silu_f(y0), bf_lo(x0)), o1 = fmaf(accs[4 * q + 1], silu_f(y1), bf_hi(x0));
        const float o2 = fmaf(accs[4 * q + 2], silu_f(y2), bf_lo(x1)), o3 = fmaf(accs[4 * q + 3], silu_f(y3), bf_hi(x1));
        sts_u32(a0, pack2(o0, o1));
        sts_u32(a1, pack2(o2, o3));
      }
      fence_async_smem();
      __syncwarp();
      if (lane == 0) {
        asm volatile("cp.async.bulk.tensor.2d.global.shared::cta.bulk_group [%0, {%2, %3}], [%1];"
                     ::"l"(&tm_out), "r"(sb + OFF_XT + warp * 2048), "r"(128 * nt + 64 * khalf), "r"(rb * 128 + warp * 16) : "memory");
        asm volatile("cp.async.bulk.commit_group;" ::: "memory");
        asm volatile("cp.async.bulk.wait_group.read 0;" ::: "memory");
      }
    }
    PROF(11);
    if (tid == 0) red_inc(&g_done);
  }
}

typedef CUresult (*EncodeFn)(CUtensorMap*, CUtensorMapDataType, cuuint32_t, void*, const cuuint64_t*, const cuuint64_t*,
                             const cuuint32_t*, const cuuint32_t*, CUtensorMapInterleave, CUtensorMapSwizzle,
                             CUtensorMapL2promotion, CUtensorMapFloatOOBfill);

void make_map(EncodeFn enc, CUtensorMap* tm, const void* ptr, int rows, int cols, int box_rows) {
  cuuint64_t gd[2] = {(cuuint64_t)cols, (cuuint64_t)rows};
  cuuint64_t gs[1] = {(cuuint64_t)cols * 2};
  cuuint32_t bd[2] = {64, (cuuint32_t)box_rows};
  cuuint32_t es[2] = {1, 1};
  enc(tm, CU_TENSOR_MAP_DATA_TYPE_BFLOAT16, 2, const_cast<void*>(ptr), gd, gs, bd, es, CU_TENSOR_MAP_INTERLEAVE_NONE,
      CU_TENSOR_MAP_SWIZZLE_128B, CU_TENSOR_MAP_L2_PROMOTION_L2_128B, CU_TENSOR_MAP_FLOAT_OOB_FILL_NONE);
}

}

extern "C" void kernel_launch(void* const* d_in, const int* in_sizes, int n_in, void* d_out, int out_size) {
  const __nv_bfloat16* x = (const __nv_bfloat16*)d_in[0];
  const void* wqkv = d_in[1];
  const void* wo = d_in[2];
  const void* w1 = d_in[4];
  const __nv_bfloat16* b1 = (const __nv_bfloat16*)d_in[5];
  const void* w2 = d_in[6];
  static EncodeFn enc = nullptr;
  if (!enc) {
    cudaDriverEntryPointQueryResult qr;
    void* fn = nullptr;
    cudaGetDriverEntryPoint("cuTensorMapEncodeTiled", &fn, cudaEnableDefault, &qr);
    enc = (EncodeFn)fn;
    cudaFuncSetAttribute(fused_kernel, cudaFuncAttributeMaxDynamicSharedMemorySize, SMEM_ALLOC);
  }
  CUtensorMap tx, tq, t1, t2a, t2b, to, tout;
  make_map(enc, &tx, x, 2048, DM, 128);
  make_map(enc, &tq, wqkv, DM, 3 * DM, 32);
  make_map(enc, &t1, w1, DM, FF, 64);
  make_map(enc, &t2a, w2, FF, DM, 64);
  make_map(enc, &t2b, w2, FF, DM, 48);
  make_map(enc, &to, wo, DM, DM, 64);
  make_map(enc, &tout, d_out, 2048, DM, 16);
  fused_kernel<<<NCTA, 384, SMEM_ALLOC>>>(tx, tq, t1, t2a, t2b, to, tout, (const uint8_t*)wqkv, (const uint8_t*)w1,
                                          (const uint8_t*)w2, (const uint8_t*)wo, b1);
}
```

```cpp
#include <cuda_runtime.h>
#include <cuda_bf16.h>
#include <cuda.h>
#include <stdint.h>

namespace {

constexpr int DM = 512, FF = 1792;
constexpr int NCTA = 128;
constexpr int NRING = 6;
constexpr int NSLOT = 12;
constexpr int SLOT_BYTES = 16384;
constexpr uint32_t SMEM_BASE = 1024;
constexpr int OFF_D = 0;
constexpr int OFF_PK = 0, OFF_V = 16384;
constexpr int OFF_KVB = 0;
constexpr int OFF_XT = 16384;
constexpr int OFF_RING = 131072;
constexpr int OFF_ONES = 32768;
constexpr int OFF_MISC = OFF_RING + NRING * SLOT_BYTES;
constexpr int OFF_BAR = OFF_MISC;
constexpr int OFF_B1 = OFF_MISC + 512;
constexpr int SMEM_ALLOC = OFF_MISC + 1536;

enum { BAR_FULL = 0, BAR_EMPTY = NSLOT, BAR_X = 2 * NSLOT, BAR_BIAS = BAR_X + 4, BAR_XT,
       BAR_PUB_KV, BAR_RDY_KV, BAR_END, BAR_OWN_B, BAR_OWN_O, BAR_KVP, BAR_KVF, BAR_COUNT };
static_assert(BAR_COUNT <= 40, "too many barriers");

constexpr int NSTAGES = 56;
constexpr int LDG_FROM = 16;
__host__ __device__ constexpr bool a_direct(int rs) { return rs >= LDG_FROM && rs < 24 && (rs & 1); }
constexpr int O_STAGE = 7;
__host__ __device__ constexpr int slot_of(int gs) {
  constexpr int t[6] = {7, 8, 9, 10, 6, 11};
  return gs < 32 ? gs % 6 : t[(gs - 32) % 6];
}
__host__ __device__ constexpr int slot2_of(int gs) { return ((gs - 32) % 6 + 2) % 6; }
__host__ __device__ constexpr int use_of(int gs) { return gs < 32 ? gs / 6 : (gs - 32) / 6; }
__host__ __device__ constexpr int slot_off(int sl) { return sl < 6 ? OFF_RING + sl * SLOT_BYTES : OFF_D + (sl - 4) * SLOT_BYTES; }

__device__ uint4 g_act[16 * 112 * 8 * 32];
__device__ uint4 g_o[16 * 32 * 8 * 32];
__device__ float4 g_yp[NCTA * 8 * 8 * 32];
__device__ float4 g_kv[2][8 * 272];
__device__ unsigned g_cntKV[8 * 8];
__device__ unsigned g_done;


__device__ __forceinline__ uint32_t smem_u32(const void* p) { return (uint32_t)__cvta_generic_to_shared(p); }
__device__ __forceinline__ void mbar_init(uint32_t bar, uint32_t cnt) { asm volatile("mbarrier.init.shared::cta.b64 [%0], %1;" ::"r"(bar), "r"(cnt)); }
__device__ __forceinline__ void mbar_expect_tx(uint32_t bar, uint32_t bytes) { asm volatile("mbarrier.arrive.expect_tx.shared::cta.b64 _, [%0], %1;" ::"r"(bar), "r"(bytes) : "memory"); }
__device__ __forceinline__ void mbar_arrive(uint32_t bar) { asm volatile("mbarrier.arrive.shared::cta.b64 _, [%0];" ::"r"(bar) : "memory"); }
__device__ __forceinline__ void mbar_wait(uint32_t bar, uint32_t parity) {
  asm volatile("{\n.reg .pred P1;\n"
               "LAB_WAIT:\n"
               "mbarrier.try_wait.parity.shared::cta.b64 P1, [%0], %1;\n@!P1 bra LAB_WAIT;\n}" ::"r"(bar), "r"(parity) : "memory");
}
__device__ __forceinline__ bool mbar_try(uint32_t bar, uint32_t parity) {
  uint32_t done;
  asm volatile("{\n.reg .pred p;\nmbarrier.try_wait.parity.shared::cta.b64 p, [%1], %2;\nselp.u32 %0, 1, 0, p;\n}" : "=r"(done) : "r"(bar), "r"(parity) : "memory");
  return done != 0;
}
__device__ __forceinline__ void tma2d(uint32_t dst, const CUtensorMap* tm, int c0, int c1, uint32_t bar) {
  asm volatile("cp.async.bulk.tensor.2d.shared::cluster.global.mbarrier::complete_tx::bytes [%0], [%1, {%3, %4}], [%2];" ::"r"(dst), "l"(tm), "r"(bar), "r"(c0), "r"(c1) : "memory");
}
__device__ __forceinline__ void bulk_g2s(uint32_t dst, const void* src, uint32_t bytes, uint32_t bar) {
  asm volatile("cp.async.bulk.shared::cluster.global.mbarrier::complete_tx::bytes [%0], [%1], %2, [%3];" ::"r"(dst), "l"(src), "r"(bytes), "r"(bar) : "memory");
}
__device__ __forceinline__ void wg_fence() { asm volatile("wgmma.fence.sync.aligned;" ::: "memory"); }
__device__ __forceinline__ void wg_commit() { asm volatile("wgmma.commit_group.sync.aligned;" ::: "memory"); }
template <int N> __device__ __forceinline__ void wg_wait() { asm volatile("wgmma.wait_group.sync.aligned %0;" ::"n"(N) : "memory"); }
template <int N> __device__ __forceinline__ void zero_regs(float (&d)[N]) {
#pragma unroll
  for (int i = 0; i < N; i++) d[i] = 0.f;
}
template <int N> __device__ __forceinline__ void fence_regs(float (&d)[N]) {
#pragma unroll
  for (int i = 0; i < N; i++) asm volatile("" : "+f"(d[i])::"memory");
}
__device__ __forceinline__ void fence_u4(uint4& v) { asm volatile("" : "+r"(v.x), "+r"(v.y), "+r"(v.z), "+r"(v.w)::"memory"); }
__device__ __forceinline__ void named_bar_sync(int id, int n) { asm volatile("bar.sync %0, %1;" ::"r"(id), "r"(n) : "memory"); }
__device__ __forceinline__ void fence_async_smem() { asm volatile("fence.proxy.async.shared::cta;" ::: "memory"); }
__device__ __forceinline__ constexpr uint32_t dlo(uint32_t addr, uint32_t lbo_bytes) { return ((addr & 0x3FFFFu) >> 4) | ((lbo_bytes >> 4) << 16); }
__device__ __forceinline__ void mma16816(float (&c)[4], uint32_t a0, uint32_t a1, uint32_t a2, uint32_t a3, uint32_t b0, uint32_t b1) {
  asm volatile("mma.sync.aligned.m16n8k16.row.col.f32.bf16.bf16.f32 {%0,%1,%2,%3}, {%4,%5,%6,%7}, {%8,%9}, {%0,%1,%2,%3};"
               : "+f"(c[0]), "+f"(c[1]), "+f"(c[2]), "+f"(c[3]) : "r"(a0), "r"(a1), "r"(a2), "r"(a3), "r"(b0), "r"(b1));
}
__device__ __forceinline__ void stmatrix_x4(uint32_t addr, uint32_t a, uint32_t b, uint32_t c, uint32_t d) {
  asm volatile("stmatrix.sync.aligned.m8n8.x4.shared.b16 [%0], {%1,%2,%3,%4};" ::"r"(addr), "r"(a), "r"(b), "r"(c), "r"(d) : "memory");
}
__device__ __forceinline__ uint32_t pack2(float lo, float hi) { uint32_t r; asm("cvt.rn.bf16x2.f32 %0, %1, %2;" : "=r"(r) : "f"(hi), "f"(lo)); return r; }
__device__ __forceinline__ float ex2(float x) { float r; asm("ex2.approx.ftz.f32 %0, %1;" : "=f"(r) : "f"(x)); return r; }
__device__ __forceinline__ float rcp(float x) { float r; asm("rcp.approx.ftz.f32 %0, %1;" : "=f"(r) : "f"(x)); return r; }
__device__ __forceinline__ float bf_lo(uint32_t v) { return __uint_as_float(v << 16); }
__device__ __forceinline__ float bf_hi(uint32_t v) { return __uint_as_float(v & 0xffff0000u); }
__device__ __forceinline__ uint32_t hsub2_bf16(uint32_t a, uint32_t b) {
  __nv_bfloat162 x = *reinterpret_cast<__nv_bfloat162*>(&a), y = *reinterpret_cast<__nv_bfloat162*>(&b);
  __nv_bfloat162 r = __hsub2(x, y);
  return *reinterpret_cast<uint32_t*>(&r);
}
__device__ __forceinline__ void stg_frag(void* p, uint32_t a, uint32_t b, uint32_t c, uint32_t d, uint32_t tag) {
  asm volatile("st.relaxed.gpu.global.v4.u32 [%0], {%1,%2,%3,%4};" ::"l"(p), "r"((a & ~1u) | tag), "r"(b), "r"(c), "r"(d) : "memory");
}
__device__ __forceinline__ void validate4(uint4 (&v)[4], const void* p, uint32_t tag4) {
  asm volatile("{\n.reg .pred P1;\n.reg .u32 tc, tb;\n"
               "lop3.b32 tb, %0, %4, %17, 0x7E;\nlop3.b32 tc, %8, %12, %17, 0x7E;\nor.b32 tb, tb, tc;\nand.b32 tb, tb, 1;\nsetp.eq.u32 P1, tb, 0;\n@P1 bra DONE;\n"
               "LAB_RETRY:\n"
               "ld.relaxed.gpu.global.v4.u32 {%0,%1,%2,%3}, [%16];\n"
               "ld.relaxed.gpu.global.v4.u32 {%4,%5,%6,%7}, [%16+4096];\n"
               "ld.relaxed.gpu.global.v4.u32 {%8,%9,%10,%11}, [%16+8192];\n"
               "ld.relaxed.gpu.global.v4.u32 {%12,%13,%14,%15}, [%16+12288];\n"
               "lop3.b32 tb, %0, %4, %17, 0x7E;\nlop3.b32 tc, %8, %12, %17, 0x7E;\nor.b32 tb, tb, tc;\nand.b32 tb, tb, 1;\nsetp.eq.u32 P1, tb, 0;\n@P1 bra DONE;\n"
               "bra LAB_RETRY;\n"
               "DONE:\n}"
               : "+r"(v[0].x), "+r"(v[0].y), "+r"(v[0].z), "+r"(v[0].w), "+r"(v[1].x), "+r"(v[1].y), "+r"(v[1].z), "+r"(v[1].w),
                 "+r"(v[2].x), "+r"(v[2].y), "+r"(v[2].z), "+r"(v[2].w), "+r"(v[3].x), "+r"(v[3].y), "+r"(v[3].z), "+r"(v[3].w)
               : "l"(p), "r"(tag4) : "memory");
}
__device__ __forceinline__ void validate3(uint4 (&v)[4], const void* p, uint32_t tag4) {
  asm volatile("{\n.reg .pred P1;\n.reg .u32 tc, tb;\n"
               "lop3.b32 tb, %0, %4, %13, 0x7E;\nxor.b32 tc, %8, %13;\nor.b32 tb, tb, tc;\nand.b32 tb, tb, 1;\nsetp.eq.u32 P1, tb, 0;\n@P1 bra DONE;\n"
               "LAB_RETRY:\n"
               "ld.relaxed.gpu.global.v4.u32 {%0,%1,%2,%3}, [%12];\n"
               "ld.relaxed.gpu.global.v4.u32 {%4,%5,%6,%7}, [%12+4096];\n"
               "ld.relaxed.gpu.global.v4.u32 {%8,%9,%10,%11}, [%12+8192];\n"
               "lop3.b32 tb, %0, %4, %13, 0x7E;\nxor.b32 tc, %8, %13;\nor.b32 tb, tb, tc;\nand.b32 tb, tb, 1;\nsetp.eq.u32 P1, tb, 0;\n@P1 bra DONE;\n"
               "bra LAB_RETRY;\n"
               "DONE:\n}"
               : "+r"(v[0].x), "+r"(v[0].y), "+r"(v[0].z), "+r"(v[0].w), "+r"(v[1].x), "+r"(v[1].y), "+r"(v[1].z), "+r"(v[1].w),
                 "+r"(v[2].x), "+r"(v[2].y), "+r"(v[2].z), "+r"(v[2].w)
               : "l"(p), "r"(tag4) : "memory");
}
__device__ __forceinline__ void sts_v4(uint32_t addr, uint32_t a, uint32_t b, uint32_t c, uint32_t d) {
  asm volatile("st.shared.v4.u32 [%0], {%1,%2,%3,%4};" ::"r"(addr), "r"(a), "r"(b), "r"(c), "r"(d) : "memory");
}
__device__ __forceinline__ void sts_f32(uint32_t addr, float v) { asm volatile("st.shared.f32 [%0], %1;" ::"r"(addr), "f"(v) : "memory"); }
__device__ __forceinline__ void sts_f32x2(uint32_t addr, float a, float b) { asm volatile("st.shared.v2.f32 [%0], {%1,%2};" ::"r"(addr), "f"(a), "f"(b) : "memory"); }
__device__ __forceinline__ uint4 lds_v4(uint32_t addr) { uint4 v; asm volatile("ld.shared.v4.u32 {%0,%1,%2,%3}, [%4];" : "=r"(v.x), "=r"(v.y), "=r"(v.z), "=r"(v.w) : "r"(addr) : "memory"); return v; }
__device__ __forceinline__ uint32_t lds_u32(uint32_t addr) { uint32_t v; asm volatile("ld.shared.u32 %0, [%1];" : "=r"(v) : "r"(addr) : "memory"); return v; }
__device__ __forceinline__ void sts_u32(uint32_t addr, uint32_t v) { asm volatile("st.shared.u32 [%0], %1;" ::"r"(addr), "r"(v) : "memory"); }
__device__ __forceinline__ float2 lds_f32x2(uint32_t addr) { float2 v; asm volatile("ld.shared.v2.f32 {%0,%1}, [%2];" : "=f"(v.x), "=f"(v.y) : "r"(addr) : "memory"); return v; }
__device__ __forceinline__ void red_inc(unsigned* cnt) { asm volatile("red.relaxed.gpu.global.add.u32 [%0], 1;" ::"l"(cnt) : "memory"); }
__device__ __forceinline__ float atom_add4(float4* p, float a, float b, float c, float d) {
  float r0, r1, r2, r3;
  asm volatile("atom.relaxed.gpu.global.add.v4.f32 {%0,%1,%2,%3}, [%4], {%5,%6,%7,%8};" : "=f"(r0), "=f"(r1), "=f"(r2), "=f"(r3) : "l"(p), "f"(a), "f"(b), "f"(c), "f"(d) : "memory");
  return r0;
}
__device__ __forceinline__ uint4 ld_relaxed4(const float4* p) {
  uint4 v; asm volatile("ld.relaxed.gpu.global.v4.u32 {%0,%1,%2,%3}, [%4];" : "=r"(v.x), "=r"(v.y), "=r"(v.z), "=r"(v.w) : "l"(p) : "memory"); return v;
}

template <int SCALE_D> __device__ __forceinline__ void wgmma_ss_n192(float (&d)[96], uint32_t da, uint32_t db) {
  asm volatile("{\n.reg .b64 da, db;\nmov.b64 da, {%96, %98};\nmov.b64 db, {%97, %98};\n"
    "wgmma.mma_async.sync.aligned.m64n192k16.f32.bf16.bf16 {%0, %1, %2, %3, %4, %5, %6, %7, %8, %9, %10, %11, %12, %13, %14, %15, %16, %17, %18, %19, %20, %21, %22, %23, %24, %25, %26, %27, %28, %29, %30, %31, %32, %33, %34, %35, %36, %37, %38, %39, %40, %41, %42, %43, %44, %45, %46, %47, %48, %49, %50, %51, %52, %53, %54, %55, %56, %57, %58, %59, %60, %61, %62, %63, %64, %65, %66, %67, %68, %69, %70, %71, %72, %73, %74, %75, %76, %77, %78, %79, %80, %81, %82, %83, %84, %85, %86, %87, %88, %89, %90, %91, %92, %93, %94, %95}, da, db, %99, 1, 1, 0, 1;\n}\n"
    : "+f"(d[0]), "+f"(d[1]), "+f"(d[2]), "+f"(d[3]), "+f"(d[4]), "+f"(d[5]), "+f"(d[6]), "+f"(d[7]), "+f"(d[8]), "+f"(d[9]), "+f"(d[10]), "+f"(d[11]), "+f"(d[12]), "+f"(d[13]), "+f"(d[14]), "+f"(d[15]), "+f"(d[16]), "+f"(d[17]), "+f"(d[18]), "+f"(d[19]), "+f"(d[20]), "+f"(d[21]), "+f"(d[22]), "+f"(d[23]), "+f"(d[24]), "+f"(d[25]), "+f"(d[26]), "+f"(d[27]), "+f"(d[28]), "+f"(d[29]), "+f"(d[30]), "+f"(d[31]), "+f"(d[32]), "+f"(d[33]), "+f"(d[34]), "+f"(d[35]), "+f"(d[36]), "+f"(d[37]), "+f"(d[38]), "+f"(d[39]), "+f"(d[40]), "+f"(d[41]), "+f"(d[42]), "+f"(d[43]), "+f"(d[44]), "+f"(d[45]), "+f"(d[46]), "+f"(d[47]), "+f"(d[48]), "+f"(d[49]), "+f"(d[50]), "+f"(d[51]), "+f"(d[52]), "+f"(d[53]), "+f"(d[54]), "+f"(d[55]), "+f"(d[56]), "+f"(d[57]), "+f"(d[58]), "+f"(d[59]), "+f"(d[60]), "+f"(d[61]), "+f"(d[62]), "+f"(d[63]), "+f"(d[64]), "+f"(d[65]), "+f"(d[66]), "+f"(d[67]), "+f"(d[68]), "+f"(d[69]), "+f"(d[70]), "+f"(d[71]), "+f"(d[72]), "+f"(d[73]), "+f"(d[74]), "+f"(d[75]), "+f"(d[76]), "+f"(d[77]), "+f"(d[78]), "+f"(d[79]), "+f"(d[80]), "+f"(d[81]), "+f"(d[82]), "+f"(d[83]), "+f"(d[84]), "+f"(d[85]), "+f"(d[86]), "+f"(d[87]), "+f"(d[88]), "+f"(d[89]), "+f"(d[90]), "+f"(d[91]), "+f"(d[92]), "+f"(d[93]), "+f"(d[94]), "+f"(d[95])
    : "r"(da), "r"(db), "r"(0x40000040u), "n"(SCALE_D));
}
template <int SCALE_D> __device__ __forceinline__ void wgmma_ss_n128(float (&d)[64], uint32_t da, uint32_t db) {
  asm volatile("{\n.reg .b64 da, db;\nmov.b64 da, {%64, %66};\nmov.b64 db, {%65, %66};\n"
    "wgmma.mma_async.sync.aligned.m64n128k16.f32.bf16.bf16 {%0, %1, %2, %3, %4, %5, %6, %7, %8, %9, %10, %11, %12, %13, %14, %15, %16, %17, %18, %19, %20, %21, %22, %23, %24, %25, %26, %27, %28, %29, %30, %31, %32, %33, %34, %35, %36, %37, %38, %39, %40, %41, %42, %43, %44, %45, %46, %47, %48, %49, %50, %51, %52, %53, %54, %55, %56, %57, %58, %59, %60, %61, %62, %63}, da, db, %67, 1, 1, 0, 1;\n}\n"
    : "+f"(d[0]), "+f"(d[1]), "+f"(d[2]), "+f"(d[3]), "+f"(d[4]), "+f"(d[5]), "+f"(d[6]), "+f"(d[7]), "+f"(d[8]), "+f"(d[9]), "+f"(d[10]), "+f"(d[11]), "+f"(d[12]), "+f"(d[13]), "+f"(d[14]), "+f"(d[15]), "+f"(d[16]), "+f"(d[17]), "+f"(d[18]), "+f"(d[19]), "+f"(d[20]), "+f"(d[21]), "+f"(d[22]), "+f"(d[23]), "+f"(d[24]), "+f"(d[25]), "+f"(d[26]), "+f"(d[27]), "+f"(d[28]), "+f"(d[29]), "+f"(d[30]), "+f"(d[31]), "+f"(d[32]), "+f"(d[33]), "+f"(d[34]), "+f"(d[35]), "+f"(d[36]), "+f"(d[37]), "+f"(d[38]), "+f"(d[39]), "+f"(d[40]), "+f"(d[41]), "+f"(d[42]), "+f"(d[43]), "+f"(d[44]), "+f"(d[45]), "+f"(d[46]), "+f"(d[47]), "+f"(d[48]), "+f"(d[49]), "+f"(d[50]), "+f"(d[51]), "+f"(d[52]), "+f"(d[53]), "+f"(d[54]), "+f"(d[55]), "+f"(d[56]), "+f"(d[57]), "+f"(d[58]), "+f"(d[59]), "+f"(d[60]), "+f"(d[61]), "+f"(d[62]), "+f"(d[63])
    : "r"(da), "r"(db), "r"(0x40000040u), "n"(SCALE_D));
}
template <int SCALE_D> __device__ __forceinline__ void wgmma_ss_n96(float (&d)[48], uint32_t da, uint32_t db) {
  asm volatile("{\n.reg .b64 da, db;\nmov.b64 da, {%48, %50};\nmov.b64 db, {%49, %50};\n"
    "wgmma.mma_async.sync.aligned.m64n96k16.f32.bf16.bf16 {%0, %1, %2, %3, %4, %5, %6, %7, %8, %9, %10, %11, %12, %13, %14, %15, %16, %17, %18, %19, %20, %21, %22, %23, %24, %25, %26, %27, %28, %29, %30, %31, %32, %33, %34, %35, %36, %37, %38, %39, %40, %41, %42, %43, %44, %45, %46, %47}, da, db, %51, 1, 1, 0, 1;\n}\n"
    : "+f"(d[0]), "+f"(d[1]), "+f"(d[2]), "+f"(d[3]), "+f"(d[4]), "+f"(d[5]), "+f"(d[6]), "+f"(d[7]), "+f"(d[8]), "+f"(d[9]), "+f"(d[10]), "+f"(d[11]), "+f"(d[12]), "+f"(d[13]), "+f"(d[14]), "+f"(d[15]), "+f"(d[16]), "+f"(d[17]), "+f"(d[18]), "+f"(d[19]), "+f"(d[20]), "+f"(d[21]), "+f"(d[22]), "+f"(d[23]), "+f"(d[24]), "+f"(d[25]), "+f"(d[26]), "+f"(d[27]), "+f"(d[28]), "+f"(d[29]), "+f"(d[30]), "+f"(d[31]), "+f"(d[32]), "+f"(d[33]), "+f"(d[34]), "+f"(d[35]), "+f"(d[36]), "+f"(d[37]), "+f"(d[38]), "+f"(d[39]), "+f"(d[40]), "+f"(d[41]), "+f"(d[42]), "+f"(d[43]), "+f"(d[44]), "+f"(d[45]), "+f"(d[46]), "+f"(d[47])
    : "r"(da), "r"(db), "r"(0x40000040u), "n"(SCALE_D));
}
template <int SCALE_D> __device__ __forceinline__ void wgmma_tt_n72(float (&d)[36], uint32_t da, uint32_t db) {
  asm volatile("{\n.reg .b64 da, db;\nmov.b64 da, {%36, %38};\nmov.b64 db, {%37, %38};\n"
    "wgmma.mma_async.sync.aligned.m64n72k16.f32.bf16.bf16 {%0, %1, %2, %3, %4, %5, %6, %7, %8, %9, %10, %11, %12, %13, %14, %15, %16, %17, %18, %19, %20, %21, %22, %23, %24, %25, %26, %27, %28, %29, %30, %31, %32, %33, %34, %35}, da, db, %39, 1, 1, 1, 1;\n}\n"
    : "+f"(d[0]), "+f"(d[1]), "+f"(d[2]), "+f"(d[3]), "+f"(d[4]), "+f"(d[5]), "+f"(d[6]), "+f"(d[7]), "+f"(d[8]), "+f"(d[9]), "+f"(d[10]), "+f"(d[11]), "+f"(d[12]), "+f"(d[13]), "+f"(d[14]), "+f"(d[15]), "+f"(d[16]), "+f"(d[17]), "+f"(d[18]), "+f"(d[19]), "+f"(d[20]), "+f"(d[21]), "+f"(d[22]), "+f"(d[23]), "+f"(d[24]), "+f"(d[25]), "+f"(d[26]), "+f"(d[27]), "+f"(d[28]), "+f"(d[29]), "+f"(d[30]), "+f"(d[31]), "+f"(d[32]), "+f"(d[33]), "+f"(d[34]), "+f"(d[35])
    : "r"(da), "r"(db), "r"(0x40000040u), "n"(SCALE_D));
}
template <int SCALE_D> __device__ __forceinline__ void wgmma_rs_n128(float (&d)[64], const uint4& a, uint32_t db) {
  asm volatile("{\n.reg .b64 db;\nmov.b64 db, {%68, %69};\n"
    "wgmma.mma_async.sync.aligned.m64n128k16.f32.bf16.bf16 {%0, %1, %2, %3, %4, %5, %6, %7, %8, %9, %10, %11, %12, %13, %14, %15, %16, %17, %18, %19, %20, %21, %22, %23, %24, %25, %26, %27, %28, %29, %30, %31, %32, %33, %34, %35, %36, %37, %38, %39, %40, %41, %42, %43, %44, %45, %46, %47, %48, %49, %50, %51, %52, %53, %54, %55, %56, %57, %58, %59, %60, %61, %62, %63}, {%64, %65, %66, %67}, db, %70, 1, 1, 1;\n}\n"
    : "+f"(d[0]), "+f"(d[1]), "+f"(d[2]), "+f"(d[3]), "+f"(d[4]), "+f"(d[5]), "+f"(d[6]), "+f"(d[7]), "+f"(d[8]), "+f"(d[9]), "+f"(d[10]), "+f"(d[11]), "+f"(d[12]), "+f"(d[13]), "+f"(d[14]), "+f"(d[15]), "+f"(d[16]), "+f"(d[17]), "+f"(d[18]), "+f"(d[19]), "+f"(d[20]), "+f"(d[21]), "+f"(d[22]), "+f"(d[23]), "+f"(d[24]), "+f"(d[25]), "+f"(d[26]), "+f"(d[27]), "+f"(d[28]), "+f"(d[29]), "+f"(d[30]), "+f"(d[31]), "+f"(d[32]), "+f"(d[33]), "+f"(d[34]), "+f"(d[35]), "+f"(d[36]), "+f"(d[37]), "+f"(d[38]), "+f"(d[39]), "+f"(d[40]), "+f"(d[41]), "+f"(d[42]), "+f"(d[43]), "+f"(d[44]), "+f"(d[45]), "+f"(d[46]), "+f"(d[47]), "+f"(d[48]), "+f"(d[49]), "+f"(d[50]), "+f"(d[51]), "+f"(d[52]), "+f"(d[53]), "+f"(d[54]), "+f"(d[55]), "+f"(d[56]), "+f"(d[57]), "+f"(d[58]), "+f"(d[59]), "+f"(d[60]), "+f"(d[61]), "+f"(d[62]), "+f"(d[63])
    : "r"(a.x), "r"(a.y), "r"(a.z), "r"(a.w), "r"(db), "r"(0x40000040u), "n"(SCALE_D));
}
template <int SCALE_D> __device__ __forceinline__ void wgmma_rs_n96(float (&d)[48], const uint4& a, uint32_t db) {
  asm volatile("{\n.reg .b64 db;\nmov.b64 db, {%52, %53};\n"
    "wgmma.mma_async.sync.aligned.m64n96k16.f32.bf16.bf16 {%0, %1, %2, %3, %4, %5, %6, %7, %8, %9, %10, %11, %12, %13, %14, %15, %16, %17, %18, %19, %20, %21, %22, %23, %24, %25, %26, %27, %28, %29, %30, %31, %32, %33, %34, %35, %36, %37, %38, %39, %40, %41, %42, %43, %44, %45, %46, %47}, {%48, %49, %50, %51}, db, %54, 1, 1, 1;\n}\n"
    : "+f"(d[0]), "+f"(d[1]), "+f"(d[2]), "+f"(d[3]), "+f"(d[4]), "+f"(d[5]), "+f"(d[6]), "+f"(d[7]), "+f"(d[8]), "+f"(d[9]), "+f"(d[10]), "+f"(d[11]), "+f"(d[12]), "+f"(d[13]), "+f"(d[14]), "+f"(d[15]), "+f"(d[16]), "+f"(d[17]), "+f"(d[18]), "+f"(d[19]), "+f"(d[20]), "+f"(d[21]), "+f"(d[22]), "+f"(d[23]), "+f"(d[24]), "+f"(d[25]), "+f"(d[26]), "+f"(d[27]), "+f"(d[28]), "+f"(d[29]), "+f"(d[30]), "+f"(d[31]), "+f"(d[32]), "+f"(d[33]), "+f"(d[34]), "+f"(d[35]), "+f"(d[36]), "+f"(d[37]), "+f"(d[38]), "+f"(d[39]), "+f"(d[40]), "+f"(d[41]), "+f"(d[42]), "+f"(d[43]), "+f"(d[44]), "+f"(d[45]), "+f"(d[46]), "+f"(d[47])
    : "r"(a.x), "r"(a.y), "r"(a.z), "r"(a.w), "r"(db), "r"(0x40000040u), "n"(SCALE_D));
}
template <int SCALE_D> __device__ __forceinline__ void wgmma_rs_n64(float (&d)[32], const uint4& a, uint32_t db) {
  asm volatile("{\n.reg .b64 db;\nmov.b64 db, {%36, %37};\n"
    "wgmma.mma_async.sync.aligned.m64n64k16.f32.bf16.bf16 {%0, %1, %2, %3, %4, %5, %6, %7, %8, %9, %10, %11, %12, %13, %14, %15, %16, %17, %18, %19, %20, %21, %22, %23, %24, %25, %26, %27, %28, %29, %30, %31}, {%32, %33, %34, %35}, db, %38, 1, 1, 1;\n}\n"
    : "+f"(d[0]), "+f"(d[1]), "+f"(d[2]), "+f"(d[3]), "+f"(d[4]), "+f"(d[5]), "+f"(d[6]), "+f"(d[7]), "+f"(d[8]), "+f"(d[9]), "+f"(d[10]), "+f"(d[11]), "+f"(d[12]), "+f"(d[13]), "+f"(d[14]), "+f"(d[15]), "+f"(d[16]), "+f"(d[17]), "+f"(d[18]), "+f"(d[19]), "+f"(d[20]), "+f"(d[21]), "+f"(d[22]), "+f"(d[23]), "+f"(d[24]), "+f"(d[25]), "+f"(d[26]), "+f"(d[27]), "+f"(d[28]), "+f"(d[29]), "+f"(d[30]), "+f"(d[31])
    : "r"(a.x), "r"(a.y), "r"(a.z), "r"(a.w), "r"(db), "r"(0x40000040u), "n"(SCALE_D));
}


constexpr float LOG2E = 1.4426950408889634f;
__device__ __forceinline__ float silu_f(float y) { return y * rcp(1.f + ex2(-y * LOG2E)); }

__device__ __forceinline__ void mish_tile(const float* c, float rs0, float rs1, float rl0, float rl1, uint4* dst, uint32_t tag) {
  float h[8], u[8], r[8];
#pragma unroll
  for (int i = 0; i < 8; i++) {
    const bool hi = (i >> 1) & 1;
    h[i] = c[i] * (hi ? rs1 : rs0);
    u[i] = ex2(fminf(c[i] * (hi ? rl1 : rl0), 28.853900817779268f));
  }
#pragma unroll
  for (int i = 0; i < 8; i++) { const float tt = u[i] + 2.f; r[i] = rcp(fmaf(u[i], tt, 2.f)); h[i] *= u[i] * tt; }
#pragma unroll
  for (int i = 0; i < 8; i++) h[i] *= r[i];
  stg_frag(dst, pack2(h[0], h[1]), pack2(h[2], h[3]), pack2(h[4], h[5]), pack2(h[6], h[7]), tag);
}
__device__ __forceinline__ float phi_c(float c, float rs, float rl) {
  const float e = ex2(c * rl) + 1e-6f;
  const float p = fmaf(c, rs, 1.000001f);
  return c > 0.f ? p : e;
}
__device__ __forceinline__ uint4 phi_tile(const float* c, float rs0, float rs1, float rl0, float rl1) {
  uint4 r;
  r.x = pack2(phi_c(c[0], rs0, rl0), phi_c(c[1], rs0, rl0)); r.y = pack2(phi_c(c[2], rs1, rl1), phi_c(c[3], rs1, rl1));
  r.z = pack2(phi_c(c[4], rs0, rl0), phi_c(c[5], rs0, rl0)); r.w = pack2(phi_c(c[6], rs1, rl1), phi_c(c[7], rs1, rl1));
  return r;
}
template <int NB> __device__ __forceinline__ void init_bias(float* acc, uint32_t bias_addr, float ir0, float ir1) {
#pragma unroll
  for (int nb = 0; nb < NB; nb++) {
    const float2 b = lds_f32x2(bias_addr + 32 * nb);
    acc[4 * nb] = b.x * ir0; acc[4 * nb + 1] = b.y * ir0; acc[4 * nb + 2] = b.x * ir1; acc[4 * nb + 3] = b.y * ir1;
  }
}

__global__ void __launch_bounds__(384, 1)
fused_kernel(const __grid_constant__ CUtensorMap tm_x, const __grid_constant__ CUtensorMap tm_qkv,
             const __grid_constant__ CUtensorMap tm_w1, const __grid_constant__ CUtensorMap tm_w2a,
             const __grid_constant__ CUtensorMap tm_w2b, const __grid_constant__ CUtensorMap tm_wo,
             const __grid_constant__ CUtensorMap tm_out,
             const uint8_t* __restrict__ wqkv, const uint8_t* __restrict__ w1, const uint8_t* __restrict__ w2,
             const uint8_t* __restrict__ wo, const __nv_bfloat16* __restrict__ b1, const uint8_t* __restrict__ xin) {
  extern __shared__ __align__(1024) uint8_t smem_raw[];
  constexpr uint32_t sb = SMEM_BASE;
  const int tid = threadIdx.x, lane = tid & 31;
  const int warp = __shfl_sync(0xffffffffu, tid >> 5, 0);
  const int bid = blockIdx.x;
  const int khalf = (bid >> 4) & 1, rb = (bid >> 5) * 4 + ((bid >> 2) & 3), nt = bid & 3;
  const int pbid = bid ^ 16;
  const int j = khalf + 2 * nt;
  constexpr uint32_t bar0 = sb + OFF_BAR;


  if (warp >= 8) {
    asm volatile("setmaxnreg.dec.sync.aligned.u32 40;");
    if (warp == 8) {
      if (lane == 0) {
        asm volatile("cp.async.bulk.prefetch.L2.global [%0], %1;" ::"l"(xin + ((size_t)rb * 128 + j * 16) * 1024), "r"(16384) : "memory");
        if (smem_u32(smem_raw) != SMEM_BASE) asm volatile("trap;");
#pragma unroll
        for (int i = 0; i < 4; i++) mbar_init(bar0 + 8 * (BAR_X + i), 1);
        asm volatile("fence.mbarrier_init.release.cluster;" ::: "memory");
#pragma unroll 1
        for (int i = 0; i < 4; i++) {
          mbar_expect_tx(bar0 + 8 * (BAR_X + i), 32768);
          tma2d(sb + OFF_D + (2 * i) * 16384, &tm_x, 128 * i, rb * 128, bar0 + 8 * (BAR_X + i));
          tma2d(sb + OFF_D + (2 * i + 1) * 16384, &tm_x, 128 * i + 64, rb * 128, bar0 + 8 * (BAR_X + i));
        }
        asm volatile("prefetch.tensormap [%0];" ::"l"(&tm_w1) : "memory");
      }
      __syncwarp();
      named_bar_sync(0, 384);
      if (lane == 0) {
        const int c_own = 128 * nt + 64 * khalf, c_par = 128 * nt + 64 * (1 - khalf);
        uint32_t epar = 0x3Fu;
        int slot = 0;
        uint32_t full, dst;
        auto acquire = [&](uint32_t bytes) {
          full = bar0 + 8 * (BAR_FULL + slot);
          dst = sb + (slot < 6 ? OFF_RING + slot * SLOT_BYTES : OFF_D + (slot - 4) * SLOT_BYTES);
          mbar_wait(bar0 + 8 * (BAR_EMPTY + slot), (epar >> slot) & 1u);
          epar ^= 1u << slot;
          mbar_expect_tx(full, bytes);
        };
#pragma unroll 1
        for (int st = 0; st < 32; st++) {
          if (st >= 8 && st < 24) {
            acquire(12288);
            const int k0 = 32 * (st - 8);
            tma2d(dst, &tm_qkv, 512 + 64 * j, k0, full);
            tma2d(dst + 4096, &tm_qkv, 1024 + 64 * j, k0, full);
            tma2d(dst + 8192, &tm_qkv, 64 * j, k0, full);
          } else {
            acquire(16384);
            const int k0 = 64 * (st & 7), c0 = 224 * j + (st >= 8 ? 128 : 0);
            tma2d(dst, &tm_w1, c0, k0, full);
            tma2d(dst + 8192, &tm_w1, c0 + 64, k0, full);
          }
          slot = slot == 5 ? 0 : slot + 1;
        }
        const uint8_t* act_src = reinterpret_cast<const uint8_t*>(g_act) + (size_t)(rb * 112 + 56 * khalf) * 4096;
        const uint8_t* o_src = reinterpret_cast<const uint8_t*>(g_o) + (size_t)rb * 32 * 4096;
        int pr = 0;
#pragma unroll 1
        for (int i = 0; i < 24; i++) {
          slot = pr < 4 ? 7 + pr : pr == 4 ? 6 : 11;
          const int slot2 = pr < 4 ? pr + 2 : pr - 4;
          const uint32_t dst2 = sb + OFF_RING + slot2 * SLOT_BYTES;
          if (i < 6) mbar_wait(bar0 + 8 * (BAR_EMPTY + slot2), (epar >> slot2) & 1u);
          const int src = (i & 7) >> 1;
          const int ksrc = 224 * (4 * khalf + src);
          if (i < 8) {
            acquire(32768);
            tma2d(dst, &tm_w2a, c_own, ksrc + 64 * (i & 1), full);
            tma2d(dst + 8192, &tm_w2a, c_par, ksrc + 64 * (i & 1), full);
            bulk_g2s(dst2, act_src + (14 * src + 4 * (i & 1)) * 4096, 16384, full);
          } else if (i < 16) {
            const bool direct = i >= LDG_FROM && (i & 1);
            acquire(direct ? 12288 : 24576);
            tma2d(dst, &tm_w2b, c_own, ksrc + 128 + 48 * (i & 1), full);
            tma2d(dst + 6144, &tm_w2b, c_par, ksrc + 128 + 48 * (i & 1), full);
            if (i == 8) {
              mbar_wait(bar0 + 8 * BAR_KVP, 0);
              mbar_expect_tx(bar0 + 8 * BAR_XT, 16384);
              tma2d(sb + OFF_XT, &tm_x, c_own, rb * 128, bar0 + 8 * BAR_XT);
              mbar_wait(bar0 + 8 * BAR_OWN_B, 0);
            }
            if (!direct) bulk_g2s(dst2, act_src + (14 * src + 8 + 3 * (i & 1)) * 4096, 12288, full);
          } else {
            const bool direct = i >= LDG_FROM && (i & 1);
            acquire(direct ? 8192 : 24576);
            tma2d(dst, &tm_wo, c_own, 64 * (i - 16), full);
            if (i == 16) mbar_wait(bar0 + 8 * BAR_OWN_O, 0);
            if (!direct) bulk_g2s(dst2, o_src + (i - 16) * 16384, 16384, full);
          }
          pr = pr == 5 ? 0 : pr + 1;
        }
      }
    } else {
      const int aw = warp - 9;
      if (aw == 0) {
        if (lane < 2 * NSLOT) mbar_init(bar0 + 8 * lane, lane < NSLOT ? 1 : 8);
        if (lane == 28) {
          mbar_init(bar0 + 8 * BAR_BIAS, 1); mbar_init(bar0 + 8 * BAR_XT, 1);
          mbar_init(bar0 + 8 * BAR_PUB_KV, 8); mbar_init(bar0 + 8 * BAR_RDY_KV, 2); mbar_init(bar0 + 8 * BAR_END, 8);
          mbar_init(bar0 + 8 * BAR_KVP, 2); mbar_init(bar0 + 8 * BAR_KVF, 1); mbar_init(bar0 + 8 * BAR_OWN_B, 8); mbar_init(bar0 + 8 * BAR_OWN_O, 8);
        }
        asm volatile("fence.mbarrier_init.release.cluster;" ::: "memory");
        fence_async_smem();
        __syncwarp();
        named_bar_sync(0, 384);
        uint16_t bv[7];
#pragma unroll
        for (int i = 0; i < 7; i++) asm volatile("ld.global.nc.u16 %0, [%1];" : "=h"(bv[i]) : "l"(b1 + 224 * j + i * 32 + lane));
#pragma unroll
        for (int i = 0; i < 7; i++) sts_f32(sb + OFF_B1 + 4 * (i * 32 + lane), __uint_as_float((uint32_t)bv[i] << 16));
        __syncwarp();
        if (lane == 0) mbar_arrive(bar0 + 8 * BAR_BIAS);
        if (lane == 0) {
          unsigned long long t0, t1;
          asm volatile("mov.u64 %0, %%globaltimer;" : "=l"(t0));
          while (!mbar_try(bar0 + 8 * BAR_END, 0)) {
            asm volatile("mov.u64 %0, %%globaltimer;" : "=l"(t1));
            if (t1 - t0 > 2000000000ull) asm volatile("trap;");
          }
        }
      } else {
        unsigned dn; asm volatile("ld.relaxed.gpu.global.u32 %0, [%1];" : "=r"(dn) : "l"(&g_done) : "memory");
        const int hw = aw - 1;
        if (hw == 0 && lane < 4) {
          const uint8_t* base = lane == 0 ? wqkv : lane == 1 ? w1 : lane == 2 ? w2 : wo;
          asm volatile("prefetch.global.L2 [%0];" ::"l"(base + (size_t)bid * 4096));
        }
        named_bar_sync(0, 384);
        if (hw == 0 && lane < 4) {
          mbar_wait(bar0 + 8 * (BAR_X + 3), 0);
          const uint8_t* base = lane == 0 ? wqkv : lane == 1 ? w1 : lane == 2 ? w2 : wo;
          const uint32_t bytes = lane == 0 ? 12288u : lane == 3 ? 4096u : 14336u;
          asm volatile("cp.async.bulk.prefetch.L2.global [%0], %1;" ::"l"(base + (size_t)bid * bytes), "r"(bytes) : "memory");
        }
        __syncwarp();
        const unsigned ep1 = dn / NCTA + 1u;
        if (rb == 0) {
          for (int i = hw * 32 + lane; i < 272; i += 64) g_kv[ep1 & 1][j * 272 + i] = make_float4(0.f, 0.f, 0.f, 0.f);
        }
        float4* kvbuf = &g_kv[(ep1 & 1) ^ 1][j * 272];
        mbar_wait(bar0 + 8 * BAR_PUB_KV, 0);
        {
          uint4 a[4], b[4];
#pragma unroll
          for (int q = 0; q < 4; q++) { const int i = (hw * 4 + q) * 32 + lane; a[q] = lds_v4(sb + OFF_V + i * 16); b[q] = lds_v4(sb + OFF_V + 8192 + i * 16); }
          float sink = 0.f;
          if (hw == 1 && lane < 16) {
            const uint4 c = lds_v4(sb + OFF_V + (256 + lane) * 16), e = lds_v4(sb + OFF_V + 8192 + (256 + lane) * 16);
            sink += atom_add4(kvbuf + 256 + lane, __uint_as_float(c.x) + __uint_as_float(e.x), __uint_as_float(c.y) + __uint_as_float(e.y),
                              __uint_as_float(c.z) + __uint_as_float(e.z), __uint_as_float(c.w) + __uint_as_float(e.w));
          }
          float r[4];
#pragma unroll
          for (int q = 0; q < 4; q++)
            r[q] = atom_add4(kvbuf + (hw * 4 + q) * 32 + lane, __uint_as_float(a[q].x) + __uint_as_float(b[q].x), __uint_as_float(a[q].y) + __uint_as_float(b[q].y),
                             __uint_as_float(a[q].z) + __uint_as_float(b[q].z), __uint_as_float(a[q].w) + __uint_as_float(b[q].w));
          __syncwarp();
          if (lane == 0) mbar_arrive(bar0 + 8 * BAR_KVP);
#pragma unroll
          for (int i = 0; i < 8; i++) {
            const uint32_t za = sb + OFF_KVB + hw * 4096 + (i * 32 + lane) * 16;
            sts_v4(za, 0u, 0u, 0u, 0u); sts_v4(za + 8192, 0u, 0u, 0u, 0u);
          }
          sink += (r[0] + r[1]) + (r[2] + r[3]);
          asm volatile("" ::"f"(sink) : "memory");
          __syncwarp();
          if (lane == 0) {
            red_inc(&g_cntKV[j * 8]);
            if (hw == 0) {
              const unsigned tgt = 32u * ep1;
              unsigned v;
              while (true) {
                asm volatile("ld.relaxed.gpu.global.u32 %0, [%1];" : "=r"(v) : "l"(&g_cntKV[j * 8]) : "memory");
                if ((int)(v - tgt) >= 0) break;
              }
              asm volatile("ld.acquire.gpu.global.u32 %0, [%1];" : "=r"(v) : "l"(&g_cntKV[j * 8]) : "memory");
              mbar_arrive(bar0 + 8 * BAR_KVF);
            }
          }
          __syncwarp();
          mbar_wait(bar0 + 8 * BAR_KVF, 0);
        }
        {
          const int d = lane >> 1, hf = lane & 1;
          uint4 v[2][2], zz[2];
#pragma unroll
          for (int q = 0; q < 2; q++) {
            const int hh = 2 * hw + q;
            v[q][0] = ld_relaxed4(kvbuf + hh * 64 + d * 4 + hf * 2); v[q][1] = ld_relaxed4(kvbuf + hh * 64 + d * 4 + hf * 2 + 1);
            zz[q] = ld_relaxed4(kvbuf + 256 + hh * 4 + (d >> 2));
          }
#pragma unroll
          for (int q = 0; q < 2; q++) {
            const int hh = 2 * hw + q;
            const uint32_t dst = sb + OFF_KVB + d * 128 + hh * 2048;
            sts_v4(dst + (((2 * hh + hf) ^ (d & 7)) << 4),
                   pack2(__uint_as_float(v[q][0].x), __uint_as_float(v[q][0].y)), pack2(__uint_as_float(v[q][0].z), __uint_as_float(v[q][0].w)),
                   pack2(__uint_as_float(v[q][1].x), __uint_as_float(v[q][1].y)), pack2(__uint_as_float(v[q][1].z), __uint_as_float(v[q][1].w)));
            const int zi = d & 3;
            const float zf = __uint_as_float(zi == 0 ? zz[q].x : zi == 1 ? zz[q].y : zi == 2 ? zz[q].z : zz[q].w);
            const uint32_t z2 = pack2(zf, zf);
            if (hf == 0) sts_v4(dst + 8192 + ((hh ^ (d & 7)) << 4), z2, z2, z2, z2);
          }
        }
        fence_async_smem();
        __syncwarp();
        if (lane == 0) mbar_arrive(bar0 + 8 * BAR_RDY_KV);
      }
    }
  } else {
    asm volatile("setmaxnreg.inc.sync.aligned.u32 232;");
    const int wg = warp >> 2;
    const int g = lane >> 2, t = lane & 3;
    const int lr0 = warp * 16 + g;
    unsigned dn; asm volatile("ld.relaxed.gpu.global.u32 %0, [%1];" : "=r"(dn) : "l"(&g_done) : "memory");
    const uint32_t a_lo = dlo(sb + OFF_D + wg * 8192, 16);
    constexpr uint32_t sb_lo = sb >> 4;

#define B_LO(gs, off, lbo) (sb_lo + ((slot_off(slot_of(gs)) + (off)) >> 4) + (((lbo) >> 4) << 16))
#define WAIT_FULL(gs) do { if ((gs) < NSTAGES) mbar_wait(bar0 + 8 * (BAR_FULL + slot_of((gs) < NSTAGES ? (gs) : 0)), use_of((gs) < NSTAGES ? (gs) : 0) & 1); } while (0)
#define RELEASE_SLOT(sl) do { if (lane == 0) mbar_arrive(bar0 + 8 * (BAR_EMPTY + (sl))); } while (0)
#define RELEASE_STAGE(gs) do { if ((gs) >= 0 && (gs) < 50) RELEASE_SLOT(slot_of((gs) < 0 ? 0 : (gs))); } while (0)
#define WARP_ARRIVE(b) do { __syncwarp(); if (lane == 0) mbar_arrive(bar0 + 8 * (b)); } while (0)

    uint4* act_out = g_act + (size_t)((rb * 112 + 14 * j) * 8 + warp) * 32 + lane;
    const uint32_t bias_addr = sb + OFF_B1 + 8 * t;
    float rs0, rs1;
    float pool[160];
    float (&acca)[64] = reinterpret_cast<float (&)[64]>(pool[0]);
    float (&accq)[96] = reinterpret_cast<float (&)[96]>(pool[64]);
    float (&accb)[48] = reinterpret_cast<float (&)[48]>(pool[0]);
    float (&accy)[64] = reinterpret_cast<float (&)[64]>(pool[64]);
    float (&accs)[32] = reinterpret_cast<float (&)[32]>(pool[0]);
    float rl0, rl1, ir0, ir1;
    const uint32_t tag = (dn / NCTA + 1u) & 1u;
    {
      uint4 q[16], p[16];
      const int par = g & 1;
      const uint32_t rowa = sb + OFF_D + lr0 * 128;
      const uint32_t u0 = (uint32_t)(((par * 4 + t) ^ g) << 4), u1 = u0 ^ 64u;
      named_bar_sync(0, 384);
      float sm[2][4], ga[2][4], gb[2][4];
#pragma unroll
      for (int a = 0; a < 2; a++) {
        sm[a][0] = sm[a][1] = sm[a][2] = sm[a][3] = 0.f;
        ga[a][0] = ga[a][1] = ga[a][2] = ga[a][3] = 0.f;
        gb[a][0] = gb[a][1] = gb[a][2] = gb[a][3] = 0.f;
      }
      const uint32_t ones = 0x3F803F80u;
#pragma unroll
      for (int c = 0; c < 8; c++) {
        if ((c & 1) == 0) mbar_wait(bar0 + 8 * (BAR_X + (c >> 1)), 0);
        q[2 * c] = lds_v4(rowa + c * 16384 + u0);     p[2 * c] = lds_v4(rowa + c * 16384 + 1024 + u0);
        q[2 * c + 1] = lds_v4(rowa + c * 16384 + u1); p[2 * c + 1] = lds_v4(rowa + c * 16384 + 1024 + u1);
#pragma unroll
        for (int h = 0; h < 2; h++) {
          const int i = 2 * c + h;
          mma16816(sm[0], q[i].x, p[i].x, q[i].y, p[i].y, ones, ones);
          mma16816(sm[1], q[i].z, p[i].z, q[i].w, p[i].w, ones, ones);
          mma16816(ga[0], q[i].x, p[i].x, q[i].y, p[i].y, q[i].x, q[i].y);
          mma16816(ga[1], q[i].z, p[i].z, q[i].w, p[i].w, q[i].z, q[i].w);
          mma16816(gb[0], q[i].x, p[i].x, q[i].y, p[i].y, p[i].x, p[i].y);
          mma16816(gb[1], q[i].z, p[i].z, q[i].w, p[i].w, p[i].z, p[i].w);
        }
      }
      const float m0 = (sm[0][0] + sm[1][0]) * (1.f / DM);
      const float m1 = (sm[0][2] + sm[1][2]) * (1.f / DM);
      const uint32_t mb0 = pack2(m0, m0), mb1 = pack2(m1, m1);
#pragma unroll
      for (int i = 0; i < 16; i++) {
        const uint32_t off = (uint32_t)(i >> 1) * 16384 + ((i & 1) ? u1 : u0);
        sts_v4(rowa + off, hsub2_bf16(q[i].x, mb0), hsub2_bf16(q[i].y, mb0), hsub2_bf16(q[i].z, mb0), hsub2_bf16(q[i].w, mb0));
        sts_v4(rowa + 1024 + off, hsub2_bf16(p[i].x, mb1), hsub2_bf16(p[i].y, mb1), hsub2_bf16(p[i].z, mb1), hsub2_bf16(p[i].w, mb1));
      }
      fence_async_smem();
      float d0 = par ? ga[0][1] + ga[1][1] : ga[0][0] + ga[1][0];
      float d1 = par ? gb[0][3] + gb[1][3] : gb[0][2] + gb[1][2];
      d0 = __shfl_sync(0xffffffffu, d0, (lane & ~3) | (g >> 1));
      d1 = __shfl_sync(0xffffffffu, d1, (lane & ~3) | (g >> 1));
      const float v0 = fmaxf(d0 * (1.f / DM) - m0 * m0, 0.f) + 1e-5f;
      const float v1 = fmaxf(d1 * (1.f / DM) - m1 * m1, 0.f) + 1e-5f;
      rs0 = rsqrtf(v0); rs1 = rsqrtf(v1);
      ir0 = v0 * rs0; ir1 = v1 * rs1;
      rl0 = rs0 * LOG2E; rl1 = rs1 * LOG2E;
      mbar_wait(bar0 + 8 * BAR_BIAS, 0);
      init_bias<16>(acca, bias_addr, ir0, ir1);
      named_bar_sync(1 + wg, 128);
    }
    const uint4* act_in = g_act + (size_t)((rb * 112 + 56 * khalf) * 8 + warp) * 32 + lane;
    const uint4* o_in = g_o + (size_t)(rb * 32 * 8 + warp) * 32 + lane;
    const uint32_t a_lds = sb + warp * 512 + lane * 16;
    uint4 ab[5][4];
    auto abuf = [](int rs) { return a_direct(rs) ? 3 + ((rs >> 1) & 1) : rs % 3; };
    auto a_gptr = [&](int rs) -> const uint4* {
      if (rs < 8) return act_in + (14 * (rs >> 1) + 4 * (rs & 1)) * 256;
      if (rs < 16) return act_in + (14 * ((rs - 8) >> 1) + 8 + 3 * (rs & 1)) * 256;
      return o_in + 4 * (rs - 16) * 256;
    };
    auto load_direct = [&](int rs) {
      if (!a_direct(rs)) return;
#pragma unroll
      for (int kk = 0; kk < 4; kk++) if (!(rs >= 8 && rs < 16 && kk == 3)) ab[abuf(rs)][kk] = ld_relaxed4(reinterpret_cast<const float4*>(a_gptr(rs) + kk * 256));
    };
    auto fetch_a = [&](int rs) {
      if (rs >= 24) return;
      if (!a_direct(rs)) {
        const uint32_t a = a_lds + slot_off(slot2_of(32 + rs));
#pragma unroll
        for (int kk = 0; kk < 4; kk++) if (!(rs >= 8 && rs < 16 && kk == 3)) ab[abuf(rs)][kk] = lds_v4(a + kk * 4096);
      }
      if (rs >= 8 && rs < 16) validate3(ab[abuf(rs)], a_gptr(rs), tag);
      else validate4(ab[abuf(rs)], a_gptr(rs), tag);
    };
    auto keep_a = [&](int rs) {
      if (rs < 0) return;
#pragma unroll
      for (int kk = 0; kk < 4; kk++) if (!(rs >= 8 && rs < 16 && kk == 3)) fence_u4(ab[abuf(rs)][kk]);
    };
    WAIT_FULL(0);
#pragma unroll
    for (int st = 0; st < 8; st++) {
      wg_fence();
#pragma unroll
      for (int kk = 0; kk < 4; kk++) wgmma_ss_n128<1>(acca, a_lo + ((st * 16384 + kk * 32) >> 4), B_LO(st, kk * 2048, 8192));
      wg_commit();
      if (st == 0) zero_regs(accq);
      WAIT_FULL(st + 1);
      wg_wait<1>();
      RELEASE_STAGE(st - 1);
    }
#pragma unroll
    for (int st = 0; st < 16; st++) {
      const int gs = 8 + st;
      const uint32_t as = a_lo + (((st >> 1) * 16384 + (st & 1) * 64) >> 4);
      wg_fence();
      wgmma_ss_n192<1>(accq, as, B_LO(gs, 0, 4096));
      wgmma_ss_n192<1>(accq, as + 2, B_LO(gs, 2048, 4096));
      wg_commit();
      if (st == 1) fence_regs(acca);
      if (st >= 1 && st < 9) mish_tile(acca + 8 * (st - 1), rs0, rs1, rl0, rl1, act_out + (st - 1) * 256, tag);
      if (st == 9) init_bias<12>(accb, bias_addr + 512, ir0, ir1);
      WAIT_FULL(gs + 1);
      wg_wait<1>();
      RELEASE_STAGE(gs - 1);

    }
    uint4 pq[4];
    {
      const int m = lane >> 3, rr = lane & 7;
      const uint32_t srow = sb + OFF_D + (warp * 16 + (m & 1) * 8 + rr) * 128;
      const uint32_t ka = dlo(sb + OFF_PK + wg * 8192, 16);
      const uint32_t vb = dlo(sb + OFF_V + wg * 8192, OFF_ONES - OFF_V);
      float (&acck)[36] = reinterpret_cast<float (&)[36]>(pool[64]);
#pragma unroll
      for (int st = 0; st < 8; st++) {
        const int gs = 24 + st;
        wg_fence();
#pragma unroll
        for (int kk = 0; kk < 4; kk++) wgmma_ss_n96<1>(accb, a_lo + ((st * 16384 + kk * 32) >> 4), B_LO(gs, kk * 2048, 8192));
        if (st == 4) {
          wgmma_tt_n72<0>(acck, ka, vb);
#pragma unroll
          for (int kk = 1; kk < 4; kk++) wgmma_tt_n72<1>(acck, ka + kk * 128, vb + kk * 128);
        }
        wg_commit();
        if (st == 1) {
          fence_regs(accq);
          pq[0] = phi_tile(accq, rs0, rs1, rl0, rl1); pq[1] = phi_tile(accq + 8, rs0, rs1, rl0, rl1);
        } else if (st == 2) {
          pq[2] = phi_tile(accq + 16, rs0, rs1, rl0, rl1); pq[3] = phi_tile(accq + 24, rs0, rs1, rl0, rl1);
#pragma unroll
          for (int i = 0; i < 4; i++)
            stmatrix_x4(srow + OFF_PK + (((2 * i + (m >> 1)) ^ rr) << 4), pq[i].x, pq[i].y, pq[i].z, pq[i].w);
        } else if (st == 3) {
#pragma unroll
          for (int i = 0; i < 4; i++) {
            const float* c = accq + 32 + 8 * i;
            stmatrix_x4(srow + OFF_V + (((2 * i + (m >> 1)) ^ rr) << 4),
                        pack2(c[0] * rs0, c[1] * rs0), pack2(c[2] * rs1, c[3] * rs1), pack2(c[4] * rs0, c[5] * rs0), pack2(c[6] * rs1, c[7] * rs1));
          }
        } else if (st == 4) {
          pq[0] = phi_tile(accq + 64, rs0, rs1, rl0, rl1); pq[1] = phi_tile(accq + 72, rs0, rs1, rl0, rl1);
        } else if (st == 5) {
          pq[2] = phi_tile(accq + 80, rs0, rs1, rl0, rl1); pq[3] = phi_tile(accq + 88, rs0, rs1, rl0, rl1);
        } else if (st == 6) {
          fence_regs(acck);
          const int wq = warp & 3;
          const uint32_t hb = sb + OFF_V + wg * 8192 + wq * 1024;
          const uint32_t a0p = hb + (g * 16 + 2 * t) * 4;
#pragma unroll
          for (int w = 0; w < 4; w++) {
            if (wq == w) {
              sts_f32x2(a0p, acck[8 * w], acck[8 * w + 1]); sts_f32x2(a0p + 512, acck[8 * w + 2], acck[8 * w + 3]);
              sts_f32x2(a0p + 32, acck[8 * w + 4], acck[8 * w + 5]); sts_f32x2(a0p + 544, acck[8 * w + 6], acck[8 * w + 7]);
            }
          }
          if (t == 0) { const uint32_t zb = sb + OFF_V + wg * 8192 + 4096 + wq * 64 + g * 4; sts_f32(zb, acck[32]); sts_f32(zb + 32, acck[34]); }
          WARP_ARRIVE(BAR_PUB_KV);
        }
        WAIT_FULL(gs + 1);
        if (st == 7) fetch_a(0);
        wg_wait<1>();
        RELEASE_STAGE(gs - 1);
        if (st == 3) {
          if (lane < 16) sts_v4(sb + OFF_ONES + (warp * 16 + lane) * 128 + ((lane & 7) << 4), 0x3F803F80u, 0x3F803F80u, 0x3F803F80u, 0x3F803F80u);
          fence_async_smem();
          named_bar_sync(1 + wg, 128);
        }
        if (st >= 4) RELEASE_SLOT(4 + (st - 1));
        if (st == 5) RELEASE_SLOT(6);
      }
    }
    uint4 pv[8];
    const float4* ypp = g_yp + (size_t)((pbid * 8 + warp) * 8) * 32 + lane;
#pragma unroll
    for (int rs = 0; rs < 24; rs++) {
      const int gs = 32 + rs;
      if (rs == O_STAGE) mbar_wait(bar0 + 8 * BAR_RDY_KV, 0);
      wg_fence();
      if (rs == O_STAGE) {
        const uint32_t kb = dlo(sb + OFF_KVB, 8192);
        wgmma_rs_n96<0>(accb, pq[0], kb);
#pragma unroll
        for (int kk = 1; kk < 4; kk++) wgmma_rs_n96<1>(accb, pq[kk], kb + kk * 128);
        wg_commit();
      }
      if (rs < 8) {
#pragma unroll
        for (int kk = 0; kk < 4; kk++) {
          if (rs == 0 && kk == 0) wgmma_rs_n128<0>(accy, ab[abuf(rs)][kk], B_LO(gs, kk * 2048, 8192));
          else wgmma_rs_n128<1>(accy, ab[abuf(rs)][kk], B_LO(gs, kk * 2048, 8192));
        }
      } else if (rs < 16) {
#pragma unroll
        for (int kk = 0; kk < 3; kk++) wgmma_rs_n128<1>(accy, ab[abuf(rs)][kk], B_LO(gs, kk * 2048, 6144));
      } else {
#pragma unroll
        for (int kk = 0; kk < 4; kk++) {
          if (rs == 16 && kk == 0) wgmma_rs_n64<0>(accs, ab[abuf(rs)][kk], B_LO(gs, kk * 2048, 8192));
          else wgmma_rs_n64<1>(accs, ab[abuf(rs)][kk], B_LO(gs, kk * 2048, 8192));
        }
      }
      wg_commit();
      if (rs == 1) fence_regs(accb);
      if (rs >= 1 && rs <= 3) {
#pragma unroll
        for (int i = 2 * (rs - 1); i < 2 * (rs - 1) + 2; i++)
          mish_tile(accb + 8 * i, rs0, rs1, rl0, rl1, act_out + (8 + i) * 256, tag);
        if (rs == 3) WARP_ARRIVE(BAR_OWN_B);
      }
      if (rs == O_STAGE + 1) {
        fence_regs(accb);
#pragma unroll
        for (int kk = 0; kk < 4; kk++) fence_u4(pq[kk]);
        uint4* o_out = g_o + (size_t)((rb * 32 + 4 * j) * 8 + warp) * 32 + lane;
#pragma unroll
        for (int hh = 0; hh < 4; hh++) {
          const float i0 = __fdividef(1.f, accb[32 + 4 * hh] + 1e-6f), i1 = __fdividef(1.f, accb[34 + 4 * hh] + 1e-6f);
          const float* n = accb + 8 * hh;
          stg_frag(o_out + hh * 256, pack2(n[0] * i0, n[1] * i0), pack2(n[2] * i1, n[3] * i1), pack2(n[4] * i0, n[5] * i0), pack2(n[6] * i1, n[7] * i1), tag);
        }
        WARP_ARRIVE(BAR_OWN_O);
      }
      if (rs >= 17 && rs < 20) {
        if (rs == 17) fence_regs(accy);
        float4* yp = g_yp + (size_t)((bid * 8 + warp) * 8) * 32 + lane;
#pragma unroll
        for (int q = 3 * (rs - 17); q < 3 * (rs - 17) + 3 && q < 8; q++) {
          const uint32_t v0 = (__float_as_uint(accy[32 + 4 * q]) & ~1u) | tag, v1 = (__float_as_uint(accy[33 + 4 * q]) & ~1u) | tag;
          const uint32_t v2 = (__float_as_uint(accy[34 + 4 * q]) & ~1u) | tag, v3 = (__float_as_uint(accy[35 + 4 * q]) & ~1u) | tag;
          asm volatile("st.relaxed.gpu.global.v4.u32 [%0], {%1,%2,%3,%4};" ::"l"(yp + q * 32), "r"(v0), "r"(v1), "r"(v2), "r"(v3) : "memory");
        }
      }
      WAIT_FULL(gs + 1);
      fetch_a(rs + 1);
      if (rs < 23) wg_wait<1>();
      RELEASE_STAGE(gs - 1);
      if (rs == 0) RELEASE_SLOT(11);
      if (rs < 23) keep_a(rs - 1);
      load_direct(rs + 3);
    }
    {
#pragma unroll
      for (int q = 0; q < 8; q++) pv[q] = ld_relaxed4(ypp + q * 32);
      wg_wait<0>();
      keep_a(22); keep_a(23);
      fence_regs(accs);
      while (true) {
        uint32_t an = 0xffffffffu, orr = 0u;
#pragma unroll
        for (int q = 0; q < 8; q++) {
          asm("lop3.b32 %0, %0, %1, %2, 0x80;" : "+r"(an) : "r"(pv[q].x), "r"(pv[q].y));
          asm("lop3.b32 %0, %0, %1, %2, 0x80;" : "+r"(an) : "r"(pv[q].z), "r"(pv[q].w));
          asm("lop3.b32 %0, %0, %1, %2, 0xFE;" : "+r"(orr) : "r"(pv[q].x), "r"(pv[q].y));
          asm("lop3.b32 %0, %0, %1, %2, 0xFE;" : "+r"(orr) : "r"(pv[q].z), "r"(pv[q].w));
        }
        if ((((an ^ tag) | (orr ^ tag)) & 1u) == 0u) break;
#pragma unroll
        for (int q = 0; q < 8; q++) pv[q] = ld_relaxed4(ypp + q * 32);
      }
      __syncwarp();
      mbar_wait(bar0 + 8 * BAR_XT, 0);
      const uint32_t xa = sb + OFF_XT + lr0 * 128 + 4 * t;
#pragma unroll
      for (int q = 0; q < 8; q++) {
        const uint32_t a0 = xa + ((q ^ g) << 4), a1 = a0 + 1024;
        const uint32_t x0 = lds_u32(a0), x1 = lds_u32(a1);
        const float y0 = accy[4 * q] + __uint_as_float(pv[q].x), y1 = accy[4 * q + 1] + __uint_as_float(pv[q].y);
        const float y2 = accy[4 * q + 2] + __uint_as_float(pv[q].z), y3 = accy[4 * q + 3] + __uint_as_float(pv[q].w);
        const float o0 = fmaf(accs[4 * q], silu_f(y0), bf_lo(x0)), o1 = fmaf(accs[4 * q + 1], silu_f(y1), bf_hi(x0));
        const float o2 = fmaf(accs[4 * q + 2], silu_f(y2), bf_lo(x1)), o3 = fmaf(accs[4 * q + 3], silu_f(y3), bf_hi(x1));
        sts_u32(a0, pack2(o0, o1));
        sts_u32(a1, pack2(o2, o3));
      }
      fence_async_smem();
      __syncwarp();
      if (lane == 0) {
        asm volatile("cp.async.bulk.tensor.2d.global.shared::cta.bulk_group [%0, {%2, %3}], [%1];"
                     ::"l"(&tm_out), "r"(sb + OFF_XT + warp * 2048), "r"(128 * nt + 64 * khalf), "r"(rb * 128 + warp * 16) : "memory");
        asm volatile("cp.async.bulk.commit_group;" ::: "memory");
        asm volatile("cp.async.bulk.wait_group.read 0;" ::: "memory");
      }
    }
    if (lane == 0) mbar_arrive(bar0 + 8 * BAR_END);
    if (tid == 0) red_inc(&g_done);
  }
}

typedef CUresult (*EncodeFn)(CUtensorMap*, CUtensorMapDataType, cuuint32_t, void*, const cuuint64_t*, const cuuint64_t*,
                             const cuuint32_t*, const cuuint32_t*, CUtensorMapInterleave, CUtensorMapSwizzle,
                             CUtensorMapL2promotion, CUtensorMapFloatOOBfill);

void make_map(EncodeFn enc, CUtensorMap* tm, const void* ptr, int rows, int cols, int box_rows) {
  cuuint64_t gd[2] = {(cuuint64_t)cols, (cuuint64_t)rows};
  cuuint64_t gs[1] = {(cuuint64_t)cols * 2};
  cuuint32_t bd[2] = {64, (cuuint32_t)box_rows};
  cuuint32_t es[2] = {1, 1};
  enc(tm, CU_TENSOR_MAP_DATA_TYPE_BFLOAT16, 2, const_cast<void*>(ptr), gd, gs, bd, es, CU_TENSOR_MAP_INTERLEAVE_NONE,
      CU_TENSOR_MAP_SWIZZLE_128B, CU_TENSOR_MAP_L2_PROMOTION_L2_128B, CU_TENSOR_MAP_FLOAT_OOB_FILL_NONE);
}

}

extern "C" void kernel_launch(void* const* d_in, const int* in_sizes, int n_in, void* d_out, int out_size) {
  const __nv_bfloat16* x = (const __nv_bfloat16*)d_in[0];
  const void* wqkv = d_in[1];
  const void* wo = d_in[2];
  const void* w1 = d_in[4];
  const __nv_bfloat16* b1 = (const __nv_bfloat16*)d_in[5];
  const void* w2 = d_in[6];
  static EncodeFn enc = nullptr;
  if (!enc) {
    cudaDriverEntryPointQueryResult qr;
    void* fn = nullptr;
    cudaGetDriverEntryPoint("cuTensorMapEncodeTiled", &fn, cudaEnableDefault, &qr);
    enc = (EncodeFn)fn;
    cudaFuncSetAttribute(fused_kernel, cudaFuncAttributeMaxDynamicSharedMemorySize, SMEM_ALLOC);
  }
  CUtensorMap tx, tq, t1, t2a, t2b, to, tout;
  make_map(enc, &tx, x, 2048, DM, 128);
  make_map(enc, &tq, wqkv, DM, 3 * DM, 32);
  make_map(enc, &t1, w1, DM, FF, 64);
  make_map(enc, &t2a, w2, FF, DM, 64);
  make_map(enc, &t2b, w2, FF, DM, 48);
  make_map(enc, &to, wo, DM, DM, 64);
  make_map(enc, &tout, d_out, 2048, DM, 16);
  fused_kernel<<<NCTA, 384, SMEM_ALLOC>>>(tx, tq, t1, t2a, t2b, to, tout, (const uint8_t*)wqkv, (const uint8_t*)w1,
                                          (const uint8_t*)w2, (const uint8_t*)wo, b1, (const uint8_t*)x);
}
```
